```python
import torch

def _softmax(x, axis=-1):
    return torch.softmax(x, dim=axis)
def _gelu(x):
    return torch.nn.functional.gelu(x, approximate="tanh")
def _silu(x):
    return torch.nn.functional.silu(x)
def _sigmoid(x):
    return torch.sigmoid(x)
def _layernorm(x, axis=-1, eps=1e-5):
    m = x.mean(dim=axis, keepdim=True)
    v = x.var(dim=axis, keepdim=True, unbiased=False)
    return (x - m) / torch.sqrt(v + eps)
def _scatter_add(tgt, idx, src, axis=0):
    return tgt.clone().index_add_(axis, idx, src)
def _segment_sum(src, seg, n):
    out = torch.zeros((n,) + src.shape[1:], dtype=src.dtype)
    return out.index_add_(0, seg, src)
def _pad(x, pw):
    flat = tuple(v for pair in reversed(pw) for v in pair)
    return torch.nn.functional.pad(x, flat)

kernel_name = 'recurrent_scan__mha_block__glu_gated_swiglu__prompt'

def setup_inputs():

    _w = (lambda a: (lambda t: t.to(torch.bfloat16) if t.is_floating_point() else t)(torch.as_tensor(a)))
    def _A_setup():
        B, S, D, H = 1, 2048, 512, 32
        return {
            "x": _w((lambda *s: torch.randn(*s, dtype=torch.bfloat16) * 0.05)(B, S, D)),
            "wqkv": _w((lambda *s: torch.randn(*s, dtype=torch.bfloat16) * 0.2)(D, 3 * D)),
            "wo": _w((lambda *s: torch.randn(*s, dtype=torch.bfloat16) * 0.2)(D, D)),
        }
    _A_in = _A_setup()

    def _B_setup():
        B, S, D, F = 1, 2048, 512, 1792
        return {
            "x": _w((lambda *s: torch.randn(*s, dtype=torch.bfloat16) * 0.05)(B, S, D)),
            "w1": _w((lambda *s: torch.randn(*s, dtype=torch.bfloat16) * 0.1)(D, F) * (2.0 / D) ** 0.5),
            "w3": _w((lambda *s: torch.randn(*s, dtype=torch.bfloat16) * 0.1)(D, F) * (2.0 / D) ** 0.5),
            "w2": _w((lambda *s: torch.randn(*s, dtype=torch.bfloat16) * 0.1)(F, D) * (2.0 / F) ** 0.5),
        }
    _B_in = _B_setup()

    return {
        "A_x": _A_in["x"],
        "A_wqkv": _A_in["wqkv"],
        "A_wo": _A_in["wo"],
        "B_x": _B_in["x"],
        "B_w1": _B_in["w1"],
        "B_w3": _B_in["w3"],
        "B_w2": _B_in["w2"],
    }

def reference(A_x, A_wqkv, A_wo, B_x, B_w1, B_w3, B_w2):
    def _A_ref(x, wqkv, wo):
        B, S, D = x.shape
        H = 32
        Dh = D // H
        qkv = (lambda x, *d: x.permute(*d))((x @ wqkv).reshape(B, S, 3, H, Dh), 2, 0, 3, 1, 4)
        q, k, v = qkv[0], qkv[1], qkv[2]
        scores = torch.einsum("bhqd,bhkd->bhqk", q, k) * (Dh ** -0.5)
        p = _softmax(scores, axis=-1)
        o = torch.einsum("bhqk,bhkd->bhqd", p, v)
        return (lambda x, *d: x.permute(*d))(o, 0, 2, 1, 3).reshape(B, S, D) @ wo

    def _B_ref(x, w1, w3, w2):
        gate = torch.einsum("bsd,df->bsf", x, w1)
        up = torch.einsum("bsd,df->bsf", x, w3)
        h = _silu(gate) * up
        out = torch.einsum("bsf,fd->bsd", h, w2)
        return out

    x = A_x
    xn = _layernorm(x, axis=-1)
    s = _A_ref(xn, A_wqkv, A_wo)
    g = _silu(_B_ref(xn, B_w1, B_w3, B_w2))
    return x + s * g
```

```cpp
#include <cuda_runtime.h>
#include <cuda_bf16.h>
#include <cuda.h>
#include <stdint.h>

namespace {

constexpr int SEQ = 2048, DM = 512, FF = 1792;

__device__ uint4 g_q[32 * 128 * 32];
__device__ uint4 g_k[32 * 4096];
__device__ uint4 g_v[32 * 4096];
__device__ uint4 g_h[32 * 28 * 512];
__device__ uint4 g_o[32 * 8 * 512];
__device__ unsigned g_ocnt[32];
#define TSTAMP(k, i)

__device__ __forceinline__ uint32_t smem_u32(const void* p) { return (uint32_t)__cvta_generic_to_shared(p); }
__device__ __forceinline__ void mbar_init(uint32_t a, int c) { asm volatile("mbarrier.init.shared::cta.b64 [%0], %1;" :: "r"(a), "r"(c)); }
__device__ __forceinline__ void mbar_expect(uint32_t a, int b) { asm volatile("mbarrier.arrive.expect_tx.shared::cta.b64 _, [%0], %1;" :: "r"(a), "r"(b) : "memory"); }
__device__ __forceinline__ void mbar_arrive(uint32_t a) { asm volatile("mbarrier.arrive.shared::cta.b64 _, [%0];" :: "r"(a) : "memory"); }
__device__ __forceinline__ void mbar_arrive_cluster(uint32_t a, uint32_t cta) {
    asm volatile("{\n.reg .b32 r;\nmapa.shared::cluster.u32 r, %0, %1;\nmbarrier.arrive.release.cluster.shared::cluster.b64 _, [r];\n}" :: "r"(a), "r"(cta) : "memory");
}
__device__ __forceinline__ void mbar_wait(uint32_t a, uint32_t ph) {
    asm volatile("{\n.reg .pred p;\n.reg .u32 n;\nmov.u32 n, 0;\n"
                 "W_LOOP:\nmbarrier.try_wait.parity.shared::cta.b64 p, [%0], %1;\n@p bra W_DONE;\n"
                 "add.u32 n, n, 1;\nsetp.lt.u32 p, n, 4000000;\n@p bra W_LOOP;\ntrap;\nW_DONE:\n}" :: "r"(a), "r"(ph) : "memory");
}
__device__ __forceinline__ void tma2d(uint32_t dst, const CUtensorMap* m, int c0, int c1, uint32_t bar) {
    asm volatile("cp.async.bulk.tensor.2d.shared::cluster.global.mbarrier::complete_tx::bytes [%0], [%1, {%3, %4}], [%2];"
                 :: "r"(dst), "l"(m), "r"(bar), "r"(c0), "r"(c1) : "memory");
}
__device__ __forceinline__ void tma2d_mc(uint32_t dst, const CUtensorMap* m, int c0, int c1, uint32_t bar) {
    asm volatile("cp.async.bulk.tensor.2d.shared::cluster.global.mbarrier::complete_tx::bytes.multicast::cluster [%0], [%1, {%3, %4}], [%2], %5;"
                 :: "r"(dst), "l"(m), "r"(bar), "r"(c0), "r"(c1), "h"((uint16_t)3) : "memory");
}
__device__ __forceinline__ void bulk_load(uint32_t dst, const void* src, int bytes, uint32_t bar) {
    asm volatile("cp.async.bulk.shared::cluster.global.mbarrier::complete_tx::bytes [%0], [%1], %2, [%3];"
                 :: "r"(dst), "l"(src), "r"(bytes), "r"(bar) : "memory");
}
__device__ __forceinline__ void bar_sync(int id, int n) { asm volatile("bar.sync %0, %1;" :: "r"(id), "r"(n) : "memory"); }
__device__ __forceinline__ void fence_async_smem() { asm volatile("fence.proxy.async.shared::cta;" ::: "memory"); }
__device__ __forceinline__ void fence_async_all() { asm volatile("fence.proxy.async;" ::: "memory"); }
__device__ __forceinline__ void wg_fence() { asm volatile("wgmma.fence.sync.aligned;" ::: "memory"); }
__device__ __forceinline__ void wg_commit() { asm volatile("wgmma.commit_group.sync.aligned;" ::: "memory"); }
template <int N> __device__ __forceinline__ void wg_wait() { asm volatile("wgmma.wait_group.sync.aligned %0;" :: "n"(N) : "memory"); }
template <int N> __device__ __forceinline__ void pin(float* d) {
#pragma unroll
    for (int i = 0; i < N; i++) asm volatile("" : "+f"(d[i]) :: "memory");
}
template <int N> __device__ __forceinline__ void pin(uint32_t* d) {
#pragma unroll
    for (int i = 0; i < N; i++) asm volatile("" : "+r"(d[i]) :: "memory");
}
__device__ __forceinline__ uint64_t mkdesc(uint32_t addr, uint32_t lbo, uint32_t sbo, uint32_t swz) {
    return (uint64_t)((addr & 0x3FFFF) >> 4) | ((uint64_t)(lbo >> 4) << 16) | ((uint64_t)(sbo >> 4) << 32) | ((uint64_t)swz << 62);
}
__device__ __forceinline__ float ex2f(float x) { float y; asm("ex2.approx.ftz.f32 %0, %1;" : "=f"(y) : "f"(x)); return y; }
__device__ __forceinline__ float rcpf(float x) { float y; asm("rcp.approx.ftz.f32 %0, %1;" : "=f"(y) : "f"(x)); return y; }
__device__ __forceinline__ uint32_t pack_bf16(float lo, float hi) { uint32_t r; asm("cvt.rn.bf16x2.f32 %0, %1, %2;" : "=r"(r) : "f"(hi), "f"(lo)); return r; }
__device__ __forceinline__ float bf_lo(uint32_t v) { return __uint_as_float(v << 16); }
__device__ __forceinline__ float bf_hi(uint32_t v) { return __uint_as_float(v & 0xFFFF0000u); }
__device__ __forceinline__ float bf_round(float x) { return __bfloat162float(__float2bfloat16_rn(x)); }
__device__ __forceinline__ float siluf(float g) { return g * rcpf(1.0f + ex2f(g * -1.4426950408889634f)); }

__device__ __forceinline__ void wgmma_ss_n256(float* d, uint64_t da, uint64_t db, int acc) {
    asm volatile("{\n.reg .pred p;\nsetp.ne.b32 p, %130, 0;\nwgmma.mma_async.sync.aligned.m64n256k16.f32.bf16.bf16 {"
        "%0,%1,%2,%3,%4,%5,%6,%7,%8,%9,%10,%11,%12,%13,%14,%15,%16,%17,%18,%19,%20,%21,%22,%23,%24,%25,%26,%27,%28,%29,%30,%31,%32,%33,%34,%35,%36,%37,%38,%39,"
        "%40,%41,%42,%43,%44,%45,%46,%47,%48,%49,%50,%51,%52,%53,%54,%55,%56,%57,%58,%59,%60,%61,%62,%63,%64,%65,%66,%67,%68,%69,%70,%71,%72,%73,%74,%75,%76,"
        "%77,%78,%79,%80,%81,%82,%83,%84,%85,%86,%87,%88,%89,%90,%91,%92,%93,%94,%95,%96,%97,%98,%99,%100,%101,%102,%103,%104,%105,%106,%107,%108,%109,%110,"
        "%111,%112,%113,%114,%115,%116,%117,%118,%119,%120,%121,%122,%123,%124,%125,%126,%127"
        "}, %128, %129, p, 1, 1, 0, 1;\n}\n"
        : "+f"(d[0]),"+f"(d[1]),"+f"(d[2]),"+f"(d[3]),"+f"(d[4]),"+f"(d[5]),"+f"(d[6]),"+f"(d[7]),"+f"(d[8]),"+f"(d[9]),"+f"(d[10]),"+f"(d[11]),"+f"(d[12]),
          "+f"(d[13]),"+f"(d[14]),"+f"(d[15]),"+f"(d[16]),"+f"(d[17]),"+f"(d[18]),"+f"(d[19]),"+f"(d[20]),"+f"(d[21]),"+f"(d[22]),"+f"(d[23]),"+f"(d[24]),
          "+f"(d[25]),"+f"(d[26]),"+f"(d[27]),"+f"(d[28]),"+f"(d[29]),"+f"(d[30]),"+f"(d[31]),"+f"(d[32]),"+f"(d[33]),"+f"(d[34]),"+f"(d[35]),"+f"(d[36]),
          "+f"(d[37]),"+f"(d[38]),"+f"(d[39]),"+f"(d[40]),"+f"(d[41]),"+f"(d[42]),"+f"(d[43]),"+f"(d[44]),"+f"(d[45]),"+f"(d[46]),"+f"(d[47]),"+f"(d[48]),
          "+f"(d[49]),"+f"(d[50]),"+f"(d[51]),"+f"(d[52]),"+f"(d[53]),"+f"(d[54]),"+f"(d[55]),"+f"(d[56]),"+f"(d[57]),"+f"(d[58]),"+f"(d[59]),"+f"(d[60]),
          "+f"(d[61]),"+f"(d[62]),"+f"(d[63]),"+f"(d[64]),"+f"(d[65]),"+f"(d[66]),"+f"(d[67]),"+f"(d[68]),"+f"(d[69]),"+f"(d[70]),"+f"(d[71]),"+f"(d[72]),
          "+f"(d[73]),"+f"(d[74]),"+f"(d[75]),"+f"(d[76]),"+f"(d[77]),"+f"(d[78]),"+f"(d[79]),"+f"(d[80]),"+f"(d[81]),"+f"(d[82]),"+f"(d[83]),"+f"(d[84]),
          "+f"(d[85]),"+f"(d[86]),"+f"(d[87]),"+f"(d[88]),"+f"(d[89]),"+f"(d[90]),"+f"(d[91]),"+f"(d[92]),"+f"(d[93]),"+f"(d[94]),"+f"(d[95]),"+f"(d[96]),
          "+f"(d[97]),"+f"(d[98]),"+f"(d[99]),"+f"(d[100]),"+f"(d[101]),"+f"(d[102]),"+f"(d[103]),"+f"(d[104]),"+f"(d[105]),"+f"(d[106]),"+f"(d[107]),
          "+f"(d[108]),"+f"(d[109]),"+f"(d[110]),"+f"(d[111]),"+f"(d[112]),"+f"(d[113]),"+f"(d[114]),"+f"(d[115]),"+f"(d[116]),"+f"(d[117]),"+f"(d[118]),
          "+f"(d[119]),"+f"(d[120]),"+f"(d[121]),"+f"(d[122]),"+f"(d[123]),"+f"(d[124]),"+f"(d[125]),"+f"(d[126]),"+f"(d[127])
        : "l"(da), "l"(db), "r"(acc));
}
__device__ __forceinline__ void wgmma_ss_n128(float* d, uint64_t da, uint64_t db, int acc) {
    asm volatile("{\n.reg .pred p;\nsetp.ne.b32 p, %66, 0;\nwgmma.mma_async.sync.aligned.m64n128k16.f32.bf16.bf16 {"
        "%0,%1,%2,%3,%4,%5,%6,%7,%8,%9,%10,%11,%12,%13,%14,%15,%16,%17,%18,%19,%20,%21,%22,%23,%24,%25,%26,%27,%28,%29,%30,%31,%32,%33,%34,%35,%36,%37,%38,%39,"
        "%40,%41,%42,%43,%44,%45,%46,%47,%48,%49,%50,%51,%52,%53,%54,%55,%56,%57,%58,%59,%60,%61,%62,%63"
        "}, %64, %65, p, 1, 1, 0, 1;\n}\n"
        : "+f"(d[0]),"+f"(d[1]),"+f"(d[2]),"+f"(d[3]),"+f"(d[4]),"+f"(d[5]),"+f"(d[6]),"+f"(d[7]),"+f"(d[8]),"+f"(d[9]),"+f"(d[10]),"+f"(d[11]),"+f"(d[12]),
          "+f"(d[13]),"+f"(d[14]),"+f"(d[15]),"+f"(d[16]),"+f"(d[17]),"+f"(d[18]),"+f"(d[19]),"+f"(d[20]),"+f"(d[21]),"+f"(d[22]),"+f"(d[23]),"+f"(d[24]),
          "+f"(d[25]),"+f"(d[26]),"+f"(d[27]),"+f"(d[28]),"+f"(d[29]),"+f"(d[30]),"+f"(d[31]),"+f"(d[32]),"+f"(d[33]),"+f"(d[34]),"+f"(d[35]),"+f"(d[36]),
          "+f"(d[37]),"+f"(d[38]),"+f"(d[39]),"+f"(d[40]),"+f"(d[41]),"+f"(d[42]),"+f"(d[43]),"+f"(d[44]),"+f"(d[45]),"+f"(d[46]),"+f"(d[47]),"+f"(d[48]),
          "+f"(d[49]),"+f"(d[50]),"+f"(d[51]),"+f"(d[52]),"+f"(d[53]),"+f"(d[54]),"+f"(d[55]),"+f"(d[56]),"+f"(d[57]),"+f"(d[58]),"+f"(d[59]),"+f"(d[60]),
          "+f"(d[61]),"+f"(d[62]),"+f"(d[63])
        : "l"(da), "l"(db), "r"(acc));
}
__device__ __forceinline__ void wgmma_ss_n64(float* d, uint64_t da, uint64_t db, int acc) {
    asm volatile("{\n.reg .pred p;\nsetp.ne.b32 p, %34, 0;\nwgmma.mma_async.sync.aligned.m64n64k16.f32.bf16.bf16 {"
        "%0,%1,%2,%3,%4,%5,%6,%7,%8,%9,%10,%11,%12,%13,%14,%15,%16,%17,%18,%19,%20,%21,%22,%23,%24,%25,%26,%27,%28,%29,%30,%31"
        "}, %32, %33, p, 1, 1, 0, 1;\n}\n"
        : "+f"(d[0]),"+f"(d[1]),"+f"(d[2]),"+f"(d[3]),"+f"(d[4]),"+f"(d[5]),"+f"(d[6]),"+f"(d[7]),"+f"(d[8]),"+f"(d[9]),"+f"(d[10]),"+f"(d[11]),"+f"(d[12]),
          "+f"(d[13]),"+f"(d[14]),"+f"(d[15]),"+f"(d[16]),"+f"(d[17]),"+f"(d[18]),"+f"(d[19]),"+f"(d[20]),"+f"(d[21]),"+f"(d[22]),"+f"(d[23]),"+f"(d[24]),
          "+f"(d[25]),"+f"(d[26]),"+f"(d[27]),"+f"(d[28]),"+f"(d[29]),"+f"(d[30]),"+f"(d[31])
        : "l"(da), "l"(db), "r"(acc));
}
__device__ __forceinline__ void wgmma_rs_n64_zero(float* d, const uint32_t* a, uint64_t db) {
    asm volatile("wgmma.mma_async.sync.aligned.m64n64k16.f32.bf16.bf16 {"
        "%0,%1,%2,%3,%4,%5,%6,%7,%8,%9,%10,%11,%12,%13,%14,%15,%16,%17,%18,%19,%20,%21,%22,%23,%24,%25,%26,%27,%28,%29,%30,%31"
        "}, {%32,%33,%34,%35}, %36, 0, 1, 1, 0;\n"
        : "=f"(d[0]),"=f"(d[1]),"=f"(d[2]),"=f"(d[3]),"=f"(d[4]),"=f"(d[5]),"=f"(d[6]),"=f"(d[7]),"=f"(d[8]),"=f"(d[9]),"=f"(d[10]),"=f"(d[11]),"=f"(d[12]),
          "=f"(d[13]),"=f"(d[14]),"=f"(d[15]),"=f"(d[16]),"=f"(d[17]),"=f"(d[18]),"=f"(d[19]),"=f"(d[20]),"=f"(d[21]),"=f"(d[22]),"=f"(d[23]),"=f"(d[24]),
          "=f"(d[25]),"=f"(d[26]),"=f"(d[27]),"=f"(d[28]),"=f"(d[29]),"=f"(d[30]),"=f"(d[31])
        : "r"(a[0]), "r"(a[1]), "r"(a[2]), "r"(a[3]), "l"(db));
}
__device__ __forceinline__ void wgmma_rs_n64_acc(float* d, const uint32_t* a, uint64_t db) {
    asm volatile("wgmma.mma_async.sync.aligned.m64n64k16.f32.bf16.bf16 {"
        "%0,%1,%2,%3,%4,%5,%6,%7,%8,%9,%10,%11,%12,%13,%14,%15,%16,%17,%18,%19,%20,%21,%22,%23,%24,%25,%26,%27,%28,%29,%30,%31"
        "}, {%32,%33,%34,%35}, %36, 1, 1, 1, 0;\n"
        : "+f"(d[0]),"+f"(d[1]),"+f"(d[2]),"+f"(d[3]),"+f"(d[4]),"+f"(d[5]),"+f"(d[6]),"+f"(d[7]),"+f"(d[8]),"+f"(d[9]),"+f"(d[10]),"+f"(d[11]),"+f"(d[12]),
          "+f"(d[13]),"+f"(d[14]),"+f"(d[15]),"+f"(d[16]),"+f"(d[17]),"+f"(d[18]),"+f"(d[19]),"+f"(d[20]),"+f"(d[21]),"+f"(d[22]),"+f"(d[23]),"+f"(d[24]),
          "+f"(d[25]),"+f"(d[26]),"+f"(d[27]),"+f"(d[28]),"+f"(d[29]),"+f"(d[30]),"+f"(d[31])
        : "r"(a[0]), "r"(a[1]), "r"(a[2]), "r"(a[3]), "l"(db));
}
__device__ __forceinline__ void wgmma_rs_n24_acc(float* d, const uint32_t* a, uint64_t db) {
    asm volatile("wgmma.mma_async.sync.aligned.m64n24k16.f32.bf16.bf16 {"
        "%0,%1,%2,%3,%4,%5,%6,%7,%8,%9,%10,%11"
        "}, {%12,%13,%14,%15}, %16, 1, 1, 1, 1;\n"
        : "+f"(d[0]),"+f"(d[1]),"+f"(d[2]),"+f"(d[3]),"+f"(d[4]),"+f"(d[5]),"+f"(d[6]),"+f"(d[7]),"+f"(d[8]),"+f"(d[9]),"+f"(d[10]),"+f"(d[11])
        : "r"(a[0]), "r"(a[1]), "r"(a[2]), "r"(a[3]), "l"(db));
}
__device__ __forceinline__ void wgmma_rs_n24_zero(float* d, const uint32_t* a, uint64_t db) {
    asm volatile("wgmma.mma_async.sync.aligned.m64n24k16.f32.bf16.bf16 {"
        "%0,%1,%2,%3,%4,%5,%6,%7,%8,%9,%10,%11"
        "}, {%12,%13,%14,%15}, %16, 0, 1, 1, 1;\n"
        : "=f"(d[0]),"=f"(d[1]),"=f"(d[2]),"=f"(d[3]),"=f"(d[4]),"=f"(d[5]),"=f"(d[6]),"=f"(d[7]),"=f"(d[8]),"=f"(d[9]),"=f"(d[10]),"=f"(d[11])
        : "r"(a[0]), "r"(a[1]), "r"(a[2]), "r"(a[3]), "l"(db));
}

constexpr int K1_STAGES = 6, K1_STAGE_BYTES = 16384;
constexpr int K1_SMEM = 131072 + K1_STAGES * K1_STAGE_BYTES + 1024 + 128;

template <int N> __device__ __forceinline__ void k1_mainloop(float* acc, uint32_t sA, uint32_t sB, uint32_t bars, int& st, uint32_t& ph, int tid_wg) {
    constexpr int NST = N / 16, KPS = 512 / NST / 16;
    int prev = -1;
#pragma unroll 1
    for (int s = 0; s < NST; s++) {
        mbar_wait(bars + 8 * st, ph);
        const uint64_t db = mkdesc(sB + st * K1_STAGE_BYTES, N == 256 ? 4096 : 8192, 1024, 1);
        const int k0 = s * KPS;
        const uint64_t da = mkdesc(sA + (k0 >> 2) * 16384 + (k0 & 3) * 32, 16, 1024, 1);
        wg_fence();
#pragma unroll
        for (int k = 0; k < KPS; k++) {
            if (N == 256) wgmma_ss_n256(acc, da + k * 2, db + k * 128, (s | k) != 0);
            else          wgmma_ss_n128(acc, da + k * 2, db + k * 128, (s | k) != 0);
        }
        wg_commit();
        if (prev >= 0) {
            wg_wait<1>();
            if (tid_wg < 2) mbar_arrive_cluster(bars + 8 * (K1_STAGES + prev), tid_wg);
        }
        prev = st;
        if (++st == K1_STAGES) { st = 0; ph ^= 1; }
    }
    wg_wait<0>();
    if (tid_wg < 2) mbar_arrive_cluster(bars + 8 * (K1_STAGES + prev), tid_wg);
    pin<N / 2>(acc);
}

__global__ void __cluster_dims__(2, 1, 1) __launch_bounds__(384, 1)
k1_ln_gemm(const __nv_bfloat16* __restrict__ x, const __grid_constant__ CUtensorMap mqkv, const __grid_constant__ CUtensorMap mw1,
           const __grid_constant__ CUtensorMap mw3) {
    extern __shared__ uint8_t smem_raw[];
    const uint32_t sA = (smem_u32(smem_raw) + 1023) & ~1023u;
    const uint32_t sB = sA + 131072;
    const uint32_t bars = sB + K1_STAGES * K1_STAGE_BYTES;
    const int tid = threadIdx.x, lane = tid & 31;
    const int wg = __shfl_sync(0xffffffffu, tid >> 7, 0);
    const int rank = blockIdx.x & 1, grp = (blockIdx.x >> 1) & 7, mblk = (blockIdx.x >> 4) * 2 + rank;
    const bool typeA = grp < 4;
    const int qb0 = typeA ? 4 * grp : 8 + 2 * grp;
    const int gu0 = typeA ? 3 * grp : 4 * grp - 4;

    if (tid == 0) {
        TSTAMP(0, 0);
        for (int i = 0; i < K1_STAGES; i++) { mbar_init(bars + 8 * i, 1); mbar_init(bars + 8 * (K1_STAGES + i), 4); }
        asm volatile("fence.mbarrier_init.release.cluster;" ::: "memory");
    }
    if (blockIdx.x == 0 && tid < 32) g_ocnt[tid] = 0;
    asm volatile("barrier.cluster.arrive.aligned;" ::: "memory");

    if (wg == 2) {
        asm volatile("barrier.cluster.wait.aligned;" ::: "memory");
        if (tid == 256) {
            int st = 0; uint32_t ph = 1;
            for (int t = 0; t < 3; t++) {
                const bool n256 = typeA ? (t < 2) : (t > 0);
                const CUtensorMap *m0, *m1; int c0, c1;
                if (t == 0) {
                    m0 = m1 = &mqkv;
                    c0 = n256 ? 64 * (qb0 + 2 * rank) : 64 * (qb0 + rank);
                    c1 = n256 ? c0 + 64 : c0;
                } else {
                    const int u = gu0 + 2 * (t - 1);
                    if (n256) { m0 = &mw1; m1 = &mw3; c0 = c1 = 64 * (u + rank); }
                    else      { m0 = m1 = rank ? &mw3 : &mw1; c0 = c1 = 64 * u; }
                }
                const int nst = n256 ? 16 : 8, kstep = n256 ? 32 : 64, k1off = n256 ? 0 : 32;
                for (int s = 0; s < nst; s++) {
                    mbar_wait(bars + 8 * (K1_STAGES + st), ph);
                    mbar_expect(bars + 8 * st, K1_STAGE_BYTES);
                    const uint32_t dst = sB + st * K1_STAGE_BYTES + rank * 8192;
                    tma2d_mc(dst, m0, c0, s * kstep, bars + 8 * st);
                    tma2d_mc(dst + 4096, m1, c1, s * kstep + k1off, bars + 8 * st);
                    if (++st == K1_STAGES) { st = 0; ph ^= 1; }
                }
            }
        }
    } else {
        const int warp = tid >> 5, g = lane >> 2, t4 = lane & 3;
        {
            uint4 xv[2][16];
            const int r0 = warp * 16 + g;
#pragma unroll
            for (int rr = 0; rr < 2; rr++) {
                const uint4* src = reinterpret_cast<const uint4*>(x + (size_t)(mblk * 128 + r0 + rr * 8) * DM);
#pragma unroll
                for (int j = 0; j < 16; j++) xv[rr][j] = __ldg(src + ((j ^ (g & 1)) * 4 + t4));
            }
#pragma unroll
            for (int rr = 0; rr < 2; rr++) {
                uint32_t* w = reinterpret_cast<uint32_t*>(xv[rr]);
                float s0 = 0.f, s1 = 0.f;
#pragma unroll
                for (int j = 0; j < 64; j++) { s0 += bf_lo(w[j]); s1 += bf_hi(w[j]); }
                s0 += s1;
                s0 += __shfl_xor_sync(0xffffffffu, s0, 1); s0 += __shfl_xor_sync(0xffffffffu, s0, 2);
                const float mean = s0 * (1.0f / DM);
                float v0 = 0.f, v1 = 0.f;
#pragma unroll
                for (int j = 0; j < 64; j++) { const float a = bf_lo(w[j]) - mean, b = bf_hi(w[j]) - mean; v0 = fmaf(a, a, v0); v1 = fmaf(b, b, v1); }
                v0 += v1;
                v0 += __shfl_xor_sync(0xffffffffu, v0, 1); v0 += __shfl_xor_sync(0xffffffffu, v0, 2);
                const float sd = bf_round(sqrtf(bf_round(bf_round(v0 * (1.0f / DM)) + 1e-5f)));
                const float rinv = 1.0f / sd;
                const float rhi = bf_round(rinv);
                const uint32_t nm2 = pack_bf16(-mean, -mean), rh2 = pack_bf16(rhi, rhi), rl2 = pack_bf16(rinv - rhi, rinv - rhi);
#pragma unroll
                for (int j = 0; j < 64; j++) {
                    uint32_t d, e;
                    asm("add.rn.bf16x2 %0, %1, %2;" : "=r"(d) : "r"(w[j]), "r"(nm2));
                    asm("mul.rn.bf16x2 %0, %1, %2;" : "=r"(e) : "r"(d), "r"(rl2));
                    asm("fma.rn.bf16x2 %0, %1, %2, %3;" : "=r"(w[j]) : "r"(d), "r"(rh2), "r"(e));
                }
                const int r = r0 + rr * 8;
#pragma unroll
                for (int j = 0; j < 16; j++) {
                    const int c = (j ^ (g & 1)) * 4 + t4;
                    const uint32_t a = sA + (c >> 3) * 16384 + r * 128 + (((c & 7) ^ g) << 4);
                    asm volatile("st.shared.v4.b32 [%0], {%1,%2,%3,%4};" :: "r"(a), "r"(xv[rr][j].x), "r"(xv[rr][j].y), "r"(xv[rr][j].z), "r"(xv[rr][j].w) : "memory");
                }
            }
            fence_async_smem();
            bar_sync(1 + wg, 128);
        }
        asm volatile("barrier.cluster.wait.aligned;" ::: "memory");
        if (tid == 0) TSTAMP(0, 1);

        float acc[128];
        int st = 0; uint32_t ph = 0;
        const int wq = warp & 3, rowblk = mblk * 2 + wg;
#pragma unroll 1
        for (int t = 0; t < 3; t++) {
            const bool n256 = typeA ? (t < 2) : (t > 0);
            if (n256) k1_mainloop<256>(acc, sA + wg * 8192, sB, bars, st, ph, tid & 127);
            else      k1_mainloop<128>(acc, sA + wg * 8192, sB, bars, st, ph, tid & 127);
            if (tid == 0) TSTAMP(0, 2 + 2 * t);
            if (t == 0) {
                const int tile16 = rowblk * 4 + wq;
#pragma unroll
                for (int hh = 0; hh < 16; hh++) {
                    if (hh < 8 || n256) {
                        const int head = (qb0 * 4 + hh) & 31;
                        const float* a = acc + hh * 8;
                        if (qb0 < 8) {
                            const float sc = 5.421010862427522e-20f;
                            g_q[(head * 128 + tile16) * 32 + lane] = make_uint4(pack_bf16(a[0] * sc, a[1] * sc), pack_bf16(a[2] * sc, a[3] * sc),
                                                                                pack_bf16(a[4] * sc, a[5] * sc), pack_bf16(a[6] * sc, a[7] * sc));
                        } else {
                            uint32_t* p; int s8, sh;
                            if (qb0 < 16) { p = reinterpret_cast<uint32_t*>(g_k + head * 4096) + tile16 * 128 + lane; s8 = 64; sh = 32; }
                            else          { p = reinterpret_cast<uint32_t*>(g_v + head * 4096) + tile16 * 64 + lane;  s8 = 32; sh = 8192; }
                            p[0] = pack_bf16(a[0], a[1]); p[s8] = pack_bf16(a[2], a[3]);
                            p[sh] = pack_bf16(a[4], a[5]); p[sh + s8] = pack_bf16(a[6], a[7]);
                        }
                    }
                }
                __threadfence();
                bar_sync(3, 256);
                if (tid == 0) asm volatile("griddepcontrol.launch_dependents;" ::: "memory");
            } else {
#pragma unroll
                for (int u = 0; u < 2; u++) {
                    if (u == 0 || n256) {
                        uint32_t* p = reinterpret_cast<uint32_t*>(g_h + (rowblk * 28 + gu0 + 2 * (t - 1) + u) * 512) + wq * 512 + lane;
#pragma unroll
                        for (int j = 0; j < 8; j++) {
                            const float* ga = acc + u * 64 + j * 4; const float* up = ga + 32;
                            p[j * 32] = pack_bf16(siluf(ga[0]) * up[0], siluf(ga[1]) * up[1]);
                            p[256 + j * 32] = pack_bf16(siluf(ga[2]) * up[2], siluf(ga[3]) * up[3]);
                        }
                    }
                }
            }
            if (tid == 0) TSTAMP(0, 3 + 2 * t);
        }
    }
    __syncwarp();
    asm volatile("barrier.cluster.arrive.aligned;\nbarrier.cluster.wait.aligned;" ::: "memory");
}

constexpr int K2_OFF_ONES = 131072;
constexpr int K2_OFF_RING = K2_OFF_ONES + 4096;
constexpr int K2_RING = 5;
constexpr int K2_OFF_BARS = K2_OFF_RING + K2_RING * 16384;
constexpr int K2_SMEM = K2_OFF_BARS + 256 + 1024;

__device__ __forceinline__ uint32_t exp2_fixed(float lo, float hi, uint32_t half2) {
    uint32_t y, g, d;
    asm("cvt.pack.sat.s16.s32 %0, %1, %2;" : "=r"(y) : "r"(__float_as_uint(hi)), "r"(__float_as_uint(lo)));
    asm("lop3.b32 %0, %1, 0x007F007F, %2, 0xEA;" : "=r"(g) : "r"(y), "r"(half2));
    asm("fma.rn.bf16x2 %0, %1, %2, %3;" : "=r"(d) : "r"(y), "r"(g), "r"(y & 0xFF80FF80u));
    return d;
}
constexpr float C_MUFU = 0.25f * 1.4426950408889634f * 18446744073709551616.0f;
constexpr float C_FIX = 0.25f * 1.4426950408889634f * 3.308722450212111e-24f;

__device__ __forceinline__ void softmax_tile(const float* s, uint32_t* p, const float* bm, const float* bf, uint32_t half2) {
#pragma unroll
    for (int i = 0; i < 16; i++) {
        const int r = i & 1;
        if (((i * 5) & 7) < 5) p[i] = exp2_fixed(fmaf(s[2 * i], C_FIX, bf[r]), fmaf(s[2 * i + 1], C_FIX, bf[r]), half2);
        else                   p[i] = pack_bf16(ex2f(fmaf(s[2 * i], C_MUFU, bm[r])), ex2f(fmaf(s[2 * i + 1], C_MUFU, bm[r])));
    }
}
__device__ __forceinline__ uint32_t k_tile_addr(uint32_t base, int tile) {
    const int c = tile >> 2;
    return base + ((tile & 2) ? 98304 + c * 4096 : (2 * c + 1) * 4096) + (tile & 1) * 2048;
}

__global__ void __launch_bounds__(640, 1)
k2_attn(const __nv_bfloat16* __restrict__ x, __nv_bfloat16* __restrict__ out, const __grid_constant__ CUtensorMap mw2,
        const __grid_constant__ CUtensorMap mwo, uint32_t half2) {
    extern __shared__ uint8_t smem_raw[];
    const uint32_t sb = (smem_u32(smem_raw) + 1023) & ~1023u;
    const uint32_t bars = sb + K2_OFF_BARS;
    const uint32_t bar_ring = bars + 64, bar_o = bars + 64 + 8 * K2_RING;
    const uint32_t bar_done = bar_o + 64;
    const int tid = threadIdx.x, lane = tid & 31;
    const int wg = __shfl_sync(0xffffffffu, tid >> 7, 0);
    const int head = blockIdx.x >> 2, qb = blockIdx.x & 3;

    if (tid == 0) {
        TSTAMP(1, 0);
        for (int i = 0; i < 8 + K2_RING + 8; i++) mbar_init(bars + 8 * i, 1);
        mbar_init(bar_done, 4);
        asm volatile("fence.mbarrier_init.release.cluster;" ::: "memory");
    }
    if (tid < 256) asm volatile("st.shared.v4.b32 [%0], {%1,%1,%1,%1};" :: "r"(sb + K2_OFF_ONES + tid * 16), "r"(0x3F803F80u) : "memory");
    fence_async_smem();
    __syncthreads();

    if (wg < 4) {
        if (tid < 32) {
            fence_async_all();
            const int c = lane >> 2, part = lane & 3;
            if (part == 0) mbar_expect(bars + 8 * c, 16384);
            __syncwarp();
            const uint8_t* src = part < 2 ? reinterpret_cast<const uint8_t*>(g_k + head * 4096) + (2 * c + part) * 4096
                                          : reinterpret_cast<const uint8_t*>(g_v + head * 4096) + (part - 2) * 32768 + c * 4096;
            const uint32_t dst = part == 0 ? (2 * c + 1) * 4096 : part == 1 ? 98304 + c * 4096 : part == 2 ? 2 * c * 4096 : 65536 + c * 4096;
            bulk_load(sb + dst, src, 4096, bars + 8 * c);
        }
        const int wq = (tid >> 5) & 3;
#pragma unroll 1
        for (int round = 0; round < 2; round++) {
            const int rowblk = qb * 8 + round * 4 + wg;
            uint32_t q[4];
            { const uint4 v = __ldcg(g_q + (head * 128 + rowblk * 4 + wq) * 32 + lane); q[0] = v.x; q[1] = v.y; q[2] = v.z; q[3] = v.w; }
            float o[12];
            int nmax = 1;
#pragma unroll 1
            for (;;) {
                float s[32]; uint32_t p[16];
                float m0 = -INFINITY, m1 = -INFINITY;
                mbar_wait(bars, 0);
#pragma unroll 1
                for (int t = 0; t < nmax; t++) {
                    wg_fence();
                    wgmma_rs_n64_zero(s, q, mkdesc(k_tile_addr(sb, t), 128, 256, 0));
                    wg_commit();
                    wg_wait<0>();
                    pin<32>(s);
#pragma unroll
                    for (int i = 0; i < 8; i++) { m0 = fmaxf(m0, fmaxf(s[4 * i], s[4 * i + 1])); m1 = fmaxf(m1, fmaxf(s[4 * i + 2], s[4 * i + 3])); }
                }
                m0 = fmaxf(m0, __shfl_xor_sync(0xffffffffu, m0, 1)); m0 = fmaxf(m0, __shfl_xor_sync(0xffffffffu, m0, 2));
                m1 = fmaxf(m1, __shfl_xor_sync(0xffffffffu, m1, 1)); m1 = fmaxf(m1, __shfl_xor_sync(0xffffffffu, m1, 2));
                m0 = rintf(m0 * C_MUFU); m1 = rintf(m1 * C_MUFU);
                float bm[2] = {-79.41395f - m0, -79.41395f - m1};
                float bf[2] = {(47.0f - m0) * 4.235164736271502e-22f * 4.235164736271502e-22f, (47.0f - m1) * 4.235164736271502e-22f * 4.235164736271502e-22f};
#pragma unroll
                for (int i = 0; i < 12; i++) o[i] = 0.f;
                pin<12>(o);
                if (tid == 0) TSTAMP(1, 1 + 2 * round);
#pragma unroll 1
                for (int c = 0; c < 8; c++) {
                    mbar_wait(bars + 8 * c, 0);
                    const uint64_t dk0 = mkdesc(sb + (2 * c + 1) * 4096, 128, 256, 0), dk1 = mkdesc(sb + 98304 + c * 4096, 128, 256, 0);
                    const uint64_t dv = mkdesc(sb + 2 * c * 4096, 128, 65536 - c * 4096, 0);
#pragma unroll
                    for (int t = 0; t < 4; t++) {
                        wg_fence();
                        wgmma_rs_n64_zero(s, q, (t & 2 ? dk1 : dk0) + (t & 1) * 128);
                        wg_commit();
                        wg_wait<0>();
                        pin<32>(s); pin<16>(p);
                        softmax_tile(s, p, bm, bf, half2);
                        wg_fence();
#pragma unroll
                        for (int k = 0; k < 4; k++) wgmma_rs_n24_acc(o, p + 4 * k, dv + (t * 4 + k) * 16);
                        wg_commit();
                    }
                }
                wg_wait<0>();
                pin<12>(o);
                float chk = 0.f;
#pragma unroll
                for (int i = 0; i < 12; i++) chk = fmaf(o[i], 0.f, chk);
                uint32_t bad;
                asm volatile("{\n.reg .pred p, q;\nsetp.neu.f32 q, %1, 0f00000000;\nbar.red.or.pred p, %2, 128, q;\nselp.u32 %0, 1, 0, p;\n}" : "=r"(bad) : "f"(chk), "r"(1 + wg) : "memory");
                if (!bad || nmax != 1) break;
                nmax = 32;
            }
            const float r0 = 1.0f / o[8], r1 = 1.0f / o[10];
            uint32_t* po = reinterpret_cast<uint32_t*>(g_o + (rowblk * 8 + (head >> 2)) * 512) + wq * 512 + (head & 3) * 64 + lane;
            po[0] = pack_bf16(o[0] * r0, o[1] * r0); po[256] = pack_bf16(o[2] * r1, o[3] * r1);
            po[32] = pack_bf16(o[4] * r0, o[5] * r0); po[288] = pack_bf16(o[6] * r1, o[7] * r1);
            __threadfence();
            bar_sync(1 + wg, 128);
            if ((tid & 127) == 0) {
                asm volatile("red.release.gpu.global.add.u32 [%0], 1;" :: "l"(g_ocnt + rowblk) : "memory");
                if (round == 1) mbar_arrive(bar_done);
            }
            if (tid == 0) TSTAMP(1, 2 + 2 * round);
        }
    } else {
        const int wq = (tid >> 5) & 3, g = lane >> 2, t4 = lane & 3;
        const bool lead = (tid & 127) == 0;
        const int cb = blockIdx.x & 7, pr = blockIdx.x >> 3;
        const int rb0 = (pr >> 2) * 8 + (pr & 3);
        const uint32_t ring = sb + K2_OFF_RING;
        uint32_t gate[2][16];
        float acc[32];
        asm volatile("griddepcontrol.wait;" ::: "memory");
        if (lead) {
            TSTAMP(1, 8);
            fence_async_all();
            for (int i = 0; i < K2_RING; i++) {
                mbar_expect(bar_ring + 8 * i, 16384);
                bulk_load(ring + i * 16384, g_h + (rb0 * 28 + i) * 512, 8192, bar_ring + 8 * i);
                tma2d(ring + i * 16384 + 8192, &mw2, cb * 64, i * 64, bar_ring + 8 * i);
            }
        }
        int st = 0; uint32_t ph = 0;
#pragma unroll
        for (int tl = 0; tl < 2; tl++) {
#pragma unroll 1
            for (int kb = 0; kb < 28; kb++) {
                mbar_wait(bar_ring + 8 * st, ph);
                const uint64_t da = mkdesc(ring + st * 16384, 128, 1024, 0), db = mkdesc(ring + st * 16384 + 8192, 8192, 1024, 1);
                wg_fence();
#pragma unroll
                for (int k = 0; k < 4; k++) wgmma_ss_n64(acc, da + k * 16, db + k * 128, (kb | k) != 0);
                wg_commit();
                wg_wait<0>();
                bar_sync(5, 128);
                const int nx = tl * 28 + kb + K2_RING;
                if (lead && nx < 56) {
                    const int ntl = nx >= 28, nkb = nx - ntl * 28;
                    mbar_expect(bar_ring + 8 * st, 16384);
                    bulk_load(ring + st * 16384, g_h + ((rb0 + 4 * ntl) * 28 + nkb) * 512, 8192, bar_ring + 8 * st);
                    tma2d(ring + st * 16384 + 8192, &mw2, cb * 64, nkb * 64, bar_ring + 8 * st);
                }
                if (++st == K2_RING) { st = 0; ph ^= 1; }
            }
            pin<32>(acc);
#pragma unroll
            for (int i = 0; i < 16; i++) gate[tl][i] = pack_bf16(siluf(acc[2 * i]), siluf(acc[2 * i + 1]));
        }
        if (lead) TSTAMP(1, 9);
        const uint32_t bar_wo = bar_ring + 8 * st;
        if (lead) {
            mbar_expect(bar_wo, 65536);
            for (int i = 0; i < 8; i++) tma2d(ring + i * 8192, &mwo, cb * 64, i * 64, bar_wo);
        }
#pragma unroll
        for (int tl = 0; tl < 2; tl++) {
            const int rb = rb0 + 4 * tl;
            uint32_t xr[16];
            const uint32_t* px = reinterpret_cast<const uint32_t*>(x + (size_t)(rb * 64 + wq * 16 + g) * DM + cb * 64) + t4;
#pragma unroll
            for (int j = 0; j < 8; j++) { xr[2 * j] = __ldg(px + j * 4); xr[2 * j + 1] = __ldg(px + 8 * DM / 2 + j * 4); }
            if (lead) {
                unsigned v; int n = 0;
                do { asm volatile("ld.acquire.gpu.global.u32 %0, [%1];" : "=r"(v) : "l"(g_ocnt + rb) : "memory"); if (v >= 32) break; __nanosleep(tl ? 20 : 200); } while (++n < 4000000);
                if (v < 32) __trap();
                fence_async_all();
                TSTAMP(1, 10 + 2 * tl);
                if (tl == 0) {
                    for (int i = 0; i < 2; i++) { mbar_expect(bar_o + 8 * i, 8192); bulk_load(ring + 65536 + i * 8192, g_o + (rb * 8 + i) * 512, 8192, bar_o + 8 * i); }
                } else {
                    mbar_wait(bar_done, 0);
                    for (int i = 0; i < 8; i++) { mbar_expect(bar_o + 8 * i, 8192); bulk_load(sb + i * 8192, g_o + (rb * 8 + i) * 512, 8192, bar_o + 8 * i); }
                }
            }
            if (tl == 0) mbar_wait(bar_wo, ph);
#pragma unroll 1
            for (int kb = 0; kb < 8; kb++) {
                mbar_wait(bar_o + 8 * kb, tl);
                const uint32_t a = tl == 0 ? ring + 65536 + (kb & 1) * 8192 : sb + kb * 8192;
                const uint64_t da = mkdesc(a, 128, 1024, 0), db = mkdesc(ring + kb * 8192, 8192, 1024, 1);
                wg_fence();
#pragma unroll
                for (int k = 0; k < 4; k++) wgmma_ss_n64(acc, da + k * 16, db + k * 128, (kb | k) != 0);
                wg_commit();
                if (tl == 0) {
                    wg_wait<0>();
                    bar_sync(5, 128);
                    if (lead && kb < 6) { mbar_expect(bar_o + 8 * (kb + 2), 8192); bulk_load(a, g_o + (rb * 8 + kb + 2) * 512, 8192, bar_o + 8 * (kb + 2)); }
                }
            }
            wg_wait<0>();
            pin<32>(acc);
            uint32_t* po = reinterpret_cast<uint32_t*>(out + (size_t)(rb * 64 + wq * 16 + g) * DM + cb * 64) + t4;
#pragma unroll
            for (int i = 0; i < 16; i++) {
                const uint32_t r = pack_bf16(fmaf(acc[2 * i], bf_lo(gate[tl][i]), bf_lo(xr[i])), fmaf(acc[2 * i + 1], bf_hi(gate[tl][i]), bf_hi(xr[i])));
                po[(i & 1) * (8 * DM / 2) + (i >> 1) * 4] = r;
            }
            if (lead) TSTAMP(1, 11 + 2 * tl);
        }
    }
}

typedef CUresult (*EncodeFn)(CUtensorMap*, CUtensorMapDataType, cuuint32_t, void*, const cuuint64_t*, const cuuint64_t*, const cuuint32_t*,
                             const cuuint32_t*, CUtensorMapInterleave, CUtensorMapSwizzle, CUtensorMapL2promotion, CUtensorMapFloatOOBfill);

void make_map(EncodeFn fn, CUtensorMap* m, const void* p, int rows, int cols, int box_rows) {
    cuuint64_t dims[2] = {(cuuint64_t)cols, (cuuint64_t)rows};
    cuuint64_t strides[1] = {(cuuint64_t)cols * 2};
    cuuint32_t box[2] = {64, (cuuint32_t)box_rows};
    cuuint32_t es[2] = {1, 1};
    fn(m, CU_TENSOR_MAP_DATA_TYPE_BFLOAT16, 2, const_cast<void*>(p), dims, strides, box, es, CU_TENSOR_MAP_INTERLEAVE_NONE,
       CU_TENSOR_MAP_SWIZZLE_128B, CU_TENSOR_MAP_L2_PROMOTION_L2_128B, CU_TENSOR_MAP_FLOAT_OOB_FILL_NONE);
}

}

extern "C" void kernel_launch(void* const* d_in, const int* in_sizes, int n_in, void* d_out, int out_size) {
    const __nv_bfloat16* x = (const __nv_bfloat16*)d_in[0];
    static EncodeFn fn = nullptr;
    if (!fn) {
        cudaDriverEntryPointQueryResult qr;
        cudaGetDriverEntryPoint("cuTensorMapEncodeTiled", (void**)&fn, cudaEnableDefault, &qr);
        cudaFuncSetAttribute(k1_ln_gemm, cudaFuncAttributeMaxDynamicSharedMemorySize, K1_SMEM);
        cudaFuncSetAttribute(k2_attn, cudaFuncAttributeMaxDynamicSharedMemorySize, K2_SMEM);
    }
    CUtensorMap mqkv, mw1, mw3, mw2, mwo;
    make_map(fn, &mqkv, d_in[1], DM, 3 * DM, 32);
    make_map(fn, &mwo, d_in[2], DM, DM, 64);
    make_map(fn, &mw1, d_in[4], DM, FF, 32);
    make_map(fn, &mw3, d_in[5], DM, FF, 32);
    make_map(fn, &mw2, d_in[6], FF, DM, 64);

    k1_ln_gemm<<<128, 384, K1_SMEM, cudaStreamPerThread>>>(x, mqkv, mw1, mw3);

    cudaLaunchConfig_t cfg = {};
    cfg.gridDim = 128; cfg.blockDim = 640; cfg.dynamicSmemBytes = K2_SMEM; cfg.stream = cudaStreamPerThread;
    cudaLaunchAttribute at[1];
    at[0].id = cudaLaunchAttributeProgrammaticStreamSerialization; at[0].val.programmaticStreamSerializationAllowed = 1;
    cfg.attrs = at; cfg.numAttrs = 1;
    cudaLaunchKernelEx(&cfg, k2_attn, x, (__nv_bfloat16*)d_out, mw2, mwo, 0x3F003F00u);
}
```

```cpp
#include <cuda_runtime.h>
#include <cuda_bf16.h>
#include <cuda.h>
#include <stdint.h>

namespace {

constexpr int SEQ = 2048, DM = 512, FF = 1792;

__device__ uint4 g_q[32 * 128 * 32];
__device__ uint4 g_k[32 * 4096];
__device__ uint4 g_v[32 * 4096];
__device__ uint4 g_h[32 * 28 * 512];
__device__ uint4 g_o[32 * 8 * 512];
__device__ unsigned g_ocnt[32];
#define TSTAMP(k, i)

__device__ __forceinline__ uint32_t smem_u32(const void* p) { return (uint32_t)__cvta_generic_to_shared(p); }
__device__ __forceinline__ void mbar_init(uint32_t a, int c) { asm volatile("mbarrier.init.shared::cta.b64 [%0], %1;" :: "r"(a), "r"(c)); }
__device__ __forceinline__ void mbar_expect(uint32_t a, int b) { asm volatile("mbarrier.arrive.expect_tx.shared::cta.b64 _, [%0], %1;" :: "r"(a), "r"(b) : "memory"); }
__device__ __forceinline__ void mbar_arrive(uint32_t a) { asm volatile("mbarrier.arrive.shared::cta.b64 _, [%0];" :: "r"(a) : "memory"); }
__device__ __forceinline__ void mbar_arrive_cluster(uint32_t a, uint32_t cta) {
    asm volatile("{\n.reg .b32 r;\nmapa.shared::cluster.u32 r, %0, %1;\nmbarrier.arrive.shared::cluster.b64 _, [r];\n}" :: "r"(a), "r"(cta) : "memory");
}
__device__ __forceinline__ bool mbar_try(uint32_t a, uint32_t ph) {
    uint32_t ok;
    asm volatile("{\n.reg .pred p;\nmbarrier.try_wait.parity.shared::cta.b64 p, [%1], %2;\nselp.u32 %0, 1, 0, p;\n}" : "=r"(ok) : "r"(a), "r"(ph) : "memory");
    return ok;
}
__device__ __forceinline__ void mbar_wait(uint32_t a, uint32_t ph) {
    for (int n = 0; !__all_sync(0xffffffffu, mbar_try(a, ph)); n++) if (n > 4000000) __trap();
}
__device__ __forceinline__ bool elect_one() {
    uint32_t p;
    asm volatile("{\n.reg .pred P;\nelect.sync _|P, 0xffffffff;\nselp.u32 %0, 1, 0, P;\n}" : "=r"(p));
    return p;
}
__device__ __forceinline__ void tma2d(uint32_t dst, const CUtensorMap* m, int c0, int c1, uint32_t bar) {
    asm volatile("cp.async.bulk.tensor.2d.shared::cluster.global.mbarrier::complete_tx::bytes [%0], [%1, {%3, %4}], [%2];"
                 :: "r"(dst), "l"(m), "r"(bar), "r"(c0), "r"(c1) : "memory");
}
__device__ __forceinline__ void tma2d_mc(uint32_t dst, const CUtensorMap* m, int c0, int c1, uint32_t bar) {
    asm volatile("cp.async.bulk.tensor.2d.shared::cluster.global.mbarrier::complete_tx::bytes.multicast::cluster [%0], [%1, {%3, %4}], [%2], %5;"
                 :: "r"(dst), "l"(m), "r"(bar), "r"(c0), "r"(c1), "h"((uint16_t)3) : "memory");
}
__device__ __forceinline__ void bulk_load(uint32_t dst, const void* src, int bytes, uint32_t bar) {
    asm volatile("cp.async.bulk.shared::cluster.global.mbarrier::complete_tx::bytes [%0], [%1], %2, [%3];"
                 :: "r"(dst), "l"(src), "r"(bytes), "r"(bar) : "memory");
}
__device__ __forceinline__ void bar_sync(int id, int n) { asm volatile("bar.sync %0, %1;" :: "r"(id), "r"(n) : "memory"); }
__device__ __forceinline__ void fence_async_smem() { asm volatile("fence.proxy.async.shared::cta;" ::: "memory"); }
__device__ __forceinline__ void fence_async_all() { asm volatile("fence.proxy.async;" ::: "memory"); }
__device__ __forceinline__ void wg_fence() { asm volatile("wgmma.fence.sync.aligned;" ::: "memory"); }
__device__ __forceinline__ void wg_commit() { asm volatile("wgmma.commit_group.sync.aligned;" ::: "memory"); }
template <int N> __device__ __forceinline__ void wg_wait() { asm volatile("wgmma.wait_group.sync.aligned %0;" :: "n"(N) : "memory"); }
template <int N> __device__ __forceinline__ void pin(float* d) {
#pragma unroll
    for (int i = 0; i < N; i++) asm volatile("" : "+f"(d[i]) :: "memory");
}
template <int N> __device__ __forceinline__ void pin(uint32_t* d) {
#pragma unroll
    for (int i = 0; i < N; i++) asm volatile("" : "+r"(d[i]) :: "memory");
}
__device__ __forceinline__ uint64_t mkdesc(uint32_t addr, uint32_t lbo, uint32_t sbo, uint32_t swz) {
    return (uint64_t)((addr & 0x3FFFF) >> 4) | ((uint64_t)(lbo >> 4) << 16) | ((uint64_t)(sbo >> 4) << 32) | ((uint64_t)swz << 62);
}
__device__ __forceinline__ float ex2f(float x) { float y; asm("ex2.approx.ftz.f32 %0, %1;" : "=f"(y) : "f"(x)); return y; }
__device__ __forceinline__ float rcpf(float x) { float y; asm("rcp.approx.ftz.f32 %0, %1;" : "=f"(y) : "f"(x)); return y; }
__device__ __forceinline__ uint32_t pack_bf16(float lo, float hi) { uint32_t r; asm("cvt.rn.bf16x2.f32 %0, %1, %2;" : "=r"(r) : "f"(hi), "f"(lo)); return r; }
__device__ __forceinline__ float bf_lo(uint32_t v) { return __uint_as_float(v << 16); }
__device__ __forceinline__ float bf_hi(uint32_t v) { return __uint_as_float(v & 0xFFFF0000u); }
__device__ __forceinline__ float bf_round(float x) { return __bfloat162float(__float2bfloat16_rn(x)); }
__device__ __forceinline__ float siluf(float g) { return g * rcpf(1.0f + ex2f(g * -1.4426950408889634f)); }

__device__ __forceinline__ void wgmma_ss_n256(float* d, uint64_t da, uint64_t db, int acc) {
    asm volatile("{\n.reg .pred p;\nsetp.ne.b32 p, %130, 0;\nwgmma.mma_async.sync.aligned.m64n256k16.f32.bf16.bf16 {"
        "%0,%1,%2,%3,%4,%5,%6,%7,%8,%9,%10,%11,%12,%13,%14,%15,%16,%17,%18,%19,%20,%21,%22,%23,%24,%25,%26,%27,%28,%29,%30,%31,%32,%33,%34,%35,%36,%37,%38,%39,"
        "%40,%41,%42,%43,%44,%45,%46,%47,%48,%49,%50,%51,%52,%53,%54,%55,%56,%57,%58,%59,%60,%61,%62,%63,%64,%65,%66,%67,%68,%69,%70,%71,%72,%73,%74,%75,%76,"
        "%77,%78,%79,%80,%81,%82,%83,%84,%85,%86,%87,%88,%89,%90,%91,%92,%93,%94,%95,%96,%97,%98,%99,%100,%101,%102,%103,%104,%105,%106,%107,%108,%109,%110,"
        "%111,%112,%113,%114,%115,%116,%117,%118,%119,%120,%121,%122,%123,%124,%125,%126,%127"
        "}, %128, %129, p, 1, 1, 0, 1;\n}\n"
        : "+f"(d[0]),"+f"(d[1]),"+f"(d[2]),"+f"(d[3]),"+f"(d[4]),"+f"(d[5]),"+f"(d[6]),"+f"(d[7]),"+f"(d[8]),"+f"(d[9]),"+f"(d[10]),"+f"(d[11]),"+f"(d[12]),
          "+f"(d[13]),"+f"(d[14]),"+f"(d[15]),"+f"(d[16]),"+f"(d[17]),"+f"(d[18]),"+f"(d[19]),"+f"(d[20]),"+f"(d[21]),"+f"(d[22]),"+f"(d[23]),"+f"(d[24]),
          "+f"(d[25]),"+f"(d[26]),"+f"(d[27]),"+f"(d[28]),"+f"(d[29]),"+f"(d[30]),"+f"(d[31]),"+f"(d[32]),"+f"(d[33]),"+f"(d[34]),"+f"(d[35]),"+f"(d[36]),
          "+f"(d[37]),"+f"(d[38]),"+f"(d[39]),"+f"(d[40]),"+f"(d[41]),"+f"(d[42]),"+f"(d[43]),"+f"(d[44]),"+f"(d[45]),"+f"(d[46]),"+f"(d[47]),"+f"(d[48]),
          "+f"(d[49]),"+f"(d[50]),"+f"(d[51]),"+f"(d[52]),"+f"(d[53]),"+f"(d[54]),"+f"(d[55]),"+f"(d[56]),"+f"(d[57]),"+f"(d[58]),"+f"(d[59]),"+f"(d[60]),
          "+f"(d[61]),"+f"(d[62]),"+f"(d[63]),"+f"(d[64]),"+f"(d[65]),"+f"(d[66]),"+f"(d[67]),"+f"(d[68]),"+f"(d[69]),"+f"(d[70]),"+f"(d[71]),"+f"(d[72]),
          "+f"(d[73]),"+f"(d[74]),"+f"(d[75]),"+f"(d[76]),"+f"(d[77]),"+f"(d[78]),"+f"(d[79]),"+f"(d[80]),"+f"(d[81]),"+f"(d[82]),"+f"(d[83]),"+f"(d[84]),
          "+f"(d[85]),"+f"(d[86]),"+f"(d[87]),"+f"(d[88]),"+f"(d[89]),"+f"(d[90]),"+f"(d[91]),"+f"(d[92]),"+f"(d[93]),"+f"(d[94]),"+f"(d[95]),"+f"(d[96]),
          "+f"(d[97]),"+f"(d[98]),"+f"(d[99]),"+f"(d[100]),"+f"(d[101]),"+f"(d[102]),"+f"(d[103]),"+f"(d[104]),"+f"(d[105]),"+f"(d[106]),"+f"(d[107]),
          "+f"(d[108]),"+f"(d[109]),"+f"(d[110]),"+f"(d[111]),"+f"(d[112]),"+f"(d[113]),"+f"(d[114]),"+f"(d[115]),"+f"(d[116]),"+f"(d[117]),"+f"(d[118]),
          "+f"(d[119]),"+f"(d[120]),"+f"(d[121]),"+f"(d[122]),"+f"(d[123]),"+f"(d[124]),"+f"(d[125]),"+f"(d[126]),"+f"(d[127])
        : "l"(da), "l"(db), "r"(acc));
}
__device__ __forceinline__ void wgmma_ss_n128(float* d, uint64_t da, uint64_t db, int acc) {
    asm volatile("{\n.reg .pred p;\nsetp.ne.b32 p, %66, 0;\nwgmma.mma_async.sync.aligned.m64n128k16.f32.bf16.bf16 {"
        "%0,%1,%2,%3,%4,%5,%6,%7,%8,%9,%10,%11,%12,%13,%14,%15,%16,%17,%18,%19,%20,%21,%22,%23,%24,%25,%26,%27,%28,%29,%30,%31,%32,%33,%34,%35,%36,%37,%38,%39,"
        "%40,%41,%42,%43,%44,%45,%46,%47,%48,%49,%50,%51,%52,%53,%54,%55,%56,%57,%58,%59,%60,%61,%62,%63"
        "}, %64, %65, p, 1, 1, 0, 1;\n}\n"
        : "+f"(d[0]),"+f"(d[1]),"+f"(d[2]),"+f"(d[3]),"+f"(d[4]),"+f"(d[5]),"+f"(d[6]),"+f"(d[7]),"+f"(d[8]),"+f"(d[9]),"+f"(d[10]),"+f"(d[11]),"+f"(d[12]),
          "+f"(d[13]),"+f"(d[14]),"+f"(d[15]),"+f"(d[16]),"+f"(d[17]),"+f"(d[18]),"+f"(d[19]),"+f"(d[20]),"+f"(d[21]),"+f"(d[22]),"+f"(d[23]),"+f"(d[24]),
          "+f"(d[25]),"+f"(d[26]),"+f"(d[27]),"+f"(d[28]),"+f"(d[29]),"+f"(d[30]),"+f"(d[31]),"+f"(d[32]),"+f"(d[33]),"+f"(d[34]),"+f"(d[35]),"+f"(d[36]),
          "+f"(d[37]),"+f"(d[38]),"+f"(d[39]),"+f"(d[40]),"+f"(d[41]),"+f"(d[42]),"+f"(d[43]),"+f"(d[44]),"+f"(d[45]),"+f"(d[46]),"+f"(d[47]),"+f"(d[48]),
          "+f"(d[49]),"+f"(d[50]),"+f"(d[51]),"+f"(d[52]),"+f"(d[53]),"+f"(d[54]),"+f"(d[55]),"+f"(d[56]),"+f"(d[57]),"+f"(d[58]),"+f"(d[59]),"+f"(d[60]),
          "+f"(d[61]),"+f"(d[62]),"+f"(d[63])
        : "l"(da), "l"(db), "r"(acc));
}
__device__ __forceinline__ void wgmma_ss_n64(float* d, uint64_t da, uint64_t db, int acc) {
    asm volatile("{\n.reg .pred p;\nsetp.ne.b32 p, %34, 0;\nwgmma.mma_async.sync.aligned.m64n64k16.f32.bf16.bf16 {"
        "%0,%1,%2,%3,%4,%5,%6,%7,%8,%9,%10,%11,%12,%13,%14,%15,%16,%17,%18,%19,%20,%21,%22,%23,%24,%25,%26,%27,%28,%29,%30,%31"
        "}, %32, %33, p, 1, 1, 0, 1;\n}\n"
        : "+f"(d[0]),"+f"(d[1]),"+f"(d[2]),"+f"(d[3]),"+f"(d[4]),"+f"(d[5]),"+f"(d[6]),"+f"(d[7]),"+f"(d[8]),"+f"(d[9]),"+f"(d[10]),"+f"(d[11]),"+f"(d[12]),
          "+f"(d[13]),"+f"(d[14]),"+f"(d[15]),"+f"(d[16]),"+f"(d[17]),"+f"(d[18]),"+f"(d[19]),"+f"(d[20]),"+f"(d[21]),"+f"(d[22]),"+f"(d[23]),"+f"(d[24]),
          "+f"(d[25]),"+f"(d[26]),"+f"(d[27]),"+f"(d[28]),"+f"(d[29]),"+f"(d[30]),"+f"(d[31])
        : "l"(da), "l"(db), "r"(acc));
}
__device__ __forceinline__ void wgmma_rs_n64_zero(float* d, const uint32_t* a, uint64_t db) {
    asm volatile("wgmma.mma_async.sync.aligned.m64n64k16.f32.bf16.bf16 {"
        "%0,%1,%2,%3,%4,%5,%6,%7,%8,%9,%10,%11,%12,%13,%14,%15,%16,%17,%18,%19,%20,%21,%22,%23,%24,%25,%26,%27,%28,%29,%30,%31"
        "}, {%32,%33,%34,%35}, %36, 0, 1, 1, 0;\n"
        : "=f"(d[0]),"=f"(d[1]),"=f"(d[2]),"=f"(d[3]),"=f"(d[4]),"=f"(d[5]),"=f"(d[6]),"=f"(d[7]),"=f"(d[8]),"=f"(d[9]),"=f"(d[10]),"=f"(d[11]),"=f"(d[12]),
          "=f"(d[13]),"=f"(d[14]),"=f"(d[15]),"=f"(d[16]),"=f"(d[17]),"=f"(d[18]),"=f"(d[19]),"=f"(d[20]),"=f"(d[21]),"=f"(d[22]),"=f"(d[23]),"=f"(d[24]),
          "=f"(d[25]),"=f"(d[26]),"=f"(d[27]),"=f"(d[28]),"=f"(d[29]),"=f"(d[30]),"=f"(d[31])
        : "r"(a[0]), "r"(a[1]), "r"(a[2]), "r"(a[3]), "l"(db));
}
__device__ __forceinline__ void wgmma_rs_n64_acc(float* d, const uint32_t* a, uint64_t db) {
    asm volatile("wgmma.mma_async.sync.aligned.m64n64k16.f32.bf16.bf16 {"
        "%0,%1,%2,%3,%4,%5,%6,%7,%8,%9,%10,%11,%12,%13,%14,%15,%16,%17,%18,%19,%20,%21,%22,%23,%24,%25,%26,%27,%28,%29,%30,%31"
        "}, {%32,%33,%34,%35}, %36, 1, 1, 1, 0;\n"
        : "+f"(d[0]),"+f"(d[1]),"+f"(d[2]),"+f"(d[3]),"+f"(d[4]),"+f"(d[5]),"+f"(d[6]),"+f"(d[7]),"+f"(d[8]),"+f"(d[9]),"+f"(d[10]),"+f"(d[11]),"+f"(d[12]),
          "+f"(d[13]),"+f"(d[14]),"+f"(d[15]),"+f"(d[16]),"+f"(d[17]),"+f"(d[18]),"+f"(d[19]),"+f"(d[20]),"+f"(d[21]),"+f"(d[22]),"+f"(d[23]),"+f"(d[24]),
          "+f"(d[25]),"+f"(d[26]),"+f"(d[27]),"+f"(d[28]),"+f"(d[29]),"+f"(d[30]),"+f"(d[31])
        : "r"(a[0]), "r"(a[1]), "r"(a[2]), "r"(a[3]), "l"(db));
}
__device__ __forceinline__ void wgmma_rs_n24_acc(float* d, const uint32_t* a, uint64_t db) {
    asm volatile("wgmma.mma_async.sync.aligned.m64n24k16.f32.bf16.bf16 {"
        "%0,%1,%2,%3,%4,%5,%6,%7,%8,%9,%10,%11"
        "}, {%12,%13,%14,%15}, %16, 1, 1, 1, 1;\n"
        : "+f"(d[0]),"+f"(d[1]),"+f"(d[2]),"+f"(d[3]),"+f"(d[4]),"+f"(d[5]),"+f"(d[6]),"+f"(d[7]),"+f"(d[8]),"+f"(d[9]),"+f"(d[10]),"+f"(d[11])
        : "r"(a[0]), "r"(a[1]), "r"(a[2]), "r"(a[3]), "l"(db));
}
__device__ __forceinline__ void wgmma_rs_n24_zero(float* d, const uint32_t* a, uint64_t db) {
    asm volatile("wgmma.mma_async.sync.aligned.m64n24k16.f32.bf16.bf16 {"
        "%0,%1,%2,%3,%4,%5,%6,%7,%8,%9,%10,%11"
        "}, {%12,%13,%14,%15}, %16, 0, 1, 1, 1;\n"
        : "=f"(d[0]),"=f"(d[1]),"=f"(d[2]),"=f"(d[3]),"=f"(d[4]),"=f"(d[5]),"=f"(d[6]),"=f"(d[7]),"=f"(d[8]),"=f"(d[9]),"=f"(d[10]),"=f"(d[11])
        : "r"(a[0]), "r"(a[1]), "r"(a[2]), "r"(a[3]), "l"(db));
}

constexpr int K1_STAGES = 6, K1_STAGE_BYTES = 16384;
constexpr int K1_SMEM = 131072 + K1_STAGES * K1_STAGE_BYTES + 1024 + 128;

template <int N> __device__ __forceinline__ void k1_mainloop(float* acc, uint32_t sA, uint32_t sB, uint32_t bars, int& st, uint32_t& ph, int tid_wg) {
    constexpr int NST = N / 16, KPS = 512 / NST / 16;
    int prev = -1;
#pragma unroll 1
    for (int s = 0; s < NST; s++) {
        mbar_wait(bars + 8 * st, ph);
        const uint64_t db = mkdesc(sB + st * K1_STAGE_BYTES, N == 256 ? 4096 : 8192, 1024, 1);
        const int k0 = s * KPS;
        const uint64_t da = mkdesc(sA + (k0 >> 2) * 16384 + (k0 & 3) * 32, 16, 1024, 1);
        wg_fence();
#pragma unroll
        for (int k = 0; k < KPS; k++) {
            if (N == 256) wgmma_ss_n256(acc, da + k * 2, db + k * 128, (s | k) != 0);
            else          wgmma_ss_n128(acc, da + k * 2, db + k * 128, (s | k) != 0);
        }
        wg_commit();
        if (prev >= 0) {
            wg_wait<1>();
            if (tid_wg < 2) mbar_arrive_cluster(bars + 8 * (K1_STAGES + prev), tid_wg);
        }
        prev = st;
        if (++st == K1_STAGES) { st = 0; ph ^= 1; }
    }
    wg_wait<0>();
    if (tid_wg < 2) mbar_arrive_cluster(bars + 8 * (K1_STAGES + prev), tid_wg);
    pin<N / 2>(acc);
}

__global__ void __cluster_dims__(2, 1, 1) __launch_bounds__(384, 1)
k1_ln_gemm(const __nv_bfloat16* __restrict__ x, const __grid_constant__ CUtensorMap mqkv, const __grid_constant__ CUtensorMap mw1,
           const __grid_constant__ CUtensorMap mw3) {
    extern __shared__ uint8_t smem_raw[];
    const uint32_t sA = (smem_u32(smem_raw) + 1023) & ~1023u;
    const uint32_t sB = sA + 131072;
    const uint32_t bars = sB + K1_STAGES * K1_STAGE_BYTES;
    const int tid = threadIdx.x, lane = tid & 31;
    const int warp = __shfl_sync(0xffffffffu, tid >> 5, 0), wg = warp >> 2;
    const int rank = blockIdx.x & 1, grp = (blockIdx.x >> 1) & 7, mblk = (blockIdx.x >> 4) * 2 + rank;
    const bool typeA = grp < 4;
    const int qb0 = typeA ? 4 * grp : 8 + 2 * grp;
    const int gu0 = typeA ? 3 * grp : 4 * grp - 4;

    if (tid == 0) {
        TSTAMP(0, 0);
        for (int i = 0; i < K1_STAGES; i++) { mbar_init(bars + 8 * i, 1); mbar_init(bars + 8 * (K1_STAGES + i), 4); }
        asm volatile("fence.mbarrier_init.release.cluster;" ::: "memory");
    }
    if (blockIdx.x == 0 && tid < 32) g_ocnt[tid] = 0;
    asm volatile("barrier.cluster.arrive.relaxed.aligned;" ::: "memory");

    if (wg == 2) {
        asm volatile("barrier.cluster.wait.aligned;" ::: "memory");
        if (warp == 8) {
            int st = 0; uint32_t ph = 1;
            for (int t = 0; t < 3; t++) {
                const bool n256 = typeA ? (t < 2) : (t > 0);
                const CUtensorMap *m0, *m1; int c0, c1;
                if (t == 0) {
                    m0 = m1 = &mqkv;
                    c0 = n256 ? 64 * (qb0 + 2 * rank) : 64 * (qb0 + rank);
                    c1 = n256 ? c0 + 64 : c0;
                } else {
                    const int u = gu0 + 2 * (t - 1);
                    if (n256) { m0 = &mw1; m1 = &mw3; c0 = c1 = 64 * (u + rank); }
                    else      { m0 = m1 = rank ? &mw3 : &mw1; c0 = c1 = 64 * u; }
                }
                const int nst = n256 ? 16 : 8, kstep = n256 ? 32 : 64, k1off = n256 ? 0 : 32;
                for (int s = 0; s < nst; s++) {
                    mbar_wait(bars + 8 * (K1_STAGES + st), ph);
                    if (elect_one()) {
                        mbar_expect(bars + 8 * st, K1_STAGE_BYTES);
                        const uint32_t dst = sB + st * K1_STAGE_BYTES + rank * 8192;
                        tma2d_mc(dst, m0, c0, s * kstep, bars + 8 * st);
                        tma2d_mc(dst + 4096, m1, c1, s * kstep + k1off, bars + 8 * st);
                    }
                    if (++st == K1_STAGES) { st = 0; ph ^= 1; }
                }
            }
        }
    } else {
        const int g = lane >> 2, t4 = lane & 3;
        {
            uint4 xv[2][16];
            const int r0 = warp * 16 + g;
#pragma unroll
            for (int rr = 0; rr < 2; rr++) {
                const uint4* src = reinterpret_cast<const uint4*>(x + (size_t)(mblk * 128 + r0 + rr * 8) * DM);
#pragma unroll
                for (int j = 0; j < 16; j++) xv[rr][j] = __ldg(src + ((j ^ (g & 1)) * 4 + t4));
            }
#pragma unroll
            for (int rr = 0; rr < 2; rr++) {
                uint32_t* w = reinterpret_cast<uint32_t*>(xv[rr]);
                float s0 = 0.f, s1 = 0.f;
#pragma unroll
                for (int j = 0; j < 64; j++) { s0 += bf_lo(w[j]); s1 += bf_hi(w[j]); }
                s0 += s1;
                s0 += __shfl_xor_sync(0xffffffffu, s0, 1); s0 += __shfl_xor_sync(0xffffffffu, s0, 2);
                const float mean = s0 * (1.0f / DM);
                float v0 = 0.f, v1 = 0.f;
#pragma unroll
                for (int j = 0; j < 64; j++) { const float a = bf_lo(w[j]) - mean, b = bf_hi(w[j]) - mean; v0 = fmaf(a, a, v0); v1 = fmaf(b, b, v1); }
                v0 += v1;
                v0 += __shfl_xor_sync(0xffffffffu, v0, 1); v0 += __shfl_xor_sync(0xffffffffu, v0, 2);
                const float sd = bf_round(sqrtf(bf_round(bf_round(v0 * (1.0f / DM)) + 1e-5f)));
                const float rinv = 1.0f / sd;
                const float rhi = bf_round(rinv);
                const uint32_t nm2 = pack_bf16(-mean, -mean), rh2 = pack_bf16(rhi, rhi), rl2 = pack_bf16(rinv - rhi, rinv - rhi);
#pragma unroll
                for (int j = 0; j < 64; j++) {
                    uint32_t d, e;
                    asm("add.rn.bf16x2 %0, %1, %2;" : "=r"(d) : "r"(w[j]), "r"(nm2));
                    asm("mul.rn.bf16x2 %0, %1, %2;" : "=r"(e) : "r"(d), "r"(rl2));
                    asm("fma.rn.bf16x2 %0, %1, %2, %3;" : "=r"(w[j]) : "r"(d), "r"(rh2), "r"(e));
                }
                const int r = r0 + rr * 8;
#pragma unroll
                for (int j = 0; j < 16; j++) {
                    const int c = (j ^ (g & 1)) * 4 + t4;
                    const uint32_t a = sA + (c >> 3) * 16384 + r * 128 + (((c & 7) ^ g) << 4);
                    asm volatile("st.shared.v4.b32 [%0], {%1,%2,%3,%4};" :: "r"(a), "r"(xv[rr][j].x), "r"(xv[rr][j].y), "r"(xv[rr][j].z), "r"(xv[rr][j].w) : "memory");
                }
            }
            fence_async_smem();
            bar_sync(1 + wg, 128);
        }
        asm volatile("barrier.cluster.wait.aligned;" ::: "memory");
        if (tid == 0) TSTAMP(0, 1);

        float acc[128];
        int st = 0; uint32_t ph = 0;
        const int wq = warp & 3, rowblk = mblk * 2 + wg;
#pragma unroll 1
        for (int t = 0; t < 3; t++) {
            const bool n256 = typeA ? (t < 2) : (t > 0);
            if (n256) k1_mainloop<256>(acc, sA + wg * 8192, sB, bars, st, ph, tid & 127);
            else      k1_mainloop<128>(acc, sA + wg * 8192, sB, bars, st, ph, tid & 127);
            if (tid == 0) TSTAMP(0, 2 + 2 * t);
            if (t == 0) {
                const int tile16 = rowblk * 4 + wq;
#pragma unroll
                for (int hh = 0; hh < 16; hh++) {
                    if (hh < 8 || n256) {
                        const int head = (qb0 * 4 + hh) & 31;
                        const float* a = acc + hh * 8;
                        if (qb0 < 8) {
                            const float sc = 5.421010862427522e-20f;
                            g_q[(head * 128 + tile16) * 32 + lane] = make_uint4(pack_bf16(a[0] * sc, a[1] * sc), pack_bf16(a[2] * sc, a[3] * sc),
                                                                                pack_bf16(a[4] * sc, a[5] * sc), pack_bf16(a[6] * sc, a[7] * sc));
                        } else {
                            uint32_t* p; int s8, sh;
                            if (qb0 < 16) { p = reinterpret_cast<uint32_t*>(g_k + head * 4096) + tile16 * 128 + lane; s8 = 64; sh = 32; }
                            else          { p = reinterpret_cast<uint32_t*>(g_v + head * 4096) + tile16 * 64 + lane;  s8 = 32; sh = 8192; }
                            p[0] = pack_bf16(a[0], a[1]); p[s8] = pack_bf16(a[2], a[3]);
                            p[sh] = pack_bf16(a[4], a[5]); p[sh + s8] = pack_bf16(a[6], a[7]);
                        }
                    }
                }
                __threadfence();
                bar_sync(3, 256);
                if (tid == 0) asm volatile("griddepcontrol.launch_dependents;" ::: "memory");
            } else {
#pragma unroll
                for (int u = 0; u < 2; u++) {
                    if (u == 0 || n256) {
                        uint32_t* p = reinterpret_cast<uint32_t*>(g_h + (rowblk * 28 + gu0 + 2 * (t - 1) + u) * 512) + wq * 512 + lane;
#pragma unroll
                        for (int j = 0; j < 8; j++) {
                            const float* ga = acc + u * 64 + j * 4; const float* up = ga + 32;
                            p[j * 32] = pack_bf16(siluf(ga[0]) * up[0], siluf(ga[1]) * up[1]);
                            p[256 + j * 32] = pack_bf16(siluf(ga[2]) * up[2], siluf(ga[3]) * up[3]);
                        }
                    }
                }
            }
            if (tid == 0) TSTAMP(0, 3 + 2 * t);
        }
    }
    __syncwarp();
    asm volatile("barrier.cluster.arrive.relaxed.aligned;\nbarrier.cluster.wait.aligned;" ::: "memory");
}

constexpr int K2_OFF_ONES = 131072;
constexpr int K2_OFF_RING = K2_OFF_ONES + 4096;
constexpr int K2_RING = 5;
constexpr int K2_OFF_BARS = K2_OFF_RING + K2_RING * 16384;
constexpr int K2_SMEM = K2_OFF_BARS + 256 + 1024;

__device__ __forceinline__ uint32_t exp2_fixed(float lo, float hi, uint32_t half2) {
    uint32_t y, g, d;
    asm("cvt.pack.sat.s16.s32 %0, %1, %2;" : "=r"(y) : "r"(__float_as_uint(hi)), "r"(__float_as_uint(lo)));
    asm("lop3.b32 %0, %1, 0x007F007F, %2, 0xEA;" : "=r"(g) : "r"(y), "r"(half2));
    asm("fma.rn.bf16x2 %0, %1, %2, %3;" : "=r"(d) : "r"(y), "r"(g), "r"(y & 0xFF80FF80u));
    return d;
}
constexpr float C_MUFU = 0.25f * 1.4426950408889634f * 18446744073709551616.0f;
constexpr float C_FIX = 0.25f * 1.4426950408889634f * 3.308722450212111e-24f;

__device__ __forceinline__ void softmax_tile(const float* s, uint32_t* p, const float* bm, const float* bf, uint32_t half2) {
#pragma unroll
    for (int i = 0; i < 16; i++) {
        const int r = i & 1;
        if (((i * 5) & 7) < 5) p[i] = exp2_fixed(fmaf(s[2 * i], C_FIX, bf[r]), fmaf(s[2 * i + 1], C_FIX, bf[r]), half2);
        else                   p[i] = pack_bf16(ex2f(fmaf(s[2 * i], C_MUFU, bm[r])), ex2f(fmaf(s[2 * i + 1], C_MUFU, bm[r])));
    }
}
__device__ __forceinline__ uint32_t k_tile_addr(uint32_t base, int tile) {
    const int c = tile >> 2;
    return base + ((tile & 2) ? 98304 + c * 4096 : (2 * c + 1) * 4096) + (tile & 1) * 2048;
}

__global__ void __launch_bounds__(640, 1)
k2_attn(const __nv_bfloat16* __restrict__ x, __nv_bfloat16* __restrict__ out, const __grid_constant__ CUtensorMap mw2,
        const __grid_constant__ CUtensorMap mwo, uint32_t half2) {
    extern __shared__ uint8_t smem_raw[];
    const uint32_t sb = (smem_u32(smem_raw) + 1023) & ~1023u;
    const uint32_t bars = sb + K2_OFF_BARS;
    const uint32_t bar_ring = bars + 64, bar_o = bars + 64 + 8 * K2_RING;
    const uint32_t bar_done = bar_o + 64;
    const int tid = threadIdx.x, lane = tid & 31;
    const int warp = __shfl_sync(0xffffffffu, tid >> 5, 0), wg = warp >> 2, wq = warp & 3;
    const int head = blockIdx.x >> 2, qb = blockIdx.x & 3;

    if (tid == 0) {
        TSTAMP(1, 0);
        for (int i = 0; i < 8 + K2_RING + 8; i++) mbar_init(bars + 8 * i, i < 8 ? 4 : 1);
        mbar_init(bar_done, 4);
        asm volatile("fence.mbarrier_init.release.cluster;" ::: "memory");
    }
    if (tid < 256) asm volatile("st.shared.v4.b32 [%0], {%1,%1,%1,%1};" :: "r"(sb + K2_OFF_ONES + tid * 16), "r"(0x3F803F80u) : "memory");
    fence_async_smem();
    __syncthreads();

    if (wg < 4) {
#pragma unroll 1
        for (int round = 0; round < 2; round++) {
            const int rowblk = qb * 8 + round * 4 + wg;
            uint32_t q[4];
            { const uint4 v = __ldcg(g_q + (head * 128 + rowblk * 4 + wq) * 32 + lane); q[0] = v.x; q[1] = v.y; q[2] = v.z; q[3] = v.w; }
            float o[12];
            int nmax = 1;
#pragma unroll 1
            for (;;) {
                float s[32]; uint32_t p[16];
                float m0 = -INFINITY, m1 = -INFINITY;
                mbar_wait(bars, 0);
#pragma unroll 1
                for (int t = 0; t < nmax; t++) {
                    wg_fence();
                    wgmma_rs_n64_zero(s, q, mkdesc(k_tile_addr(sb, t), 128, 256, 0));
                    wg_commit();
                    wg_wait<0>();
                    pin<32>(s);
#pragma unroll
                    for (int i = 0; i < 8; i++) { m0 = fmaxf(m0, fmaxf(s[4 * i], s[4 * i + 1])); m1 = fmaxf(m1, fmaxf(s[4 * i + 2], s[4 * i + 3])); }
                }
                m0 = fmaxf(m0, __shfl_xor_sync(0xffffffffu, m0, 1)); m0 = fmaxf(m0, __shfl_xor_sync(0xffffffffu, m0, 2));
                m1 = fmaxf(m1, __shfl_xor_sync(0xffffffffu, m1, 1)); m1 = fmaxf(m1, __shfl_xor_sync(0xffffffffu, m1, 2));
                m0 = rintf(m0 * C_MUFU); m1 = rintf(m1 * C_MUFU);
                float bm[2] = {-79.41395f - m0, -79.41395f - m1};
                float bf[2] = {(47.0f - m0) * 4.235164736271502e-22f * 4.235164736271502e-22f, (47.0f - m1) * 4.235164736271502e-22f * 4.235164736271502e-22f};
#pragma unroll
                for (int i = 0; i < 12; i++) o[i] = 0.f;
                pin<12>(o); pin<2>(bm); pin<2>(bf);
                if (tid == 0) TSTAMP(1, 1 + 2 * round);
#pragma unroll 1
                for (int c = 0; c < 8; c++) {
                    mbar_wait(bars + 8 * c, 0);
                    const uint64_t dk0 = mkdesc(sb + (2 * c + 1) * 4096, 128, 256, 0), dk1 = mkdesc(sb + 98304 + c * 4096, 128, 256, 0);
                    const uint64_t dv = mkdesc(sb + 2 * c * 4096, 128, 65536 - c * 4096, 0);
#pragma unroll
                    for (int t = 0; t < 4; t++) {
                        wg_fence();
                        wgmma_rs_n64_zero(s, q, (t & 2 ? dk1 : dk0) + (t & 1) * 128);
                        wg_commit();
                        wg_wait<0>();
                        pin<32>(s); pin<16>(p);
                        softmax_tile(s, p, bm, bf, half2);
                        wg_fence();
#pragma unroll
                        for (int k = 0; k < 4; k++) wgmma_rs_n24_acc(o, p + 4 * k, dv + (t * 4 + k) * 16);
                        wg_commit();
                    }
                }
                wg_wait<0>();
                pin<12>(o);
                float chk = 0.f;
#pragma unroll
                for (int i = 0; i < 12; i++) chk = fmaf(o[i], 0.f, chk);
                uint32_t bad;
                asm volatile("{\n.reg .pred p, q;\nsetp.neu.f32 q, %1, 0f00000000;\nbar.red.or.pred p, %2, 128, q;\nselp.u32 %0, 1, 0, p;\n}" : "=r"(bad) : "f"(chk), "r"(1 + wg) : "memory");
                if (!__any_sync(0xffffffffu, bad) || nmax != 1) break;
                nmax = 32;
            }
            const float r0 = 1.0f / o[8], r1 = 1.0f / o[10];
            uint32_t* po = reinterpret_cast<uint32_t*>(g_o + (rowblk * 8 + (head >> 2)) * 512) + wq * 512 + (head & 3) * 64 + lane;
            po[0] = pack_bf16(o[0] * r0, o[1] * r0); po[256] = pack_bf16(o[2] * r1, o[3] * r1);
            po[32] = pack_bf16(o[4] * r0, o[5] * r0); po[288] = pack_bf16(o[6] * r1, o[7] * r1);
            __threadfence();
            bar_sync(1 + wg, 128);
            if (wq == 0 && elect_one()) {
                asm volatile("red.release.gpu.global.add.u32 [%0], 1;" :: "l"(g_ocnt + rowblk) : "memory");
                if (round == 1) mbar_arrive(bar_done);
            }
            if (tid == 0) TSTAMP(1, 2 + 2 * round);
        }
    } else {
        const int g = lane >> 2, t4 = lane & 3;
        if (elect_one()) {
            fence_async_all();
            const uint8_t* src = wq < 2 ? reinterpret_cast<const uint8_t*>(g_k + head * 4096) + wq * 4096
                                        : reinterpret_cast<const uint8_t*>(g_v + head * 4096) + (wq - 2) * 32768;
            const uint32_t dst = sb + (wq == 0 ? 4096 : wq == 1 ? 98304 : wq == 2 ? 0 : 65536);
#pragma unroll 1
            for (int c = 0; c < 8; c++) {
                mbar_expect(bars + 8 * c, 4096);
                bulk_load(dst + c * ((wq & 1) ? 4096 : 8192), src + c * (wq < 2 ? 8192 : 4096), 4096, bars + 8 * c);
            }
        }
        const int cb = blockIdx.x & 7, pr = blockIdx.x >> 3;
        const int rb0 = (pr >> 2) * 8 + (pr & 3);
        const uint32_t ring = sb + K2_OFF_RING;
        uint32_t gate[2][16];
        float acc[32];
        asm volatile("griddepcontrol.wait;" ::: "memory");
        if (wq == 0 && elect_one()) {
            TSTAMP(1, 8);
            fence_async_all();
#pragma unroll 1
            for (int i = 0; i < K2_RING; i++) {
                mbar_expect(bar_ring + 8 * i, 16384);
                bulk_load(ring + i * 16384, g_h + (rb0 * 28 + i) * 512, 8192, bar_ring + 8 * i);
                tma2d(ring + i * 16384 + 8192, &mw2, cb * 64, i * 64, bar_ring + 8 * i);
            }
        }
        int st = 0; uint32_t ph = 0;
#pragma unroll
        for (int tl = 0; tl < 2; tl++) {
#pragma unroll 1
            for (int kb = 0; kb < 28; kb++) {
                mbar_wait(bar_ring + 8 * st, ph);
                const uint64_t da = mkdesc(ring + st * 16384, 128, 1024, 0), db = mkdesc(ring + st * 16384 + 8192, 8192, 1024, 1);
                wg_fence();
#pragma unroll
                for (int k = 0; k < 4; k++) wgmma_ss_n64(acc, da + k * 16, db + k * 128, (kb | k) != 0);
                wg_commit();
                wg_wait<0>();
                bar_sync(5, 128);
                const int nx = tl * 28 + kb + K2_RING;
                if (wq == 0 && nx < 56 && elect_one()) {
                    const int ntl = nx >= 28, nkb = nx - ntl * 28;
                    mbar_expect(bar_ring + 8 * st, 16384);
                    bulk_load(ring + st * 16384, g_h + ((rb0 + 4 * ntl) * 28 + nkb) * 512, 8192, bar_ring + 8 * st);
                    tma2d(ring + st * 16384 + 8192, &mw2, cb * 64, nkb * 64, bar_ring + 8 * st);
                }
                if (++st == K2_RING) { st = 0; ph ^= 1; }
            }
            pin<32>(acc);
#pragma unroll
            for (int i = 0; i < 16; i++) gate[tl][i] = pack_bf16(siluf(acc[2 * i]), siluf(acc[2 * i + 1]));
        }
        if (tid == 512) TSTAMP(1, 9);
        const uint32_t bar_wo = bar_ring + 8 * st;
        if (wq == 0 && elect_one()) {
            mbar_expect(bar_wo, 65536);
#pragma unroll 1
            for (int i = 0; i < 8; i++) tma2d(ring + i * 8192, &mwo, cb * 64, i * 64, bar_wo);
        }
#pragma unroll
        for (int tl = 0; tl < 2; tl++) {
            const int rb = rb0 + 4 * tl;
            uint32_t xr[16];
            const uint32_t* px = reinterpret_cast<const uint32_t*>(x + (size_t)(rb * 64 + wq * 16 + g) * DM + cb * 64) + t4;
#pragma unroll
            for (int j = 0; j < 8; j++) { xr[2 * j] = __ldg(px + j * 4); xr[2 * j + 1] = __ldg(px + 8 * DM / 2 + j * 4); }
            if (wq == 0) {
                for (int n = 0;; n++) {
                    unsigned v;
                    asm volatile("ld.acquire.gpu.global.u32 %0, [%1];" : "=r"(v) : "l"(g_ocnt + rb) : "memory");
                    if (__all_sync(0xffffffffu, v >= 32)) break;
                    if (n > 4000000) __trap();
                    __nanosleep(tl ? 20 : 200);
                }
                if (tl == 1) mbar_wait(bar_done, 0);
                if (elect_one()) {
                    fence_async_all();
                    TSTAMP(1, 10 + 2 * tl);
#pragma unroll 1
                    for (int i = 0; i < (tl ? 8 : 2); i++) {
                        mbar_expect(bar_o + 8 * i, 8192);
                        bulk_load((tl ? sb : ring + 65536) + i * 8192, g_o + (rb * 8 + i) * 512, 8192, bar_o + 8 * i);
                    }
                }
            }
            if (tl == 0) mbar_wait(bar_wo, ph);
#pragma unroll 1
            for (int kb = 0; kb < 8; kb++) {
                mbar_wait(bar_o + 8 * kb, tl);
                const uint32_t a = tl == 0 ? ring + 65536 + (kb & 1) * 8192 : sb + kb * 8192;
                const uint64_t da = mkdesc(a, 128, 1024, 0), db = mkdesc(ring + kb * 8192, 8192, 1024, 1);
                wg_fence();
#pragma unroll
                for (int k = 0; k < 4; k++) wgmma_ss_n64(acc, da + k * 16, db + k * 128, (kb | k) != 0);
                wg_commit();
                if (tl == 0) {
                    wg_wait<0>();
                    bar_sync(5, 128);
                    if (wq == 0 && kb < 6 && elect_one()) { mbar_expect(bar_o + 8 * (kb + 2), 8192); bulk_load(a, g_o + (rb * 8 + kb + 2) * 512, 8192, bar_o + 8 * (kb + 2)); }
                }
            }
            wg_wait<0>();
            pin<32>(acc);
            uint32_t* po = reinterpret_cast<uint32_t*>(out + (size_t)(rb * 64 + wq * 16 + g) * DM + cb * 64) + t4;
#pragma unroll
            for (int i = 0; i < 16; i++) {
                const uint32_t r = pack_bf16(fmaf(acc[2 * i], bf_lo(gate[tl][i]), bf_lo(xr[i])), fmaf(acc[2 * i + 1], bf_hi(gate[tl][i]), bf_hi(xr[i])));
                po[(i & 1) * (8 * DM / 2) + (i >> 1) * 4] = r;
            }
            if (tid == 512) TSTAMP(1, 11 + 2 * tl);
        }
    }
}

typedef CUresult (*EncodeFn)(CUtensorMap*, CUtensorMapDataType, cuuint32_t, void*, const cuuint64_t*, const cuuint64_t*, const cuuint32_t*,
                             const cuuint32_t*, CUtensorMapInterleave, CUtensorMapSwizzle, CUtensorMapL2promotion, CUtensorMapFloatOOBfill);

void make_map(EncodeFn fn, CUtensorMap* m, const void* p, int rows, int cols, int box_rows) {
    cuuint64_t dims[2] = {(cuuint64_t)cols, (cuuint64_t)rows};
    cuuint64_t strides[1] = {(cuuint64_t)cols * 2};
    cuuint32_t box[2] = {64, (cuuint32_t)box_rows};
    cuuint32_t es[2] = {1, 1};
    fn(m, CU_TENSOR_MAP_DATA_TYPE_BFLOAT16, 2, const_cast<void*>(p), dims, strides, box, es, CU_TENSOR_MAP_INTERLEAVE_NONE,
       CU_TENSOR_MAP_SWIZZLE_128B, CU_TENSOR_MAP_L2_PROMOTION_L2_128B, CU_TENSOR_MAP_FLOAT_OOB_FILL_NONE);
}

}

extern "C" void kernel_launch(void* const* d_in, const int* in_sizes, int n_in, void* d_out, int out_size) {
    const __nv_bfloat16* x = (const __nv_bfloat16*)d_in[0];
    static EncodeFn fn = nullptr;
    if (!fn) {
        cudaDriverEntryPointQueryResult qr;
        cudaGetDriverEntryPoint("cuTensorMapEncodeTiled", (void**)&fn, cudaEnableDefault, &qr);
        cudaFuncSetAttribute(k1_ln_gemm, cudaFuncAttributeMaxDynamicSharedMemorySize, K1_SMEM);
        cudaFuncSetAttribute(k2_attn, cudaFuncAttributeMaxDynamicSharedMemorySize, K2_SMEM);
    }
    CUtensorMap mqkv, mw1, mw3, mw2, mwo;
    make_map(fn, &mqkv, d_in[1], DM, 3 * DM, 32);
    make_map(fn, &mwo, d_in[2], DM, DM, 64);
    make_map(fn, &mw1, d_in[4], DM, FF, 32);
    make_map(fn, &mw3, d_in[5], DM, FF, 32);
    make_map(fn, &mw2, d_in[6], FF, DM, 64);

    k1_ln_gemm<<<128, 384, K1_SMEM, cudaStreamPerThread>>>(x, mqkv, mw1, mw3);

    cudaLaunchConfig_t cfg = {};
    cfg.gridDim = 128; cfg.blockDim = 640; cfg.dynamicSmemBytes = K2_SMEM; cfg.stream = cudaStreamPerThread;
    cudaLaunchAttribute at[1];
    at[0].id = cudaLaunchAttributeProgrammaticStreamSerialization; at[0].val.programmaticStreamSerializationAllowed = 1;
    cfg.attrs = at; cfg.numAttrs = 1;
    cudaLaunchKernelEx(&cfg, k2_attn, x, (__nv_bfloat16*)d_out, mw2, mwo, 0x3F003F00u);
}
```

```cpp
#include <cuda_runtime.h>
#include <cuda_bf16.h>
#include <cuda.h>
#include <stdint.h>

namespace {

constexpr int SEQ = 2048, DM = 512, FF = 1792;

__device__ uint4 g_q[32 * 128 * 32];
__device__ uint4 g_k[32 * 4096];
__device__ uint4 g_v[32 * 4096];
__device__ uint4 g_h[32 * 28 * 512];
__device__ uint4 g_o[32 * 8 * 512];
__device__ float4 g_cs[8 * 8 * 160];
__device__ float2 g_rs[SEQ];
constexpr int C_COL = 0, C_ROW = 8, C_QKV = 24, C_H = 36, C_O = 52, C_NUM = 84;
__device__ unsigned g_cnt[C_NUM * 8];
__device__ unsigned g_ticket;
#define TSTAMP(i)

__device__ __forceinline__ uint32_t smem_u32(const void* p) { return (uint32_t)__cvta_generic_to_shared(p); }
__device__ __forceinline__ void mbar_init(uint32_t a, int c) { asm volatile("mbarrier.init.shared::cta.b64 [%0], %1;" :: "r"(a), "r"(c)); }
__device__ __forceinline__ void mbar_expect(uint32_t a, int b) { asm volatile("mbarrier.arrive.expect_tx.shared::cta.b64 _, [%0], %1;" :: "r"(a), "r"(b) : "memory"); }
__device__ __forceinline__ void mbar_arrive(uint32_t a) { asm volatile("mbarrier.arrive.shared::cta.b64 _, [%0];" :: "r"(a) : "memory"); }
__device__ __forceinline__ void mbar_arrive_cluster(uint32_t a, uint32_t cta) {
    asm volatile("{\n.reg .b32 r;\nmapa.shared::cluster.u32 r, %0, %1;\nmbarrier.arrive.shared::cluster.b64 _, [r];\n}" :: "r"(a), "r"(cta) : "memory");
}
__device__ __forceinline__ bool mbar_try(uint32_t a, uint32_t ph) {
    uint32_t ok;
    asm volatile("{\n.reg .pred p;\nmbarrier.try_wait.parity.shared::cta.b64 p, [%1], %2;\nselp.u32 %0, 1, 0, p;\n}" : "=r"(ok) : "r"(a), "r"(ph) : "memory");
    return ok;
}
__device__ __forceinline__ void mbar_wait(uint32_t a, uint32_t ph) {
    for (int n = 0; !__all_sync(0xffffffffu, mbar_try(a, ph)); n++) if (n > 4000000) __trap();
}
__device__ __forceinline__ bool elect_one() {
    uint32_t p;
    asm volatile("{\n.reg .pred P;\nelect.sync _|P, 0xffffffff;\nselp.u32 %0, 1, 0, P;\n}" : "=r"(p));
    return p;
}
__device__ __forceinline__ void signal_cnt(int c) {
    asm volatile("fence.acq_rel.gpu;\nred.relaxed.gpu.global.add.u32 [%0], 1;" :: "l"(g_cnt + c * 8) : "memory");
}
__device__ __forceinline__ void wait_cnt(int c, unsigned target, int ns) {
    for (int n = 0;; n++) {
        unsigned v;
        asm volatile("ld.acquire.gpu.global.u32 %0, [%1];" : "=r"(v) : "l"(g_cnt + c * 8) : "memory");
        if (__all_sync(0xffffffffu, v >= target)) break;
        if (n > 2000000) __trap();
        __nanosleep(ns);
    }
}
__device__ __forceinline__ void tma2d(uint32_t dst, const CUtensorMap* m, int c0, int c1, uint32_t bar) {
    asm volatile("cp.async.bulk.tensor.2d.shared::cluster.global.mbarrier::complete_tx::bytes [%0], [%1, {%3, %4}], [%2];"
                 :: "r"(dst), "l"(m), "r"(bar), "r"(c0), "r"(c1) : "memory");
}
__device__ __forceinline__ void tma2d_mc(uint32_t dst, const CUtensorMap* m, int c0, int c1, uint32_t bar) {
    asm volatile("cp.async.bulk.tensor.2d.shared::cluster.global.mbarrier::complete_tx::bytes.multicast::cluster [%0], [%1, {%3, %4}], [%2], %5;"
                 :: "r"(dst), "l"(m), "r"(bar), "r"(c0), "r"(c1), "h"((uint16_t)3) : "memory");
}
__device__ __forceinline__ void bulk_load(uint32_t dst, const void* src, int bytes, uint32_t bar) {
    asm volatile("cp.async.bulk.shared::cluster.global.mbarrier::complete_tx::bytes [%0], [%1], %2, [%3];"
                 :: "r"(dst), "l"(src), "r"(bytes), "r"(bar) : "memory");
}
__device__ __forceinline__ void bar_sync(int id, int n) { asm volatile("bar.sync %0, %1;" :: "r"(id), "r"(n) : "memory"); }
__device__ __forceinline__ void fence_async_smem() { asm volatile("fence.proxy.async.shared::cta;" ::: "memory"); }
__device__ __forceinline__ void fence_async_all() { asm volatile("fence.proxy.async;" ::: "memory"); }
__device__ __forceinline__ void wg_fence() { asm volatile("wgmma.fence.sync.aligned;" ::: "memory"); }
__device__ __forceinline__ void wg_commit() { asm volatile("wgmma.commit_group.sync.aligned;" ::: "memory"); }
template <int N> __device__ __forceinline__ void wg_wait() { asm volatile("wgmma.wait_group.sync.aligned %0;" :: "n"(N) : "memory"); }
template <int N> __device__ __forceinline__ void pin(float* d) {
#pragma unroll
    for (int i = 0; i < N; i++) asm volatile("" : "+f"(d[i]) :: "memory");
}
template <int N> __device__ __forceinline__ void pin(uint32_t* d) {
#pragma unroll
    for (int i = 0; i < N; i++) asm volatile("" : "+r"(d[i]) :: "memory");
}
__device__ __forceinline__ uint64_t mkdesc(uint32_t addr, uint32_t lbo, uint32_t sbo, uint32_t swz) {
    return (uint64_t)((addr & 0x3FFFF) >> 4) | ((uint64_t)(lbo >> 4) << 16) | ((uint64_t)(sbo >> 4) << 32) | ((uint64_t)swz << 62);
}
__device__ __forceinline__ float ex2f(float x) { float y; asm("ex2.approx.ftz.f32 %0, %1;" : "=f"(y) : "f"(x)); return y; }
__device__ __forceinline__ float rcpf(float x) { float y; asm("rcp.approx.ftz.f32 %0, %1;" : "=f"(y) : "f"(x)); return y; }
__device__ __forceinline__ uint32_t pack_bf16(float lo, float hi) { uint32_t r; asm("cvt.rn.bf16x2.f32 %0, %1, %2;" : "=r"(r) : "f"(hi), "f"(lo)); return r; }
__device__ __forceinline__ float bf_lo(uint32_t v) { return __uint_as_float(v << 16); }
__device__ __forceinline__ float bf_hi(uint32_t v) { return __uint_as_float(v & 0xFFFF0000u); }
__device__ __forceinline__ float bf_round(float x) { return __bfloat162float(__float2bfloat16_rn(x)); }
__device__ __forceinline__ float siluf(float g) { return g * rcpf(1.0f + ex2f(g * -1.4426950408889634f)); }

__device__ __forceinline__ void wgmma_ss_n256(float* d, uint64_t da, uint64_t db, int acc) {
    asm volatile("{\n.reg .pred p;\nsetp.ne.b32 p, %130, 0;\nwgmma.mma_async.sync.aligned.m64n256k16.f32.bf16.bf16 {"
        "%0,%1,%2,%3,%4,%5,%6,%7,%8,%9,%10,%11,%12,%13,%14,%15,%16,%17,%18,%19,%20,%21,%22,%23,%24,%25,%26,%27,%28,%29,%30,%31,%32,%33,%34,%35,%36,%37,%38,%39,"
        "%40,%41,%42,%43,%44,%45,%46,%47,%48,%49,%50,%51,%52,%53,%54,%55,%56,%57,%58,%59,%60,%61,%62,%63,%64,%65,%66,%67,%68,%69,%70,%71,%72,%73,%74,%75,%76,"
        "%77,%78,%79,%80,%81,%82,%83,%84,%85,%86,%87,%88,%89,%90,%91,%92,%93,%94,%95,%96,%97,%98,%99,%100,%101,%102,%103,%104,%105,%106,%107,%108,%109,%110,"
        "%111,%112,%113,%114,%115,%116,%117,%118,%119,%120,%121,%122,%123,%124,%125,%126,%127"
        "}, %128, %129, p, 1, 1, 0, 1;\n}\n"
        : "+f"(d[0]),"+f"(d[1]),"+f"(d[2]),"+f"(d[3]),"+f"(d[4]),"+f"(d[5]),"+f"(d[6]),"+f"(d[7]),"+f"(d[8]),"+f"(d[9]),"+f"(d[10]),"+f"(d[11]),"+f"(d[12]),
          "+f"(d[13]),"+f"(d[14]),"+f"(d[15]),"+f"(d[16]),"+f"(d[17]),"+f"(d[18]),"+f"(d[19]),"+f"(d[20]),"+f"(d[21]),"+f"(d[22]),"+f"(d[23]),"+f"(d[24]),
          "+f"(d[25]),"+f"(d[26]),"+f"(d[27]),"+f"(d[28]),"+f"(d[29]),"+f"(d[30]),"+f"(d[31]),"+f"(d[32]),"+f"(d[33]),"+f"(d[34]),"+f"(d[35]),"+f"(d[36]),
          "+f"(d[37]),"+f"(d[38]),"+f"(d[39]),"+f"(d[40]),"+f"(d[41]),"+f"(d[42]),"+f"(d[43]),"+f"(d[44]),"+f"(d[45]),"+f"(d[46]),"+f"(d[47]),"+f"(d[48]),
          "+f"(d[49]),"+f"(d[50]),"+f"(d[51]),"+f"(d[52]),"+f"(d[53]),"+f"(d[54]),"+f"(d[55]),"+f"(d[56]),"+f"(d[57]),"+f"(d[58]),"+f"(d[59]),"+f"(d[60]),
          "+f"(d[61]),"+f"(d[62]),"+f"(d[63]),"+f"(d[64]),"+f"(d[65]),"+f"(d[66]),"+f"(d[67]),"+f"(d[68]),"+f"(d[69]),"+f"(d[70]),"+f"(d[71]),"+f"(d[72]),
          "+f"(d[73]),"+f"(d[74]),"+f"(d[75]),"+f"(d[76]),"+f"(d[77]),"+f"(d[78]),"+f"(d[79]),"+f"(d[80]),"+f"(d[81]),"+f"(d[82]),"+f"(d[83]),"+f"(d[84]),
          "+f"(d[85]),"+f"(d[86]),"+f"(d[87]),"+f"(d[88]),"+f"(d[89]),"+f"(d[90]),"+f"(d[91]),"+f"(d[92]),"+f"(d[93]),"+f"(d[94]),"+f"(d[95]),"+f"(d[96]),
          "+f"(d[97]),"+f"(d[98]),"+f"(d[99]),"+f"(d[100]),"+f"(d[101]),"+f"(d[102]),"+f"(d[103]),"+f"(d[104]),"+f"(d[105]),"+f"(d[106]),"+f"(d[107]),
          "+f"(d[108]),"+f"(d[109]),"+f"(d[110]),"+f"(d[111]),"+f"(d[112]),"+f"(d[113]),"+f"(d[114]),"+f"(d[115]),"+f"(d[116]),"+f"(d[117]),"+f"(d[118]),
          "+f"(d[119]),"+f"(d[120]),"+f"(d[121]),"+f"(d[122]),"+f"(d[123]),"+f"(d[124]),"+f"(d[125]),"+f"(d[126]),"+f"(d[127])
        : "l"(da), "l"(db), "r"(acc));
}
__device__ __forceinline__ void wgmma_ss_n128(float* d, uint64_t da, uint64_t db, int acc) {
    asm volatile("{\n.reg .pred p;\nsetp.ne.b32 p, %66, 0;\nwgmma.mma_async.sync.aligned.m64n128k16.f32.bf16.bf16 {"
        "%0,%1,%2,%3,%4,%5,%6,%7,%8,%9,%10,%11,%12,%13,%14,%15,%16,%17,%18,%19,%20,%21,%22,%23,%24,%25,%26,%27,%28,%29,%30,%31,%32,%33,%34,%35,%36,%37,%38,%39,"
        "%40,%41,%42,%43,%44,%45,%46,%47,%48,%49,%50,%51,%52,%53,%54,%55,%56,%57,%58,%59,%60,%61,%62,%63"
        "}, %64, %65, p, 1, 1, 0, 1;\n}\n"
        : "+f"(d[0]),"+f"(d[1]),"+f"(d[2]),"+f"(d[3]),"+f"(d[4]),"+f"(d[5]),"+f"(d[6]),"+f"(d[7]),"+f"(d[8]),"+f"(d[9]),"+f"(d[10]),"+f"(d[11]),"+f"(d[12]),
          "+f"(d[13]),"+f"(d[14]),"+f"(d[15]),"+f"(d[16]),"+f"(d[17]),"+f"(d[18]),"+f"(d[19]),"+f"(d[20]),"+f"(d[21]),"+f"(d[22]),"+f"(d[23]),"+f"(d[24]),
          "+f"(d[25]),"+f"(d[26]),"+f"(d[27]),"+f"(d[28]),"+f"(d[29]),"+f"(d[30]),"+f"(d[31]),"+f"(d[32]),"+f"(d[33]),"+f"(d[34]),"+f"(d[35]),"+f"(d[36]),
          "+f"(d[37]),"+f"(d[38]),"+f"(d[39]),"+f"(d[40]),"+f"(d[41]),"+f"(d[42]),"+f"(d[43]),"+f"(d[44]),"+f"(d[45]),"+f"(d[46]),"+f"(d[47]),"+f"(d[48]),
          "+f"(d[49]),"+f"(d[50]),"+f"(d[51]),"+f"(d[52]),"+f"(d[53]),"+f"(d[54]),"+f"(d[55]),"+f"(d[56]),"+f"(d[57]),"+f"(d[58]),"+f"(d[59]),"+f"(d[60]),
          "+f"(d[61]),"+f"(d[62]),"+f"(d[63])
        : "l"(da), "l"(db), "r"(acc));
}
__device__ __forceinline__ void wgmma_ss_n64(float* d, uint64_t da, uint64_t db, int acc) {
    asm volatile("{\n.reg .pred p;\nsetp.ne.b32 p, %34, 0;\nwgmma.mma_async.sync.aligned.m64n64k16.f32.bf16.bf16 {"
        "%0,%1,%2,%3,%4,%5,%6,%7,%8,%9,%10,%11,%12,%13,%14,%15,%16,%17,%18,%19,%20,%21,%22,%23,%24,%25,%26,%27,%28,%29,%30,%31"
        "}, %32, %33, p, 1, 1, 0, 1;\n}\n"
        : "+f"(d[0]),"+f"(d[1]),"+f"(d[2]),"+f"(d[3]),"+f"(d[4]),"+f"(d[5]),"+f"(d[6]),"+f"(d[7]),"+f"(d[8]),"+f"(d[9]),"+f"(d[10]),"+f"(d[11]),"+f"(d[12]),
          "+f"(d[13]),"+f"(d[14]),"+f"(d[15]),"+f"(d[16]),"+f"(d[17]),"+f"(d[18]),"+f"(d[19]),"+f"(d[20]),"+f"(d[21]),"+f"(d[22]),"+f"(d[23]),"+f"(d[24]),
          "+f"(d[25]),"+f"(d[26]),"+f"(d[27]),"+f"(d[28]),"+f"(d[29]),"+f"(d[30]),"+f"(d[31])
        : "l"(da), "l"(db), "r"(acc));
}
__device__ __forceinline__ void wgmma_rs_n64_zero(float* d, const uint32_t* a, uint64_t db) {
    asm volatile("wgmma.mma_async.sync.aligned.m64n64k16.f32.bf16.bf16 {"
        "%0,%1,%2,%3,%4,%5,%6,%7,%8,%9,%10,%11,%12,%13,%14,%15,%16,%17,%18,%19,%20,%21,%22,%23,%24,%25,%26,%27,%28,%29,%30,%31"
        "}, {%32,%33,%34,%35}, %36, 0, 1, 1, 0;\n"
        : "=f"(d[0]),"=f"(d[1]),"=f"(d[2]),"=f"(d[3]),"=f"(d[4]),"=f"(d[5]),"=f"(d[6]),"=f"(d[7]),"=f"(d[8]),"=f"(d[9]),"=f"(d[10]),"=f"(d[11]),"=f"(d[12]),
          "=f"(d[13]),"=f"(d[14]),"=f"(d[15]),"=f"(d[16]),"=f"(d[17]),"=f"(d[18]),"=f"(d[19]),"=f"(d[20]),"=f"(d[21]),"=f"(d[22]),"=f"(d[23]),"=f"(d[24]),
          "=f"(d[25]),"=f"(d[26]),"=f"(d[27]),"=f"(d[28]),"=f"(d[29]),"=f"(d[30]),"=f"(d[31])
        : "r"(a[0]), "r"(a[1]), "r"(a[2]), "r"(a[3]), "l"(db));
}
__device__ __forceinline__ void wgmma_rs_n64_acc(float* d, const uint32_t* a, uint64_t db) {
    asm volatile("wgmma.mma_async.sync.aligned.m64n64k16.f32.bf16.bf16 {"
        "%0,%1,%2,%3,%4,%5,%6,%7,%8,%9,%10,%11,%12,%13,%14,%15,%16,%17,%18,%19,%20,%21,%22,%23,%24,%25,%26,%27,%28,%29,%30,%31"
        "}, {%32,%33,%34,%35}, %36, 1, 1, 1, 0;\n"
        : "+f"(d[0]),"+f"(d[1]),"+f"(d[2]),"+f"(d[3]),"+f"(d[4]),"+f"(d[5]),"+f"(d[6]),"+f"(d[7]),"+f"(d[8]),"+f"(d[9]),"+f"(d[10]),"+f"(d[11]),"+f"(d[12]),
          "+f"(d[13]),"+f"(d[14]),"+f"(d[15]),"+f"(d[16]),"+f"(d[17]),"+f"(d[18]),"+f"(d[19]),"+f"(d[20]),"+f"(d[21]),"+f"(d[22]),"+f"(d[23]),"+f"(d[24]),
          "+f"(d[25]),"+f"(d[26]),"+f"(d[27]),"+f"(d[28]),"+f"(d[29]),"+f"(d[30]),"+f"(d[31])
        : "r"(a[0]), "r"(a[1]), "r"(a[2]), "r"(a[3]), "l"(db));
}
__device__ __forceinline__ void wgmma_rs_n24_acc(float* d, const uint32_t* a, uint64_t db) {
    asm volatile("wgmma.mma_async.sync.aligned.m64n24k16.f32.bf16.bf16 {"
        "%0,%1,%2,%3,%4,%5,%6,%7,%8,%9,%10,%11"
        "}, {%12,%13,%14,%15}, %16, 1, 1, 1, 1;\n"
        : "+f"(d[0]),"+f"(d[1]),"+f"(d[2]),"+f"(d[3]),"+f"(d[4]),"+f"(d[5]),"+f"(d[6]),"+f"(d[7]),"+f"(d[8]),"+f"(d[9]),"+f"(d[10]),"+f"(d[11])
        : "r"(a[0]), "r"(a[1]), "r"(a[2]), "r"(a[3]), "l"(db));
}
__device__ __forceinline__ void wgmma_rs_n24_zero(float* d, const uint32_t* a, uint64_t db) {
    asm volatile("wgmma.mma_async.sync.aligned.m64n24k16.f32.bf16.bf16 {"
        "%0,%1,%2,%3,%4,%5,%6,%7,%8,%9,%10,%11"
        "}, {%12,%13,%14,%15}, %16, 0, 1, 1, 1;\n"
        : "=f"(d[0]),"=f"(d[1]),"=f"(d[2]),"=f"(d[3]),"=f"(d[4]),"=f"(d[5]),"=f"(d[6]),"=f"(d[7]),"=f"(d[8]),"=f"(d[9]),"=f"(d[10]),"=f"(d[11])
        : "r"(a[0]), "r"(a[1]), "r"(a[2]), "r"(a[3]), "l"(db));
}

constexpr int OFF_ONES = 131072;
constexpr int OFF_RING = OFF_ONES + 4096;
constexpr int NRING = 5;
constexpr int OFF_B2 = OFF_RING + NRING * 16384;
constexpr int OFF_CS = OFF_B2 + 2048;
constexpr int OFF_RS = OFF_CS + 2560;
constexpr int OFF_BAR = OFF_RS + 1024;
enum { B_FULL = 0, B_A = 40, B_EMPTY = 48, B_TILE = 53, B_PART = 58, B_STATS = 59, B_QKV = 60, B_AFREE = 61, B_KV = 65,
       B_RING = 73, B_O = 78, B_DONE = 86, B_NUM = 87 };
constexpr int SMEM_BYTES = OFF_BAR + B_NUM * 8 + 1024;
constexpr unsigned FIXED_MASK = 0xB5;
constexpr float P71 = 2361183241434822606848.0f, M71 = 4.235164736271502e-22f;

__device__ __forceinline__ uint32_t exp2_fixed(float lo, float hi, uint32_t half2) {
    uint32_t y, g, d;
    asm("cvt.pack.sat.s16.s32 %0, %1, %2;" : "=r"(y) : "r"(__float_as_uint(hi)), "r"(__float_as_uint(lo)));
    asm("lop3.b32 %0, %1, 0x007F007F, %2, 0xEA;" : "=r"(g) : "r"(y), "r"(half2));
    asm("fma.rn.bf16x2 %0, %1, %2, %3;" : "=r"(d) : "r"(y), "r"(g), "r"(y & 0xFF80FF80u));
    return d;
}
__device__ __forceinline__ uint32_t k_tile_addr(uint32_t base, int tile) {
    const int c = tile >> 2;
    return base + ((tile & 2) ? 98304 + c * 4096 : (2 * c + 1) * 4096) + (tile & 1) * 2048;
}
__device__ __forceinline__ int stage_of(int t, int j) { return t == 0 ? j + (j >> 1) : (t == 1 && j < 4) ? 3 * j + 2 : 8 * t + j; }
__device__ __forceinline__ int kblk_of(int t, int j) { return t == 4 ? (0x37521640u >> (4 * j)) & 7 : j; }

__global__ void __cluster_dims__(2, 1, 1) __launch_bounds__(640, 1)
mega_kernel(const __nv_bfloat16* __restrict__ x, const __nv_bfloat16* __restrict__ wqkv, const __nv_bfloat16* __restrict__ w1,
            const __nv_bfloat16* __restrict__ w3, __nv_bfloat16* __restrict__ out,
            const __grid_constant__ CUtensorMap mx, const __grid_constant__ CUtensorMap mqkv, const __grid_constant__ CUtensorMap mw1,
            const __grid_constant__ CUtensorMap mw3, const __grid_constant__ CUtensorMap mw2, const __grid_constant__ CUtensorMap mwo,
            uint32_t half2) {
    extern __shared__ uint8_t smem_raw[];
    const uint32_t sb = (smem_u32(smem_raw) + 1023) & ~1023u;
    const uint32_t bars = sb + OFF_BAR, ring = sb + OFF_RING;
    const int tid = threadIdx.x, lane = tid & 31, g = lane >> 2, t4 = lane & 3;
    const int warp = __shfl_sync(0xffffffffu, tid >> 5, 0), wg = warp >> 2, wq = warp & 3;
    const int rank = blockIdx.x & 1, grp = (blockIdx.x >> 1) & 7, mblk = (blockIdx.x >> 4) * 2 + rank;
    const int nq = grp < 4 ? 2 : 1;
    const int qt0 = grp < 4 ? 2 * grp : 4 + grp;
    const int gu0 = (grp < 4 ? 3 * grp : 4 * grp - 4) - nq;
    const int head = blockIdx.x >> 2, qb = blockIdx.x & 3;

    if (warp == 16) {
        if (lane == 0) TSTAMP(0);
#pragma unroll 1
        for (int i = lane; i < B_NUM; i += 32) {
            const int c = (i >= B_EMPTY && i < B_TILE) || i == B_AFREE || i == B_DONE ? 4 : (i >= B_TILE && i <= B_PART) ? 8 : (i > B_AFREE && i < B_KV) ? 2 : 1;
            mbar_init(bars + 8 * i, c);
        }
        asm volatile("fence.mbarrier_init.release.cluster;" ::: "memory");
        __syncwarp();
        if (elect_one()) {
            fence_async_smem();
#pragma unroll 1
            for (int kb = 0; kb < 2; kb++) { mbar_expect(bars + 8 * (B_A + kb), 16384); tma2d(sb + kb * 16384, &mx, kb * 64, mblk * 128, bars + 8 * (B_A + kb)); }
        }
    }
    if (tid < 256) {
        asm volatile("st.shared.v4.b32 [%0], {%1,%1,%1,%1};" :: "r"(sb + OFF_ONES + tid * 16), "r"(0x3F803F80u) : "memory");
        if (tid < 128) {
            const bool fx = (FIXED_MASK >> (tid >> 4)) & 1;
            uint32_t a = fx ? pack_bf16(M71, M71) : pack_bf16(P71, P71);
            uint32_t b = fx ? pack_bf16(M71, 47.0f * M71) : pack_bf16(P71, -79.5f * P71);
            uint32_t c = fx ? 0u : pack_bf16(0.08214f * P71, 0.f);
            if (tid & 8) a = b = c = 0;
            asm volatile("st.shared.v4.b32 [%0], {%1,%2,%3,%4};" :: "r"(sb + OFF_B2 + tid * 16), "r"(a), "r"(b), "r"(c), "r"(0) : "memory");
        }
        fence_async_smem();
    }
    __syncthreads();
    asm volatile("barrier.cluster.arrive.relaxed.aligned;" ::: "memory");

    if (wg < 4) {
        const int pair = wg >> 1, half = wg & 1;
        if (pair == 1) {
            const int w8 = warp - 8;
            uint4 v[16];
            uint32_t* w = reinterpret_cast<uint32_t*>(v);
            if (w8 < 5) {
                const int u = mblk * 5 + w8, blk = u >> 3, kp = u & 7, t = blk >> 1;
                const __nv_bfloat16* src; int ld;
                if (t < nq) { src = wqkv + (qt0 * 2 + blk) * 64; ld = 3 * DM; }
                else        { src = ((blk & 1) ? w3 : w1) + (gu0 + t) * 64; ld = FF; }
                src += (size_t)(kp * 64 + (lane >> 3)) * ld + (lane & 7) * 8;
#pragma unroll
                for (int j = 0; j < 16; j++) v[j] = __ldg(reinterpret_cast<const uint4*>(src + (size_t)j * 4 * ld));
                float c[8];
#pragma unroll
                for (int e = 0; e < 4; e++) {
                    float a = 0.f, b = 0.f;
#pragma unroll
                    for (int j = 0; j < 16; j++) { a += bf_lo(w[4 * j + e]); b += bf_hi(w[4 * j + e]); }
                    a += __shfl_xor_sync(0xffffffffu, a, 8); b += __shfl_xor_sync(0xffffffffu, b, 8);
                    a += __shfl_xor_sync(0xffffffffu, a, 16); b += __shfl_xor_sync(0xffffffffu, b, 16);
                    c[2 * e] = a; c[2 * e + 1] = b;
                }
                if (lane < 16) g_cs[(grp * 8 + kp) * 160 + blk * 16 + (lane & 7) * 2 + (lane >> 3)] =
                    lane < 8 ? make_float4(c[0], c[1], c[2], c[3]) : make_float4(c[4], c[5], c[6], c[7]);
            } else if (w8 < 7) {
                const int row = mblk * 128 + grp * 16 + (w8 - 5) * 8 + g;
                const uint4* src = reinterpret_cast<const uint4*>(x + (size_t)row * DM) + t4;
#pragma unroll
                for (int j = 0; j < 16; j++) v[j] = __ldg(src + j * 4);
                const float x0 = __shfl_sync(0xffffffffu, bf_lo(w[0]), lane & 28);
                float s0 = 0.f, s1 = 0.f, v0 = 0.f, v1 = 0.f;
#pragma unroll
                for (int j = 0; j < 64; j++) { const float a = bf_lo(w[j]) - x0, b = bf_hi(w[j]) - x0; s0 += a; s1 += b; v0 = fmaf(a, a, v0); v1 = fmaf(b, b, v1); }
                s0 += s1; v0 += v1;
                s0 += __shfl_xor_sync(0xffffffffu, s0, 1); v0 += __shfl_xor_sync(0xffffffffu, v0, 1);
                s0 += __shfl_xor_sync(0xffffffffu, s0, 2); v0 += __shfl_xor_sync(0xffffffffu, v0, 2);
                s0 *= 1.0f / DM;
                const float mean = x0 + s0, var = fmaxf(fmaf(-s0, s0, v0 * (1.0f / DM)), 0.f);
                if (t4 == 0) g_rs[row] = make_float2(bf_round(mean), bf_round(sqrtf(bf_round(bf_round(var) + 1e-5f))));
            }
            __syncwarp();
            if (elect_one()) mbar_arrive(bars + 8 * B_PART);
        }
        asm volatile("barrier.cluster.wait.aligned;" ::: "memory");

        uint32_t q[4];
        {
            float acc[64];
            const int rowblk = mblk * 2 + half, tile16 = rowblk * 4 + wq;
#pragma unroll 1
            for (int t = pair; t < 5; t += 2) {
                int prev = 0;
#pragma unroll 1
                for (int j = 0; j < 8; j++) {
                    const int n = stage_of(t, j), kb = kblk_of(t, j), slot = n % NRING;
                    if (t < 2) mbar_wait(bars + 8 * (B_A + kb), 0);
                    mbar_wait(bars + 8 * (B_FULL + n), 0);
                    if (tid == 0 && n == 0) TSTAMP(1);
                    const uint64_t da = mkdesc(sb + kb * 16384 + half * 8192, 16, 1024, 1), db = mkdesc(ring + slot * 16384, 8192, 1024, 1);
                    wg_fence();
#pragma unroll
                    for (int k = 0; k < 4; k++) wgmma_ss_n128(acc, da + k * 2, db + k * 128, (j | k) != 0);
                    wg_commit();
                    if (j > 0) {
                        wg_wait<1>();
                        if (wq < 2 && elect_one()) mbar_arrive_cluster(bars + 8 * (B_EMPTY + prev), wq);
                        if (t == 4 && wq == 2 && (j == 3 || j == 4 || j == 7) && elect_one()) mbar_arrive(bars + 8 * (B_AFREE + (j == 7 ? 2 : j - 3)));
                    }
                    prev = slot;
                }
                if (t >= 3) {
                    mbar_wait(bars + 8 * B_QKV, 0);
                    const uint4 v = __ldcg(g_q + (head * 128 + (qb * 8 + wg) * 4 + wq) * 32 + lane); q[0] = v.x; q[1] = v.y; q[2] = v.z; q[3] = v.w;
                }
                wg_wait<0>();
                if (wq < 2 && elect_one()) mbar_arrive_cluster(bars + 8 * (B_EMPTY + prev), wq);
                if (t >= 3 && wq == 2 && elect_one()) mbar_arrive(bars + 8 * (B_AFREE + (t == 4 ? 3 : 0)));
                pin<64>(acc);
                if (wq == 0 && half == 0 && lane == 0) TSTAMP(2 + 2 * t);
                if (t < 2) mbar_wait(bars + 8 * B_STATS, 0);
                float m0, d0, m1, d1;
                asm volatile("ld.shared.v2.f32 {%0,%1}, [%2];" : "=f"(m0), "=f"(d0) : "r"(sb + OFF_RS + (half * 64 + wq * 16 + g) * 8));
                asm volatile("ld.shared.v2.f32 {%0,%1}, [%2];" : "=f"(m1), "=f"(d1) : "r"(sb + OFF_RS + (half * 64 + wq * 16 + g + 8) * 8));
#pragma unroll
                for (int j = 0; j < 16; j++) {
                    float c0, c1;
                    asm volatile("ld.shared.v2.f32 {%0,%1}, [%2];" : "=f"(c0), "=f"(c1) : "r"(sb + OFF_CS + (t * 128 + j * 8 + t4 * 2) * 4));
                    acc[4 * j] = fmaf(-m0, c0, acc[4 * j]); acc[4 * j + 1] = fmaf(-m0, c1, acc[4 * j + 1]);
                    acc[4 * j + 2] = fmaf(-m1, c0, acc[4 * j + 2]); acc[4 * j + 3] = fmaf(-m1, c1, acc[4 * j + 3]);
                }
                float r0 = 1.0f / d0, r1 = 1.0f / d1;
                if (t < nq) {
                    const int qt = qt0 + t, h0 = (qt & 3) * 8;
                    if (qt < 4) {
                        r0 *= 0.25f * 1.4426950408889634f * M71; r1 *= 0.25f * 1.4426950408889634f * M71;
                    } else if (qt < 8) {
                        r0 *= ((FIXED_MASK >> (2 * wq)) & 1) ? M71 : P71; r1 *= ((FIXED_MASK >> (2 * wq + 1)) & 1) ? M71 : P71;
                    }
                    uint32_t* p; int s8, sh;
                    if (qt < 8) { p = reinterpret_cast<uint32_t*>(g_k + h0 * 4096) + tile16 * 128 + lane; s8 = 64; sh = 32; }
                    else        { p = reinterpret_cast<uint32_t*>(g_v + h0 * 4096) + tile16 * 64 + lane;  s8 = 32; sh = 8192; }
#pragma unroll
                    for (int hh = 0; hh < 8; hh++) {
                        const float* a = acc + hh * 8;
                        const uint32_t e0 = pack_bf16(a[0] * r0, a[1] * r0), e1 = pack_bf16(a[2] * r1, a[3] * r1);
                        const uint32_t e2 = pack_bf16(a[4] * r0, a[5] * r0), e3 = pack_bf16(a[6] * r1, a[7] * r1);
                        if (qt < 4) g_q[((h0 + hh) * 128 + tile16) * 32 + lane] = make_uint4(e0, e1, e2, e3);
                        else { uint32_t* pp = p + hh * 16384; pp[0] = e0; pp[s8] = e1; pp[sh] = e2; pp[sh + s8] = e3; }
                    }
                } else {
                    uint32_t* p = reinterpret_cast<uint32_t*>(g_h + (rowblk * 28 + gu0 + t) * 512) + wq * 512 + lane;
                    r0 *= -1.4426950408889634f; r1 *= -1.4426950408889634f; d0 *= d0; d1 *= d1;
#pragma unroll
                    for (int j = 0; j < 8; j++) {
                        const float* a = acc + j * 4; const float* b = a + 32;
                        p[j * 32] = pack_bf16(a[0] * b[0] * rcpf(fmaf(ex2f(a[0] * r0), d0, d0)), a[1] * b[1] * rcpf(fmaf(ex2f(a[1] * r0), d0, d0)));
                        p[256 + j * 32] = pack_bf16(a[2] * b[2] * rcpf(fmaf(ex2f(a[2] * r1), d1, d1)), a[3] * b[3] * rcpf(fmaf(ex2f(a[3] * r1), d1, d1)));
                    }
                }
                __syncwarp();
                if (elect_one()) mbar_arrive(bars + 8 * (B_TILE + t));
                if (wq == 0 && half == 0 && lane == 0) TSTAMP(3 + 2 * t);
            }
        }
        const uint64_t db2 = mkdesc(sb + OFF_B2, 128, 256, 0);
#pragma unroll 1
        for (int round = 0; round < 2; round++) {
            const int rowblk = qb * 8 + round * 4 + wg;
            const uint4 qn = __ldcg(g_q + (head * 128 + (qb * 8 + 4 + wg) * 4 + wq) * 32 + lane);
            float o[12];
            int nmax = 1;
#pragma unroll 1
            for (;;) {
                float s[32]; uint32_t p[16], q2[4];
                float m0 = -INFINITY, m1 = -INFINITY, f0 = -INFINITY, f1 = -INFINITY;
                mbar_wait(bars + 8 * B_KV, 0);
#pragma unroll 1
                for (int t = 0; t < nmax; t++) {
                    wg_fence();
                    wgmma_rs_n64_zero(s, q, mkdesc(k_tile_addr(sb, t), 128, 256, 0));
                    wg_commit();
                    wg_wait<0>();
                    pin<32>(s);
#pragma unroll
                    for (int i = 0; i < 8; i++) {
                        if ((FIXED_MASK >> i) & 1) { f0 = fmaxf(f0, fmaxf(s[4 * i], s[4 * i + 1])); f1 = fmaxf(f1, fmaxf(s[4 * i + 2], s[4 * i + 3])); }
                        else                       { m0 = fmaxf(m0, fmaxf(s[4 * i], s[4 * i + 1])); m1 = fmaxf(m1, fmaxf(s[4 * i + 2], s[4 * i + 3])); }
                    }
                }
                m0 = fmaxf(m0, f0 * P71 * P71); m1 = fmaxf(m1, f1 * P71 * P71);
                m0 = fmaxf(m0, __shfl_xor_sync(0xffffffffu, m0, 1)); m0 = fmaxf(m0, __shfl_xor_sync(0xffffffffu, m0, 2));
                m1 = fmaxf(m1, __shfl_xor_sync(0xffffffffu, m1, 1)); m1 = fmaxf(m1, __shfl_xor_sync(0xffffffffu, m1, 2));
#pragma unroll
                for (int r = 0; r < 2; r++) {
                    const float m = -rintf(r ? m1 : m0), mh = bf_round(m), mm = bf_round(m - mh), ml = m - mh - mm;
                    q2[r] = t4 == 0 ? pack_bf16(mh * M71, mm * M71) : t4 == 1 ? pack_bf16(ml * M71, M71) : t4 == 2 ? pack_bf16(M71, 0.f) : 0u;
                    q2[2 + r] = q2[r];
                }
#pragma unroll
                for (int i = 0; i < 12; i++) o[i] = 0.f;
                pin<12>(o); pin<4>(q2);
                if (wq == 0 && half == 0 && lane == 0) TSTAMP(12 + 4 * round + pair);
#pragma unroll 1
                for (int c = 0; c < 8; c++) {
                    mbar_wait(bars + 8 * (B_KV + c), 0);
                    const uint64_t dk0 = mkdesc(sb + (2 * c + 1) * 4096, 128, 256, 0), dk1 = mkdesc(sb + 98304 + c * 4096, 128, 256, 0);
                    const uint64_t dv = mkdesc(sb + 2 * c * 4096, 128, 65536 - c * 4096, 0);
#pragma unroll
                    for (int t = 0; t < 4; t++) {
                        wg_fence();
                        wgmma_rs_n64_zero(s, q, (t & 2 ? dk1 : dk0) + (t & 1) * 128);
                        wgmma_rs_n64_acc(s, q2, db2);
                        wg_commit();
                        wg_wait<0>();
                        pin<32>(s); pin<16>(p);
#pragma unroll
                        for (int i = 0; i < 16; i++) {
                            if ((FIXED_MASK >> (i >> 1)) & 1) p[i] = exp2_fixed(s[2 * i], s[2 * i + 1], half2);
                            else                              p[i] = pack_bf16(ex2f(s[2 * i]), ex2f(s[2 * i + 1]));
                        }
                        wg_fence();
#pragma unroll
                        for (int k = 0; k < 4; k++) wgmma_rs_n24_acc(o, p + 4 * k, dv + (t * 4 + k) * 16);
                        wg_commit();
                    }
                }
                wg_wait<0>();
                pin<12>(o);
                float chk = 0.f;
#pragma unroll
                for (int i = 0; i < 12; i++) chk = fmaf(o[i], 0.f, chk);
                uint32_t bad;
                asm volatile("{\n.reg .pred p, q;\nsetp.neu.f32 q, %1, 0f00000000;\nbar.red.or.pred p, %2, 128, q;\nselp.u32 %0, 1, 0, p;\n}" : "=r"(bad) : "f"(chk), "r"(1 + wg) : "memory");
                if (!__any_sync(0xffffffffu, bad) || nmax != 1) break;
                nmax = 32;
            }
            const float r0 = 1.0f / o[8], r1 = 1.0f / o[10];
            uint32_t* po = reinterpret_cast<uint32_t*>(g_o + (rowblk * 8 + (head >> 2)) * 512) + wq * 512 + (head & 3) * 64 + lane;
            po[0] = pack_bf16(o[0] * r0, o[1] * r0); po[256] = pack_bf16(o[2] * r1, o[3] * r1);
            po[32] = pack_bf16(o[4] * r0, o[5] * r0); po[288] = pack_bf16(o[6] * r1, o[7] * r1);
            bar_sync(1 + wg, 128);
            if (wq == 0 && elect_one()) {
                if (round == 1) mbar_arrive(bars + 8 * B_DONE);
                signal_cnt(C_O + rowblk);
            }
            q[0] = qn.x; q[1] = qn.y; q[2] = qn.z; q[3] = qn.w;
            if (wq == 0 && half == 0 && lane == 0) TSTAMP(14 + 4 * round + pair);
        }
    } else {
        asm volatile("barrier.cluster.wait.aligned;" ::: "memory");
        if (wq == 0) {
#pragma unroll 1
            for (int n = 0; n < 40; n++) {
                int t, j;
                if (n < 12) { const int a = n / 3, b = n - 3 * a; t = b == 2; j = t ? a : 2 * a + b; } else { t = n >> 3; j = n & 7; }
                const int slot = n % NRING;
                if (n >= NRING) mbar_wait(bars + 8 * (B_EMPTY + slot), (n / NRING - 1) & 1);
                if (elect_one()) {
                    mbar_expect(bars + 8 * (B_FULL + n), 16384);
                    const CUtensorMap* m = t < nq ? &mqkv : rank ? &mw3 : &mw1;
                    const int col = t < nq ? (qt0 + t) * 128 + rank * 64 : (gu0 + t) * 64;
                    tma2d_mc(ring + slot * 16384 + rank * 8192, m, col, kblk_of(t, j) * 64, bars + 8 * (B_FULL + n));
                    if (n < 3) {
#pragma unroll 1
                        for (int kb = 2 + 2 * n; kb < 4 + 2 * n; kb++) { mbar_expect(bars + 8 * (B_A + kb), 16384); tma2d(sb + kb * 16384, &mx, kb * 64, mblk * 128, bars + 8 * (B_A + kb)); }
                    }
                }
            }
        } else if (wq == 1) {
            wait_cnt(C_COL + grp, 16, 100);
#pragma unroll
            for (int i = 0; i < 5; i++) {
                float4 a = make_float4(0.f, 0.f, 0.f, 0.f);
#pragma unroll
                for (int kp = 0; kp < 8; kp++) { const float4 b = __ldcg(g_cs + (grp * 8 + kp) * 160 + i * 32 + lane); a.x += b.x; a.y += b.y; a.z += b.z; a.w += b.w; }
                asm volatile("st.shared.v4.f32 [%0], {%1,%2,%3,%4};" :: "r"(sb + OFF_CS + (i * 32 + lane) * 16), "f"(a.x), "f"(a.y), "f"(a.z), "f"(a.w) : "memory");
            }
            wait_cnt(C_ROW + mblk, 8, 100);
#pragma unroll
            for (int i = 0; i < 2; i++) {
                const float4 a = __ldcg(reinterpret_cast<const float4*>(g_rs + mblk * 128) + i * 32 + lane);
                asm volatile("st.shared.v4.f32 [%0], {%1,%2,%3,%4};" :: "r"(sb + OFF_RS + (i * 32 + lane) * 16), "f"(a.x), "f"(a.y), "f"(a.z), "f"(a.w) : "memory");
            }
            __syncwarp();
            if (elect_one()) { mbar_arrive(bars + 8 * B_STATS); TSTAMP(28); }
#pragma unroll 1
            for (int i = 0; i < 3; i++) wait_cnt(C_QKV + i * 4 + (head >> 3), 16, 200);
            if (elect_one()) { mbar_arrive(bars + 8 * B_QKV); TSTAMP(29); }
            fence_async_all();
            const uint8_t* gk = reinterpret_cast<const uint8_t*>(g_k + head * 4096);
            const uint8_t* gv = reinterpret_cast<const uint8_t*>(g_v + head * 4096);
#pragma unroll 1
            for (int c = 0; c < 8; c++) {
                if (!(c & 1)) mbar_wait(bars + 8 * (B_AFREE + (c >> 1)), 0);
                if (elect_one()) {
                    const uint32_t b = bars + 8 * (B_KV + c);
                    mbar_expect(b, 16384);
                    bulk_load(sb + (2 * c + 1) * 4096, gk + c * 8192, 4096, b);
                    bulk_load(sb + 2 * c * 4096, gv + c * 4096, 4096, b);
                    bulk_load(sb + 65536 + c * 4096, gv + 32768 + c * 4096, 4096, b);
                    bulk_load(sb + 98304 + c * 4096, gk + c * 8192 + 4096, 4096, b);
                }
            }
        } else if (wq == 2) {
            mbar_wait(bars + 8 * B_PART, 0);
            if (elect_one()) { signal_cnt(C_COL + grp); signal_cnt(C_ROW + mblk); }
#pragma unroll 1
            for (int t = 0; t < 5; t++) {
                mbar_wait(bars + 8 * (B_TILE + t), 0);
                if (elect_one()) signal_cnt(t < nq ? C_QKV + qt0 + t : C_H + mblk);
            }
        }
        bar_sync(5, 128);
        const int cb = blockIdx.x & 7, pr = blockIdx.x >> 3;
        const int rb0 = (pr >> 2) * 8 + (pr & 3);
        uint32_t gate[2][16];
        float acc[32];
        if (wq == 0) {
            wait_cnt(C_H + (rb0 >> 1), 28, 200);
            wait_cnt(C_H + (rb0 >> 1) + 2, 28, 200);
            if (elect_one()) {
                TSTAMP(20);
                fence_async_all();
#pragma unroll 1
                for (int i = 0; i < NRING; i++) {
                    mbar_expect(bars + 8 * (B_RING + i), 16384);
                    bulk_load(ring + i * 16384, g_h + (rb0 * 28 + i) * 512, 8192, bars + 8 * (B_RING + i));
                    tma2d(ring + i * 16384 + 8192, &mw2, cb * 64, i * 64, bars + 8 * (B_RING + i));
                }
            }
        }
        int st = 0; uint32_t ph = 0;
#pragma unroll
        for (int tl = 0; tl < 2; tl++) {
#pragma unroll 1
            for (int kb = 0; kb < 28; kb++) {
                mbar_wait(bars + 8 * (B_RING + st), ph);
                const uint64_t da = mkdesc(ring + st * 16384, 128, 1024, 0), db = mkdesc(ring + st * 16384 + 8192, 8192, 1024, 1);
                wg_fence();
#pragma unroll
                for (int k = 0; k < 4; k++) wgmma_ss_n64(acc, da + k * 16, db + k * 128, (kb | k) != 0);
                wg_commit();
                wg_wait<0>();
                bar_sync(5, 128);
                const int nx = tl * 28 + kb + NRING;
                if (wq == 0 && nx < 56 && elect_one()) {
                    const int ntl = nx >= 28, nkb = nx - ntl * 28;
                    mbar_expect(bars + 8 * (B_RING + st), 16384);
                    bulk_load(ring + st * 16384, g_h + ((rb0 + 4 * ntl) * 28 + nkb) * 512, 8192, bars + 8 * (B_RING + st));
                    tma2d(ring + st * 16384 + 8192, &mw2, cb * 64, nkb * 64, bars + 8 * (B_RING + st));
                }
                if (++st == NRING) { st = 0; ph ^= 1; }
            }
            pin<32>(acc);
#pragma unroll
            for (int i = 0; i < 16; i++) gate[tl][i] = pack_bf16(siluf(acc[2 * i]), siluf(acc[2 * i + 1]));
        }
        if (tid == 512) TSTAMP(21);
        const uint32_t bar_wo = bars + 8 * (B_RING + st);
        if (wq == 0 && elect_one()) {
            mbar_expect(bar_wo, 65536);
#pragma unroll 1
            for (int i = 0; i < 8; i++) tma2d(ring + i * 8192, &mwo, cb * 64, i * 64, bar_wo);
        }
#pragma unroll
        for (int tl = 0; tl < 2; tl++) {
            const int rb = rb0 + 4 * tl;
            uint32_t xr[16];
            const uint32_t* px = reinterpret_cast<const uint32_t*>(x + (size_t)(rb * 64 + wq * 16 + g) * DM + cb * 64) + t4;
#pragma unroll
            for (int j = 0; j < 8; j++) { xr[2 * j] = __ldg(px + j * 4); xr[2 * j + 1] = __ldg(px + 8 * DM / 2 + j * 4); }
            if (wq == 0) {
                if (tl == 1) mbar_wait(bars + 8 * B_DONE, 0);
                wait_cnt(C_O + rb, 32, tl ? 20 : 200);
                if (elect_one()) {
                    fence_async_all();
                    TSTAMP(22 + 2 * tl);
#pragma unroll 1
                    for (int i = 0; i < (tl ? 8 : 2); i++) {
                        mbar_expect(bars + 8 * (B_O + i), 8192);
                        bulk_load((tl ? sb : ring + 65536) + i * 8192, g_o + (rb * 8 + i) * 512, 8192, bars + 8 * (B_O + i));
                    }
                }
            }
            if (tl == 0) mbar_wait(bar_wo, ph);
#pragma unroll 1
            for (int kb = 0; kb < 8; kb++) {
                mbar_wait(bars + 8 * (B_O + kb), tl);
                const uint32_t a = tl == 0 ? ring + 65536 + (kb & 1) * 8192 : sb + kb * 8192;
                const uint64_t da = mkdesc(a, 128, 1024, 0), db = mkdesc(ring + kb * 8192, 8192, 1024, 1);
                wg_fence();
#pragma unroll
                for (int k = 0; k < 4; k++) wgmma_ss_n64(acc, da + k * 16, db + k * 128, (kb | k) != 0);
                wg_commit();
                if (tl == 0) {
                    wg_wait<0>();
                    bar_sync(5, 128);
                    if (wq == 0 && kb < 6 && elect_one()) { mbar_expect(bars + 8 * (B_O + kb + 2), 8192); bulk_load(a, g_o + (rb * 8 + kb + 2) * 512, 8192, bars + 8 * (B_O + kb + 2)); }
                }
            }
            unsigned ticket = 0;
            if (tl == 1 && tid == 512 + 96) ticket = atomicInc(&g_ticket, 127);
            wg_wait<0>();
            pin<32>(acc);
            uint32_t* po = reinterpret_cast<uint32_t*>(out + (size_t)(rb * 64 + wq * 16 + g) * DM + cb * 64) + t4;
#pragma unroll
            for (int i = 0; i < 16; i++) {
                const uint32_t r = pack_bf16(fmaf(acc[2 * i], bf_lo(gate[tl][i]), bf_lo(xr[i])), fmaf(acc[2 * i + 1], bf_hi(gate[tl][i]), bf_hi(xr[i])));
                po[(i & 1) * (8 * DM / 2) + (i >> 1) * 4] = r;
            }
            if (tl == 1 && wq == 3 && __any_sync(0xffffffffu, ticket == 127)) {
#pragma unroll 1
                for (int i = lane; i < C_NUM; i += 32) g_cnt[i * 8] = 0;
            }
            if (tid == 512) TSTAMP(23 + 2 * tl);
        }
    }
}

typedef CUresult (*EncodeFn)(CUtensorMap*, CUtensorMapDataType, cuuint32_t, void*, const cuuint64_t*, const cuuint64_t*, const cuuint32_t*,
                             const cuuint32_t*, CUtensorMapInterleave, CUtensorMapSwizzle, CUtensorMapL2promotion, CUtensorMapFloatOOBfill);

void make_map(EncodeFn fn, CUtensorMap* m, const void* p, int rows, int cols, int box_rows) {
    cuuint64_t dims[2] = {(cuuint64_t)cols, (cuuint64_t)rows};
    cuuint64_t strides[1] = {(cuuint64_t)cols * 2};
    cuuint32_t box[2] = {64, (cuuint32_t)box_rows};
    cuuint32_t es[2] = {1, 1};
    fn(m, CU_TENSOR_MAP_DATA_TYPE_BFLOAT16, 2, const_cast<void*>(p), dims, strides, box, es, CU_TENSOR_MAP_INTERLEAVE_NONE,
       CU_TENSOR_MAP_SWIZZLE_128B, CU_TENSOR_MAP_L2_PROMOTION_L2_128B, CU_TENSOR_MAP_FLOAT_OOB_FILL_NONE);
}

}

extern "C" void kernel_launch(void* const* d_in, const int* in_sizes, int n_in, void* d_out, int out_size) {
    const __nv_bfloat16* x = (const __nv_bfloat16*)d_in[0];
    static EncodeFn fn = nullptr;
    if (!fn) {
        cudaDriverEntryPointQueryResult qr;
        cudaGetDriverEntryPoint("cuTensorMapEncodeTiled", (void**)&fn, cudaEnableDefault, &qr);
        cudaFuncSetAttribute(mega_kernel, cudaFuncAttributeMaxDynamicSharedMemorySize, SMEM_BYTES);
    }
    CUtensorMap mx, mqkv, mw1, mw3, mw2, mwo;
    make_map(fn, &mx, d_in[0], SEQ, DM, 128);
    make_map(fn, &mqkv, d_in[1], DM, 3 * DM, 64);
    make_map(fn, &mwo, d_in[2], DM, DM, 64);
    make_map(fn, &mw1, d_in[4], DM, FF, 64);
    make_map(fn, &mw3, d_in[5], DM, FF, 64);
    make_map(fn, &mw2, d_in[6], FF, DM, 64);
    mega_kernel<<<128, 640, SMEM_BYTES, cudaStreamPerThread>>>(x, (const __nv_bfloat16*)d_in[1], (const __nv_bfloat16*)d_in[4], (const __nv_bfloat16*)d_in[5],
                                                               (__nv_bfloat16*)d_out, mx, mqkv, mw1, mw3, mw2, mwo, 0x3F003F00u);
}
```

```cpp
#include <cuda_runtime.h>
#include <cuda_bf16.h>
#include <cuda.h>
#include <stdint.h>

namespace {

constexpr int SEQ = 2048, DM = 512, FF = 1792;

__device__ uint4 g_q[32 * 128 * 32];
__device__ uint4 g_k[32 * 4096];
__device__ uint4 g_v[32 * 4096];
__device__ uint4 g_h[32 * 28 * 512];
__device__ uint4 g_o[32 * 8 * 512];
__device__ float4 g_cs[40 * 8 * 32];
__device__ float2 g_rs[SEQ];
constexpr int C_COL = 0, C_ROW = 40, C_QKV = 56, C_H = 68, C_O = 84, C_NUM = 116;
__device__ unsigned g_cnt[C_NUM * 8];
__device__ unsigned g_ticket;
#define TSTAMP(i)

__device__ __forceinline__ uint32_t smem_u32(const void* p) { return (uint32_t)__cvta_generic_to_shared(p); }
__device__ __forceinline__ void mbar_init(uint32_t a, int c) { asm volatile("mbarrier.init.shared::cta.b64 [%0], %1;" :: "r"(a), "r"(c)); }
__device__ __forceinline__ void mbar_expect(uint32_t a, int b) { asm volatile("mbarrier.arrive.expect_tx.shared::cta.b64 _, [%0], %1;" :: "r"(a), "r"(b) : "memory"); }
__device__ __forceinline__ void mbar_arrive(uint32_t a) { asm volatile("mbarrier.arrive.shared::cta.b64 _, [%0];" :: "r"(a) : "memory"); }
__device__ __forceinline__ void mbar_arrive_cluster(uint32_t a, uint32_t cta) {
    asm volatile("{\n.reg .b32 r;\nmapa.shared::cluster.u32 r, %0, %1;\nmbarrier.arrive.shared::cluster.b64 _, [r];\n}" :: "r"(a), "r"(cta) : "memory");
}
__device__ __forceinline__ bool mbar_try(uint32_t a, uint32_t ph) {
    uint32_t ok;
    asm volatile("{\n.reg .pred p;\nmbarrier.try_wait.parity.shared::cta.b64 p, [%1], %2;\nselp.u32 %0, 1, 0, p;\n}" : "=r"(ok) : "r"(a), "r"(ph) : "memory");
    return ok;
}
__device__ __forceinline__ void mbar_wait(uint32_t a, uint32_t ph) {
    for (int n = 0; !__all_sync(0xffffffffu, mbar_try(a, ph)); n++) if (n > 4000000) __trap();
}
__device__ __forceinline__ bool elect_one() {
    uint32_t p;
    asm volatile("{\n.reg .pred P;\nelect.sync _|P, 0xffffffff;\nselp.u32 %0, 1, 0, P;\n}" : "=r"(p));
    return p;
}
__device__ __forceinline__ void signal_cnt(int c) {
    asm volatile("fence.acq_rel.gpu;\nred.relaxed.gpu.global.add.u32 [%0], 1;" :: "l"(g_cnt + c * 8) : "memory");
}
__device__ __forceinline__ void wait_cnt(int c, unsigned target, int ns) {
    for (int n = 0;; n++) {
        unsigned v;
        asm volatile("ld.acquire.gpu.global.u32 %0, [%1];" : "=r"(v) : "l"(g_cnt + c * 8) : "memory");
        if (__all_sync(0xffffffffu, v >= target)) break;
        if (n > 2000000) __trap();
        __nanosleep(ns);
    }
}
__device__ __forceinline__ void tma2d(uint32_t dst, const CUtensorMap* m, int c0, int c1, uint32_t bar) {
    asm volatile("cp.async.bulk.tensor.2d.shared::cluster.global.mbarrier::complete_tx::bytes [%0], [%1, {%3, %4}], [%2];"
                 :: "r"(dst), "l"(m), "r"(bar), "r"(c0), "r"(c1) : "memory");
}
__device__ __forceinline__ void tma2d_mc(uint32_t dst, const CUtensorMap* m, int c0, int c1, uint32_t bar) {
    asm volatile("cp.async.bulk.tensor.2d.shared::cluster.global.mbarrier::complete_tx::bytes.multicast::cluster [%0], [%1, {%3, %4}], [%2], %5;"
                 :: "r"(dst), "l"(m), "r"(bar), "r"(c0), "r"(c1), "h"((uint16_t)3) : "memory");
}
__device__ __forceinline__ void bulk_load(uint32_t dst, const void* src, int bytes, uint32_t bar) {
    asm volatile("cp.async.bulk.shared::cluster.global.mbarrier::complete_tx::bytes [%0], [%1], %2, [%3];"
                 :: "r"(dst), "l"(src), "r"(bytes), "r"(bar) : "memory");
}
__device__ __forceinline__ void bar_sync(int id, int n) { asm volatile("bar.sync %0, %1;" :: "r"(id), "r"(n) : "memory"); }
__device__ __forceinline__ void fence_async_smem() { asm volatile("fence.proxy.async.shared::cta;" ::: "memory"); }
__device__ __forceinline__ void fence_async_all() { asm volatile("fence.proxy.async;" ::: "memory"); }
__device__ __forceinline__ void wg_fence() { asm volatile("wgmma.fence.sync.aligned;" ::: "memory"); }
__device__ __forceinline__ void wg_commit() { asm volatile("wgmma.commit_group.sync.aligned;" ::: "memory"); }
template <int N> __device__ __forceinline__ void wg_wait() { asm volatile("wgmma.wait_group.sync.aligned %0;" :: "n"(N) : "memory"); }
template <int N> __device__ __forceinline__ void pin(float* d) {
#pragma unroll
    for (int i = 0; i < N; i++) asm volatile("" : "+f"(d[i]) :: "memory");
}
template <int N> __device__ __forceinline__ void pin(uint32_t* d) {
#pragma unroll
    for (int i = 0; i < N; i++) asm volatile("" : "+r"(d[i]) :: "memory");
}
__device__ __forceinline__ uint64_t mkdesc(uint32_t addr, uint32_t lbo, uint32_t sbo, uint32_t swz) {
    return (uint64_t)((addr & 0x3FFFF) >> 4) | ((uint64_t)(lbo >> 4) << 16) | ((uint64_t)(sbo >> 4) << 32) | ((uint64_t)swz << 62);
}
__device__ __forceinline__ float ex2f(float x) { float y; asm("ex2.approx.ftz.f32 %0, %1;" : "=f"(y) : "f"(x)); return y; }
__device__ __forceinline__ float rcpf(float x) { float y; asm("rcp.approx.ftz.f32 %0, %1;" : "=f"(y) : "f"(x)); return y; }
__device__ __forceinline__ uint32_t pack_bf16(float lo, float hi) { uint32_t r; asm("cvt.rn.bf16x2.f32 %0, %1, %2;" : "=r"(r) : "f"(hi), "f"(lo)); return r; }
__device__ __forceinline__ float bf_lo(uint32_t v) { return __uint_as_float(v << 16); }
__device__ __forceinline__ float bf_hi(uint32_t v) { return __uint_as_float(v & 0xFFFF0000u); }
__device__ __forceinline__ float bf_round(float x) { return __bfloat162float(__float2bfloat16_rn(x)); }
__device__ __forceinline__ float siluf(float g) { return g * rcpf(1.0f + ex2f(g * -1.4426950408889634f)); }

__device__ __forceinline__ void wgmma_ss_n256(float* d, uint64_t da, uint64_t db, int acc) {
    asm volatile("{\n.reg .pred p;\nsetp.ne.b32 p, %130, 0;\nwgmma.mma_async.sync.aligned.m64n256k16.f32.bf16.bf16 {"
        "%0,%1,%2,%3,%4,%5,%6,%7,%8,%9,%10,%11,%12,%13,%14,%15,%16,%17,%18,%19,%20,%21,%22,%23,%24,%25,%26,%27,%28,%29,%30,%31,%32,%33,%34,%35,%36,%37,%38,%39,"
        "%40,%41,%42,%43,%44,%45,%46,%47,%48,%49,%50,%51,%52,%53,%54,%55,%56,%57,%58,%59,%60,%61,%62,%63,%64,%65,%66,%67,%68,%69,%70,%71,%72,%73,%74,%75,%76,"
        "%77,%78,%79,%80,%81,%82,%83,%84,%85,%86,%87,%88,%89,%90,%91,%92,%93,%94,%95,%96,%97,%98,%99,%100,%101,%102,%103,%104,%105,%106,%107,%108,%109,%110,"
        "%111,%112,%113,%114,%115,%116,%117,%118,%119,%120,%121,%122,%123,%124,%125,%126,%127"
        "}, %128, %129, p, 1, 1, 0, 1;\n}\n"
        : "+f"(d[0]),"+f"(d[1]),"+f"(d[2]),"+f"(d[3]),"+f"(d[4]),"+f"(d[5]),"+f"(d[6]),"+f"(d[7]),"+f"(d[8]),"+f"(d[9]),"+f"(d[10]),"+f"(d[11]),"+f"(d[12]),
          "+f"(d[13]),"+f"(d[14]),"+f"(d[15]),"+f"(d[16]),"+f"(d[17]),"+f"(d[18]),"+f"(d[19]),"+f"(d[20]),"+f"(d[21]),"+f"(d[22]),"+f"(d[23]),"+f"(d[24]),
          "+f"(d[25]),"+f"(d[26]),"+f"(d[27]),"+f"(d[28]),"+f"(d[29]),"+f"(d[30]),"+f"(d[31]),"+f"(d[32]),"+f"(d[33]),"+f"(d[34]),"+f"(d[35]),"+f"(d[36]),
          "+f"(d[37]),"+f"(d[38]),"+f"(d[39]),"+f"(d[40]),"+f"(d[41]),"+f"(d[42]),"+f"(d[43]),"+f"(d[44]),"+f"(d[45]),"+f"(d[46]),"+f"(d[47]),"+f"(d[48]),
          "+f"(d[49]),"+f"(d[50]),"+f"(d[51]),"+f"(d[52]),"+f"(d[53]),"+f"(d[54]),"+f"(d[55]),"+f"(d[56]),"+f"(d[57]),"+f"(d[58]),"+f"(d[59]),"+f"(d[60]),
          "+f"(d[61]),"+f"(d[62]),"+f"(d[63]),"+f"(d[64]),"+f"(d[65]),"+f"(d[66]),"+f"(d[67]),"+f"(d[68]),"+f"(d[69]),"+f"(d[70]),"+f"(d[71]),"+f"(d[72]),
          "+f"(d[73]),"+f"(d[74]),"+f"(d[75]),"+f"(d[76]),"+f"(d[77]),"+f"(d[78]),"+f"(d[79]),"+f"(d[80]),"+f"(d[81]),"+f"(d[82]),"+f"(d[83]),"+f"(d[84]),
          "+f"(d[85]),"+f"(d[86]),"+f"(d[87]),"+f"(d[88]),"+f"(d[89]),"+f"(d[90]),"+f"(d[91]),"+f"(d[92]),"+f"(d[93]),"+f"(d[94]),"+f"(d[95]),"+f"(d[96]),
          "+f"(d[97]),"+f"(d[98]),"+f"(d[99]),"+f"(d[100]),"+f"(d[101]),"+f"(d[102]),"+f"(d[103]),"+f"(d[104]),"+f"(d[105]),"+f"(d[106]),"+f"(d[107]),
          "+f"(d[108]),"+f"(d[109]),"+f"(d[110]),"+f"(d[111]),"+f"(d[112]),"+f"(d[113]),"+f"(d[114]),"+f"(d[115]),"+f"(d[116]),"+f"(d[117]),"+f"(d[118]),
          "+f"(d[119]),"+f"(d[120]),"+f"(d[121]),"+f"(d[122]),"+f"(d[123]),"+f"(d[124]),"+f"(d[125]),"+f"(d[126]),"+f"(d[127])
        : "l"(da), "l"(db), "r"(acc));
}
__device__ __forceinline__ void wgmma_ss_n128(float* d, uint64_t da, uint64_t db, int acc) {
    asm volatile("{\n.reg .pred p;\nsetp.ne.b32 p, %66, 0;\nwgmma.mma_async.sync.aligned.m64n128k16.f32.bf16.bf16 {"
        "%0,%1,%2,%3,%4,%5,%6,%7,%8,%9,%10,%11,%12,%13,%14,%15,%16,%17,%18,%19,%20,%21,%22,%23,%24,%25,%26,%27,%28,%29,%30,%31,%32,%33,%34,%35,%36,%37,%38,%39,"
        "%40,%41,%42,%43,%44,%45,%46,%47,%48,%49,%50,%51,%52,%53,%54,%55,%56,%57,%58,%59,%60,%61,%62,%63"
        "}, %64, %65, p, 1, 1, 0, 1;\n}\n"
        : "+f"(d[0]),"+f"(d[1]),"+f"(d[2]),"+f"(d[3]),"+f"(d[4]),"+f"(d[5]),"+f"(d[6]),"+f"(d[7]),"+f"(d[8]),"+f"(d[9]),"+f"(d[10]),"+f"(d[11]),"+f"(d[12]),
          "+f"(d[13]),"+f"(d[14]),"+f"(d[15]),"+f"(d[16]),"+f"(d[17]),"+f"(d[18]),"+f"(d[19]),"+f"(d[20]),"+f"(d[21]),"+f"(d[22]),"+f"(d[23]),"+f"(d[24]),
          "+f"(d[25]),"+f"(d[26]),"+f"(d[27]),"+f"(d[28]),"+f"(d[29]),"+f"(d[30]),"+f"(d[31]),"+f"(d[32]),"+f"(d[33]),"+f"(d[34]),"+f"(d[35]),"+f"(d[36]),
          "+f"(d[37]),"+f"(d[38]),"+f"(d[39]),"+f"(d[40]),"+f"(d[41]),"+f"(d[42]),"+f"(d[43]),"+f"(d[44]),"+f"(d[45]),"+f"(d[46]),"+f"(d[47]),"+f"(d[48]),
          "+f"(d[49]),"+f"(d[50]),"+f"(d[51]),"+f"(d[52]),"+f"(d[53]),"+f"(d[54]),"+f"(d[55]),"+f"(d[56]),"+f"(d[57]),"+f"(d[58]),"+f"(d[59]),"+f"(d[60]),
          "+f"(d[61]),"+f"(d[62]),"+f"(d[63])
        : "l"(da), "l"(db), "r"(acc));
}
__device__ __forceinline__ void wgmma_ss_n64(float* d, uint64_t da, uint64_t db, int acc) {
    asm volatile("{\n.reg .pred p;\nsetp.ne.b32 p, %34, 0;\nwgmma.mma_async.sync.aligned.m64n64k16.f32.bf16.bf16 {"
        "%0,%1,%2,%3,%4,%5,%6,%7,%8,%9,%10,%11,%12,%13,%14,%15,%16,%17,%18,%19,%20,%21,%22,%23,%24,%25,%26,%27,%28,%29,%30,%31"
        "}, %32, %33, p, 1, 1, 0, 1;\n}\n"
        : "+f"(d[0]),"+f"(d[1]),"+f"(d[2]),"+f"(d[3]),"+f"(d[4]),"+f"(d[5]),"+f"(d[6]),"+f"(d[7]),"+f"(d[8]),"+f"(d[9]),"+f"(d[10]),"+f"(d[11]),"+f"(d[12]),
          "+f"(d[13]),"+f"(d[14]),"+f"(d[15]),"+f"(d[16]),"+f"(d[17]),"+f"(d[18]),"+f"(d[19]),"+f"(d[20]),"+f"(d[21]),"+f"(d[22]),"+f"(d[23]),"+f"(d[24]),
          "+f"(d[25]),"+f"(d[26]),"+f"(d[27]),"+f"(d[28]),"+f"(d[29]),"+f"(d[30]),"+f"(d[31])
        : "l"(da), "l"(db), "r"(acc));
}
__device__ __forceinline__ void wgmma_rs_n64_zero(float* d, const uint32_t* a, uint64_t db) {
    asm volatile("wgmma.mma_async.sync.aligned.m64n64k16.f32.bf16.bf16 {"
        "%0,%1,%2,%3,%4,%5,%6,%7,%8,%9,%10,%11,%12,%13,%14,%15,%16,%17,%18,%19,%20,%21,%22,%23,%24,%25,%26,%27,%28,%29,%30,%31"
        "}, {%32,%33,%34,%35}, %36, 0, 1, 1, 0;\n"
        : "=f"(d[0]),"=f"(d[1]),"=f"(d[2]),"=f"(d[3]),"=f"(d[4]),"=f"(d[5]),"=f"(d[6]),"=f"(d[7]),"=f"(d[8]),"=f"(d[9]),"=f"(d[10]),"=f"(d[11]),"=f"(d[12]),
          "=f"(d[13]),"=f"(d[14]),"=f"(d[15]),"=f"(d[16]),"=f"(d[17]),"=f"(d[18]),"=f"(d[19]),"=f"(d[20]),"=f"(d[21]),"=f"(d[22]),"=f"(d[23]),"=f"(d[24]),
          "=f"(d[25]),"=f"(d[26]),"=f"(d[27]),"=f"(d[28]),"=f"(d[29]),"=f"(d[30]),"=f"(d[31])
        : "r"(a[0]), "r"(a[1]), "r"(a[2]), "r"(a[3]), "l"(db));
}
__device__ __forceinline__ void wgmma_rs_n64_acc(float* d, const uint32_t* a, uint64_t db) {
    asm volatile("wgmma.mma_async.sync.aligned.m64n64k16.f32.bf16.bf16 {"
        "%0,%1,%2,%3,%4,%5,%6,%7,%8,%9,%10,%11,%12,%13,%14,%15,%16,%17,%18,%19,%20,%21,%22,%23,%24,%25,%26,%27,%28,%29,%30,%31"
        "}, {%32,%33,%34,%35}, %36, 1, 1, 1, 0;\n"
        : "+f"(d[0]),"+f"(d[1]),"+f"(d[2]),"+f"(d[3]),"+f"(d[4]),"+f"(d[5]),"+f"(d[6]),"+f"(d[7]),"+f"(d[8]),"+f"(d[9]),"+f"(d[10]),"+f"(d[11]),"+f"(d[12]),
          "+f"(d[13]),"+f"(d[14]),"+f"(d[15]),"+f"(d[16]),"+f"(d[17]),"+f"(d[18]),"+f"(d[19]),"+f"(d[20]),"+f"(d[21]),"+f"(d[22]),"+f"(d[23]),"+f"(d[24]),
          "+f"(d[25]),"+f"(d[26]),"+f"(d[27]),"+f"(d[28]),"+f"(d[29]),"+f"(d[30]),"+f"(d[31])
        : "r"(a[0]), "r"(a[1]), "r"(a[2]), "r"(a[3]), "l"(db));
}
__device__ __forceinline__ void wgmma_rs_n24_acc(float* d, const uint32_t* a, uint64_t db) {
    asm volatile("wgmma.mma_async.sync.aligned.m64n24k16.f32.bf16.bf16 {"
        "%0,%1,%2,%3,%4,%5,%6,%7,%8,%9,%10,%11"
        "}, {%12,%13,%14,%15}, %16, 1, 1, 1, 1;\n"
        : "+f"(d[0]),"+f"(d[1]),"+f"(d[2]),"+f"(d[3]),"+f"(d[4]),"+f"(d[5]),"+f"(d[6]),"+f"(d[7]),"+f"(d[8]),"+f"(d[9]),"+f"(d[10]),"+f"(d[11])
        : "r"(a[0]), "r"(a[1]), "r"(a[2]), "r"(a[3]), "l"(db));
}
__device__ __forceinline__ void wgmma_rs_n24_zero(float* d, const uint32_t* a, uint64_t db) {
    asm volatile("wgmma.mma_async.sync.aligned.m64n24k16.f32.bf16.bf16 {"
        "%0,%1,%2,%3,%4,%5,%6,%7,%8,%9,%10,%11"
        "}, {%12,%13,%14,%15}, %16, 0, 1, 1, 1;\n"
        : "=f"(d[0]),"=f"(d[1]),"=f"(d[2]),"=f"(d[3]),"=f"(d[4]),"=f"(d[5]),"=f"(d[6]),"=f"(d[7]),"=f"(d[8]),"=f"(d[9]),"=f"(d[10]),"=f"(d[11])
        : "r"(a[0]), "r"(a[1]), "r"(a[2]), "r"(a[3]), "l"(db));
}

constexpr int OFF_ONES = 131072;
constexpr int OFF_RING = OFF_ONES + 4096;
constexpr int NRING = 5;
constexpr int OFF_B2 = OFF_RING + NRING * 16384;
constexpr int OFF_CS = OFF_B2 + 2048;
constexpr int OFF_RS = OFF_CS + 2560;
constexpr int OFF_BAR = OFF_RS + 1024;
enum { B_FULL = 0, B_A = 40, B_STATS = 48, B_SUM = 53, B_QKV = 58, B_KV = 59, B_RING = 67, B_WO = 70, B_O = 71, B_CNT2 = 80,
       B_AFREE = 80, B_CNT4 = 85, B_EMPTY = 85, B_AFREE0 = 90, B_DONE = 91, B_CNT8 = 92, B_TILE = 92, B_PART = 97, B_NUM = 100 };
constexpr int SMEM_BYTES = OFF_BAR + B_NUM * 8 + 1024;
constexpr unsigned FIXED_MASK = 0xB5;
constexpr float P71 = 2361183241434822606848.0f, M71 = 4.235164736271502e-22f;

__device__ __forceinline__ uint32_t exp2_fixed(float lo, float hi, uint32_t half2) {
    uint32_t y, g, d;
    asm("cvt.pack.sat.s16.s32 %0, %1, %2;" : "=r"(y) : "r"(__float_as_uint(hi)), "r"(__float_as_uint(lo)));
    asm("lop3.b32 %0, %1, 0x007F007F, %2, 0xEA;" : "=r"(g) : "r"(y), "r"(half2));
    asm("fma.rn.bf16x2 %0, %1, %2, %3;" : "=r"(d) : "r"(y), "r"(g), "r"(y & 0xFF80FF80u));
    return d;
}
__device__ __forceinline__ uint32_t k_tile_addr(uint32_t base, int tile) {
    const int c = tile >> 2;
    return base + ((tile & 2) ? 98304 + c * 4096 : (2 * c + 1) * 4096) + (tile & 1) * 2048;
}
__device__ __forceinline__ int stage_of(int t, int j) { return t == 0 ? j + (j >> 1) : (t == 1 && j < 4) ? 3 * j + 2 : 8 * t + j; }
__device__ __forceinline__ int pos_of(int t, int j) { return t == 4 ? (0x37521640u >> (4 * j)) & 7 : j; }

__global__ void __cluster_dims__(2, 1, 1) __launch_bounds__(640, 1)
mega_kernel(const __nv_bfloat16* __restrict__ x, __nv_bfloat16* __restrict__ out,
            const __grid_constant__ CUtensorMap mx, const __grid_constant__ CUtensorMap mqkv, const __grid_constant__ CUtensorMap mw1,
            const __grid_constant__ CUtensorMap mw3, const __grid_constant__ CUtensorMap mw2, const __grid_constant__ CUtensorMap mwo,
            uint32_t half2) {
    extern __shared__ uint8_t smem_raw[];
    const uint32_t sb = (smem_u32(smem_raw) + 1023) & ~1023u;
    const uint32_t bars = sb + OFF_BAR, ring = sb + OFF_RING;
    const int tid = threadIdx.x, lane = tid & 31, g = lane >> 2, t4 = lane & 3;
    const int warp = __shfl_sync(0xffffffffu, tid >> 5, 0), wg = warp >> 2, wq = warp & 3;
    const int rank = blockIdx.x & 1, grp = (blockIdx.x >> 1) & 7, rot = blockIdx.x >> 4, mblk = rot * 2 + rank;
    const int nq = grp < 4 ? 2 : 1;
    const int qt0 = grp < 4 ? 2 * grp : 4 + grp;
    const int gu0 = (grp < 4 ? 3 * grp : 4 * grp - 4) - nq;
    const int head = blockIdx.x >> 2, qb = blockIdx.x & 3;

    if (tid == 512) TSTAMP(0);
    if (elect_one()) {
#pragma unroll
        for (int i = 0; i < 5; i++) { const int b = warp * 5 + i; mbar_init(bars + 8 * b, b < B_CNT2 ? 1 : b < B_CNT4 ? 2 : b < B_CNT8 ? 4 : 8); }
        asm volatile("fence.mbarrier_init.release.cluster;" ::: "memory");
        if (warp == 8) {
            fence_async_smem();
#pragma unroll
            for (int j = 0; j < 2; j++) { mbar_expect(bars + 8 * (B_A + j), 16384); tma2d(sb + j * 16384, &mx, ((rot + j) & 7) * 64, mblk * 128, bars + 8 * (B_A + j)); }
        }
    }
    if (tid == 512) TSTAMP(26);
    if (tid < 256) {
        asm volatile("st.shared.v4.b32 [%0], {%1,%1,%1,%1};" :: "r"(sb + OFF_ONES + tid * 16), "r"(0x3F803F80u) : "memory");
        if (tid < 128) {
            const bool fx = (FIXED_MASK >> (tid >> 4)) & 1;
            uint32_t a = fx ? pack_bf16(M71, M71) : pack_bf16(P71, P71);
            uint32_t b = fx ? pack_bf16(M71, 47.0f * M71) : pack_bf16(P71, -79.5f * P71);
            uint32_t c = fx ? 0u : pack_bf16(0.08214f * P71, 0.f);
            if (tid & 8) a = b = c = 0;
            asm volatile("st.shared.v4.b32 [%0], {%1,%2,%3,%4};" :: "r"(sb + OFF_B2 + tid * 16), "r"(a), "r"(b), "r"(c), "r"(0) : "memory");
        }
        fence_async_smem();
    }
    __syncthreads();
    asm volatile("barrier.cluster.arrive.relaxed.aligned;" ::: "memory");

    if (wg < 4) {
        const int pair = wg >> 1, half = wg & 1;
        if (pair == 1) {
            const int row = mblk * 128 + grp * 16 + (warp - 8) * 2 + (lane >> 4);
            uint4 v[4];
            const uint32_t* w = reinterpret_cast<const uint32_t*>(v);
#pragma unroll
            for (int j = 0; j < 4; j++) v[j] = __ldg(reinterpret_cast<const uint4*>(x + (size_t)row * DM) + j * 16 + (lane & 15));
            float s0 = 0.f, v0 = 0.f;
#pragma unroll
            for (int j = 0; j < 16; j++) s0 += bf_lo(w[j]) + bf_hi(w[j]);
#pragma unroll
            for (int d = 1; d < 16; d <<= 1) s0 += __shfl_xor_sync(0xffffffffu, s0, d);
            const float mean = s0 * (1.0f / DM);
#pragma unroll
            for (int j = 0; j < 16; j++) { const float a = bf_lo(w[j]) - mean, b = bf_hi(w[j]) - mean; v0 += fmaf(a, a, b * b); }
#pragma unroll
            for (int d = 1; d < 16; d <<= 1) v0 += __shfl_xor_sync(0xffffffffu, v0, d);
            if ((lane & 15) == 0) g_rs[row] = make_float2(bf_round(mean), bf_round(sqrtf(bf_round(bf_round(v0 * (1.0f / DM)) + 1e-5f))));
            __syncwarp();
            if (elect_one()) mbar_arrive(bars + 8 * B_PART);
        }
        asm volatile("barrier.cluster.wait.aligned;" ::: "memory");

        uint32_t q[4];
        {
            float acc[64];
            const int rowblk = mblk * 2 + half, tile16 = rowblk * 4 + wq;
#pragma unroll 1
            for (int t = pair; t < 5; t += 2) {
                int prev = 0;
#pragma unroll 1
                for (int j = 0; j < 8; j++) {
                    const int n = stage_of(t, j), kb = pos_of(t, j), slot = n % NRING;
                    if (t < 2) mbar_wait(bars + 8 * (B_A + kb), 0);
                    if (tid == 0 && n == 0) TSTAMP(30);
                    mbar_wait(bars + 8 * (B_FULL + n), 0);
                    if (tid == 0 && n == 0) TSTAMP(1);
                    const uint64_t da = mkdesc(sb + kb * 16384 + half * 8192, 16, 1024, 1), db = mkdesc(ring + slot * 16384, 8192, 1024, 1);
                    wg_fence();
#pragma unroll
                    for (int k = 0; k < 4; k++) wgmma_ss_n128(acc, da + k * 2, db + k * 128, (j | k) != 0);
                    wg_commit();
                    if (j > 0) {
                        wg_wait<1>();
                        if (wq < 2 && elect_one()) mbar_arrive_cluster(bars + 8 * (B_EMPTY + prev), wq);
                        if (t == 4 && wq == 2 && (j == 3 || j == 4 || j == 7) && elect_one()) mbar_arrive(bars + 8 * (j == 3 ? B_AFREE0 : j == 4 ? B_AFREE + 1 : B_AFREE + 2));
                    }
                    prev = slot;
                }
                if (t >= 3) {
                    mbar_wait(bars + 8 * B_QKV, 0);
                    const uint4 v = __ldcg(g_q + (head * 128 + (qb * 8 + wg) * 4 + wq) * 32 + lane); q[0] = v.x; q[1] = v.y; q[2] = v.z; q[3] = v.w;
                }
                wg_wait<0>();
                if (wq < 2 && elect_one()) mbar_arrive_cluster(bars + 8 * (B_EMPTY + prev), wq);
                if (t >= 3 && wq == 2 && elect_one()) mbar_arrive(bars + 8 * (t == 4 ? B_AFREE + 3 : B_AFREE0));
                pin<64>(acc);
                if (wq == 0 && half == 0 && lane == 0) TSTAMP(2 + 2 * t);
                mbar_wait(bars + 8 * (B_STATS + t), 0);
                float m0, d0, m1, d1;
                asm volatile("ld.shared.v2.f32 {%0,%1}, [%2];" : "=f"(m0), "=f"(d0) : "r"(sb + OFF_RS + (half * 64 + wq * 16 + g) * 8));
                asm volatile("ld.shared.v2.f32 {%0,%1}, [%2];" : "=f"(m1), "=f"(d1) : "r"(sb + OFF_RS + (half * 64 + wq * 16 + g + 8) * 8));
#pragma unroll
                for (int j = 0; j < 16; j++) {
                    float c0, c1;
                    asm volatile("ld.shared.v2.f32 {%0,%1}, [%2];" : "=f"(c0), "=f"(c1) : "r"(sb + OFF_CS + (t * 128 + j * 8 + t4 * 2) * 4));
                    acc[4 * j] = fmaf(-m0, c0, acc[4 * j]); acc[4 * j + 1] = fmaf(-m0, c1, acc[4 * j + 1]);
                    acc[4 * j + 2] = fmaf(-m1, c0, acc[4 * j + 2]); acc[4 * j + 3] = fmaf(-m1, c1, acc[4 * j + 3]);
                }
                float r0 = 1.0f / d0, r1 = 1.0f / d1;
                if (t < nq) {
                    const int qt = qt0 + t, h0 = (qt & 3) * 8;
                    if (qt < 4) {
                        r0 *= 0.25f * 1.4426950408889634f * M71; r1 *= 0.25f * 1.4426950408889634f * M71;
                    } else if (qt < 8) {
                        r0 *= ((FIXED_MASK >> (2 * wq)) & 1) ? M71 : P71; r1 *= ((FIXED_MASK >> (2 * wq + 1)) & 1) ? M71 : P71;
                    }
                    uint32_t* p; int s8, sh;
                    if (qt < 8) { p = reinterpret_cast<uint32_t*>(g_k + h0 * 4096) + tile16 * 128 + lane; s8 = 64; sh = 32; }
                    else        { p = reinterpret_cast<uint32_t*>(g_v + h0 * 4096) + tile16 * 64 + lane;  s8 = 32; sh = 8192; }
#pragma unroll
                    for (int hh = 0; hh < 8; hh++) {
                        const float* a = acc + hh * 8;
                        const uint32_t e0 = pack_bf16(a[0] * r0, a[1] * r0), e1 = pack_bf16(a[2] * r1, a[3] * r1);
                        const uint32_t e2 = pack_bf16(a[4] * r0, a[5] * r0), e3 = pack_bf16(a[6] * r1, a[7] * r1);
                        if (qt < 4) g_q[((h0 + hh) * 128 + tile16) * 32 + lane] = make_uint4(e0, e1, e2, e3);
                        else { uint32_t* pp = p + hh * 16384; pp[0] = e0; pp[s8] = e1; pp[sh] = e2; pp[sh + s8] = e3; }
                    }
                } else {
                    uint32_t* p = reinterpret_cast<uint32_t*>(g_h + (rowblk * 28 + gu0 + t) * 512) + wq * 512 + lane;
                    r0 *= -1.4426950408889634f; r1 *= -1.4426950408889634f; d0 *= d0; d1 *= d1;
#pragma unroll
                    for (int j = 0; j < 8; j++) {
                        const float* a = acc + j * 4; const float* b = a + 32;
                        p[j * 32] = pack_bf16(a[0] * b[0] * rcpf(fmaf(ex2f(a[0] * r0), d0, d0)), a[1] * b[1] * rcpf(fmaf(ex2f(a[1] * r0), d0, d0)));
                        p[256 + j * 32] = pack_bf16(a[2] * b[2] * rcpf(fmaf(ex2f(a[2] * r1), d1, d1)), a[3] * b[3] * rcpf(fmaf(ex2f(a[3] * r1), d1, d1)));
                    }
                }
                __syncwarp();
                if (elect_one()) mbar_arrive(bars + 8 * (B_TILE + t));
                if (wq == 0 && half == 0 && lane == 0) TSTAMP(3 + 2 * t);
            }
        }
        const uint64_t db2 = mkdesc(sb + OFF_B2, 128, 256, 0);
#pragma unroll 1
        for (int round = 0; round < 2; round++) {
            const int rowblk = qb * 8 + round * 4 + wg;
            const uint4 qn = __ldcg(g_q + (head * 128 + (qb * 8 + 4 + wg) * 4 + wq) * 32 + lane);
            float o[12];
            int nmax = 1;
#pragma unroll 1
            for (;;) {
                float s[32]; uint32_t p[16], q2[4];
                float m0 = -INFINITY, m1 = -INFINITY, f0 = -INFINITY, f1 = -INFINITY;
                mbar_wait(bars + 8 * B_KV, 0);
#pragma unroll 1
                for (int t = 0; t < nmax; t++) {
                    wg_fence();
                    wgmma_rs_n64_zero(s, q, mkdesc(k_tile_addr(sb, t), 128, 256, 0));
                    wg_commit();
                    wg_wait<0>();
                    pin<32>(s);
#pragma unroll
                    for (int i = 0; i < 8; i++) {
                        if ((FIXED_MASK >> i) & 1) { f0 = fmaxf(f0, fmaxf(s[4 * i], s[4 * i + 1])); f1 = fmaxf(f1, fmaxf(s[4 * i + 2], s[4 * i + 3])); }
                        else                       { m0 = fmaxf(m0, fmaxf(s[4 * i], s[4 * i + 1])); m1 = fmaxf(m1, fmaxf(s[4 * i + 2], s[4 * i + 3])); }
                    }
                }
                m0 = fmaxf(m0, f0 * P71 * P71); m1 = fmaxf(m1, f1 * P71 * P71);
                m0 = fmaxf(m0, __shfl_xor_sync(0xffffffffu, m0, 1)); m0 = fmaxf(m0, __shfl_xor_sync(0xffffffffu, m0, 2));
                m1 = fmaxf(m1, __shfl_xor_sync(0xffffffffu, m1, 1)); m1 = fmaxf(m1, __shfl_xor_sync(0xffffffffu, m1, 2));
#pragma unroll
                for (int r = 0; r < 2; r++) {
                    const float m = -rintf(r ? m1 : m0), mh = bf_round(m), mm = bf_round(m - mh), ml = m - mh - mm;
                    q2[r] = t4 == 0 ? pack_bf16(mh * M71, mm * M71) : t4 == 1 ? pack_bf16(ml * M71, M71) : t4 == 2 ? pack_bf16(M71, 0.f) : 0u;
                    q2[2 + r] = __shfl_sync(0xffffffffu, q2[r], 3);
                }
#pragma unroll
                for (int i = 0; i < 12; i++) o[i] = 0.f;
                pin<12>(o); pin<4>(q2);
                if (wq == 0 && half == 0 && lane == 0) TSTAMP(12 + 4 * round + pair);
                uint64_t dk0 = mkdesc(sb + 4096, 128, 256, 0), dk1 = mkdesc(sb + 98304, 128, 256, 0), dv = mkdesc(sb, 128, 65536, 0);
#pragma unroll 1
                for (int c = 0; c < 8; c++, dk0 += 512, dk1 += 256, dv += 512 - (256ull << 32)) {
                    if (round == 0) mbar_wait(bars + 8 * (B_KV + c), 0);
#pragma unroll
                    for (int t = 0; t < 4; t++) {
                        wg_fence();
                        wgmma_rs_n64_zero(s, q, (t & 2 ? dk1 : dk0) + (t & 1) * 128);
                        wgmma_rs_n64_acc(s, q2, db2);
                        wg_commit();
                        wg_wait<0>();
                        pin<32>(s); pin<16>(p);
#pragma unroll
                        for (int i = 0; i < 16; i++) {
                            if ((FIXED_MASK >> (i >> 1)) & 1) p[i] = exp2_fixed(s[2 * i], s[2 * i + 1], half2);
                            else                              p[i] = pack_bf16(ex2f(s[2 * i]), ex2f(s[2 * i + 1]));
                        }
                        wg_fence();
#pragma unroll
                        for (int k = 0; k < 4; k++) wgmma_rs_n24_acc(o, p + 4 * k, dv + (t * 4 + k) * 16);
                        wg_commit();
                    }
                }
                wg_wait<0>();
                pin<12>(o);
                float chk = 0.f;
#pragma unroll
                for (int i = 0; i < 12; i++) chk = fmaf(o[i], 0.f, chk);
                uint32_t bad;
                asm volatile("{\n.reg .pred p, q;\nsetp.neu.f32 q, %1, 0f00000000;\nbar.red.or.pred p, %2, 128, q;\nselp.u32 %0, 1, 0, p;\n}" : "=r"(bad) : "f"(chk), "r"(1 + wg) : "memory");
                if (!__any_sync(0xffffffffu, bad) || nmax != 1) break;
                nmax = 32;
            }
            const float r0 = 1.0f / o[8], r1 = 1.0f / o[10];
            uint32_t* po = reinterpret_cast<uint32_t*>(g_o + (rowblk * 8 + (head >> 2)) * 512) + wq * 512 + (head & 3) * 64 + lane;
            po[0] = pack_bf16(o[0] * r0, o[1] * r0); po[256] = pack_bf16(o[2] * r1, o[3] * r1);
            po[32] = pack_bf16(o[4] * r0, o[5] * r0); po[288] = pack_bf16(o[6] * r1, o[7] * r1);
            bar_sync(1 + wg, 128);
            if (wq == 0 && elect_one()) {
                if (round == 1) mbar_arrive(bars + 8 * B_DONE);
                signal_cnt(C_O + rowblk);
            }
            q[0] = qn.x; q[1] = qn.y; q[2] = qn.z; q[3] = qn.w;
            if (wq == 0 && half == 0 && lane == 0) TSTAMP(14 + 4 * round + pair);
        }
    } else {
        asm volatile("barrier.cluster.wait.aligned;" ::: "memory");
        if (tid == 512) TSTAMP(27);
        if (wq == 0) {
#pragma unroll 1
            for (int n = 0; n < 40; n++) {
                int t, j;
                if (n < 12) { const int a = n / 3, b = n - 3 * a; t = b == 2; j = t ? a : 2 * a + b; } else { t = n >> 3; j = n & 7; }
                const int slot = n % NRING;
                if (n >= NRING) mbar_wait(bars + 8 * (B_EMPTY + slot), (n / NRING - 1) & 1);
                if (n == 5 || n == 7 || (n > 16 && j == 5)) mbar_wait(bars + 8 * (B_SUM + (n == 5 ? 0 : n == 7 ? 1 : t)), 0);
                if (elect_one()) {
                    mbar_expect(bars + 8 * (B_FULL + n), 16384);
                    const CUtensorMap* m = t < nq ? &mqkv : rank ? &mw3 : &mw1;
                    const int col = t < nq ? (qt0 + t) * 128 + rank * 64 : (gu0 + t) * 64;
                    tma2d_mc(ring + slot * 16384 + rank * 8192, m, col, ((pos_of(t, j) + rot) & 7) * 64, bars + 8 * (B_FULL + n));
                    if (n < 3) {
#pragma unroll 1
                        for (int kb = 2 + 2 * n; kb < 4 + 2 * n; kb++) { mbar_expect(bars + 8 * (B_A + kb), 16384); tma2d(sb + kb * 16384, &mx, ((rot + kb) & 7) * 64, mblk * 128, bars + 8 * (B_A + kb)); }
                    }
                }
            }
        } else if (wq == 1) {
            wait_cnt(C_ROW + mblk, 8, 100);
#pragma unroll
            for (int i = 0; i < 2; i++) {
                const float4 a = __ldcg(reinterpret_cast<const float4*>(g_rs + mblk * 128) + i * 32 + lane);
                asm volatile("st.shared.v4.f32 [%0], {%1,%2,%3,%4};" :: "r"(sb + OFF_RS + (i * 32 + lane) * 16), "f"(a.x), "f"(a.y), "f"(a.z), "f"(a.w) : "memory");
            }
#pragma unroll 1
            for (int t = 0; t < 5; t++) {
                if (t == 3) {
#pragma unroll 1
                    for (int i = 0; i < 3; i++) wait_cnt(C_QKV + i * 4 + (head >> 3), 16, 100);
                    if (elect_one()) { mbar_arrive(bars + 8 * B_QKV); TSTAMP(29); }
                }
                wait_cnt(C_COL + grp * 5 + t, 16, 100);
                float4 a = make_float4(0.f, 0.f, 0.f, 0.f);
#pragma unroll
                for (int kp = 0; kp < 8; kp++) { const float4 b = __ldcg(g_cs + ((grp * 5 + t) * 8 + kp) * 32 + lane); a.x += b.x; a.y += b.y; a.z += b.z; a.w += b.w; }
                asm volatile("st.shared.v4.f32 [%0], {%1,%2,%3,%4};" :: "r"(sb + OFF_CS + (t * 32 + lane) * 16), "f"(a.x), "f"(a.y), "f"(a.z), "f"(a.w) : "memory");
                __syncwarp();
                if (elect_one()) { mbar_arrive(bars + 8 * (B_STATS + t)); if (t == 0) TSTAMP(28); if (t == 4) TSTAMP(31); }
            }
            fence_async_all();
            const uint8_t* gk = reinterpret_cast<const uint8_t*>(g_k + head * 4096);
            const uint8_t* gv = reinterpret_cast<const uint8_t*>(g_v + head * 4096);
#pragma unroll 1
            for (int c = 0; c < 8; c++) {
                if (!(c & 1)) mbar_wait(bars + 8 * (c ? B_AFREE + (c >> 1) : B_AFREE0), 0);
                if (elect_one()) {
                    const uint32_t b = bars + 8 * (B_KV + c);
                    mbar_expect(b, 16384);
                    bulk_load(sb + (2 * c + 1) * 4096, gk + c * 8192, 4096, b);
                    bulk_load(sb + 2 * c * 4096, gv + c * 4096, 4096, b);
                    bulk_load(sb + 65536 + c * 4096, gv + 32768 + c * 4096, 4096, b);
                    bulk_load(sb + 98304 + c * 4096, gk + c * 8192 + 4096, 4096, b);
                }
            }
        } else if (wq == 2) {
            mbar_wait(bars + 8 * B_PART, 0);
            if (elect_one()) signal_cnt(C_ROW + mblk);
#pragma unroll 1
            for (int t = 0; t < 5; t++) {
                mbar_wait(bars + 8 * (B_TILE + t), 0);
                if (elect_one()) signal_cnt(t < nq ? C_QKV + qt0 + t : C_H + mblk);
            }
        } else {
#pragma unroll 1
            for (int t = 0; t < 5; t++) {
                const int n = stage_of(t, 0);
                mbar_wait(bars + 8 * (B_FULL + n), 0);
                float c[8];
#pragma unroll
                for (int e = 0; e < 8; e++) c[e] = 0.f;
#pragma unroll 4
                for (int j = 0; j < 16; j++) {
                    const int r = j * 4 + (lane >> 3);
                    uint32_t w[4];
                    asm volatile("ld.shared.v4.b32 {%0,%1,%2,%3}, [%4];" : "=r"(w[0]), "=r"(w[1]), "=r"(w[2]), "=r"(w[3])
                                 : "r"(ring + (n % NRING) * 16384 + rank * 8192 + r * 128 + (((lane ^ r) & 7) << 4)));
#pragma unroll
                    for (int e = 0; e < 4; e++) { c[2 * e] += bf_lo(w[e]); c[2 * e + 1] += bf_hi(w[e]); }
                }
#pragma unroll
                for (int e = 0; e < 8; e++) { c[e] += __shfl_xor_sync(0xffffffffu, c[e], 8); c[e] += __shfl_xor_sync(0xffffffffu, c[e], 16); }
                if (lane < 16) g_cs[((grp * 5 + t) * 8 + rot) * 32 + rank * 16 + (lane & 7) * 2 + (lane >> 3)] =
                    lane < 8 ? make_float4(c[0], c[1], c[2], c[3]) : make_float4(c[4], c[5], c[6], c[7]);
                __syncwarp();
                if (elect_one()) { mbar_arrive(bars + 8 * (B_SUM + t)); signal_cnt(C_COL + grp * 5 + t); }
            }
        }
        bar_sync(5, 128);
        const int cb = blockIdx.x & 7, pr = blockIdx.x >> 3;
        const int rb0 = (pr >> 2) * 8 + (pr & 3);
        uint32_t gate[2][16];
        {
            float dn[64];
            auto load_stage = [&](int kb, int st) {
                const uint32_t b = bars + 8 * (B_RING + st), dst = ring + st * 24576;
                mbar_expect(b, 24576);
                bulk_load(dst, g_h + (rb0 * 28 + kb) * 512, 8192, b);
                bulk_load(dst + 8192, g_h + ((rb0 + 4) * 28 + kb) * 512, 8192, b);
                tma2d(dst + 16384, &mw2, cb * 64, kb * 64, b);
            };
            if (wq == 0) {
                wait_cnt(C_H + (rb0 >> 1), 28, 200);
                wait_cnt(C_H + (rb0 >> 1) + 2, 28, 200);
                if (elect_one()) { TSTAMP(20); fence_async_all(); load_stage(0, 0); load_stage(1, 1); }
            }
            int st = 0; uint32_t ph = 0;
#pragma unroll 1
            for (int kb = 0; kb < 28; kb++) {
                mbar_wait(bars + 8 * (B_RING + st), ph);
                const uint64_t da = mkdesc(ring + st * 24576, 128, 1024, 0), db = mkdesc(ring + st * 24576 + 16384, 8192, 1024, 1);
                wg_fence();
#pragma unroll
                for (int k = 0; k < 4; k++) { wgmma_ss_n64(dn, da + k * 16, db + k * 128, (kb | k) != 0); wgmma_ss_n64(dn + 32, da + 512 + k * 16, db + k * 128, (kb | k) != 0); }
                wg_commit();
                wg_wait<1>();
                if (wq == 0 && kb < 26 && elect_one()) load_stage(kb + 2, st == 0 ? 2 : st - 1);
                if (++st == 3) { st = 0; ph ^= 1; }
            }
            wg_wait<0>();
            pin<64>(dn);
#pragma unroll
            for (int i = 0; i < 32; i++) gate[i >> 4][i & 15] = pack_bf16(siluf(dn[2 * i]), siluf(dn[2 * i + 1]));
        }
        float acc[32];
        if (tid == 512) TSTAMP(21);
        const uint32_t bar_wo = bars + 8 * B_WO;
        if (wq == 0 && elect_one()) {
            mbar_expect(bar_wo, 65536);
#pragma unroll 1
            for (int i = 0; i < 8; i++) tma2d(ring + i * 8192, &mwo, cb * 64, i * 64, bar_wo);
        }
#pragma unroll
        for (int tl = 0; tl < 2; tl++) {
            const int rb = rb0 + 4 * tl;
            uint32_t xr[16];
            const uint32_t* px = reinterpret_cast<const uint32_t*>(x + (size_t)(rb * 64 + wq * 16 + g) * DM + cb * 64) + t4;
#pragma unroll
            for (int j = 0; j < 8; j++) { xr[2 * j] = __ldg(px + j * 4); xr[2 * j + 1] = __ldg(px + 8 * DM / 2 + j * 4); }
            if (wq == 0) {
                if (tl == 1) mbar_wait(bars + 8 * B_DONE, 0);
                wait_cnt(C_O + rb, 32, tl ? 20 : 200);
                if (elect_one()) {
                    fence_async_all();
                    TSTAMP(22 + 2 * tl);
#pragma unroll 1
                    for (int i = 0; i < (tl ? 8 : 2); i++) {
                        mbar_expect(bars + 8 * (B_O + i), 8192);
                        bulk_load((tl ? sb : ring + 65536) + i * 8192, g_o + (rb * 8 + i) * 512, 8192, bars + 8 * (B_O + i));
                    }
                }
            }
            if (tl == 0) mbar_wait(bar_wo, 0);
#pragma unroll 1
            for (int kb = 0; kb < 8; kb++) {
                mbar_wait(bars + 8 * (B_O + kb), tl);
                const uint32_t a = tl == 0 ? ring + 65536 + (kb & 1) * 8192 : sb + kb * 8192;
                const uint64_t da = mkdesc(a, 128, 1024, 0), db = mkdesc(ring + kb * 8192, 8192, 1024, 1);
                wg_fence();
#pragma unroll
                for (int k = 0; k < 4; k++) wgmma_ss_n64(acc, da + k * 16, db + k * 128, (kb | k) != 0);
                wg_commit();
                if (tl == 0) {
                    wg_wait<0>();
                    bar_sync(5, 128);
                    if (wq == 0 && kb < 6 && elect_one()) { mbar_expect(bars + 8 * (B_O + kb + 2), 8192); bulk_load(a, g_o + (rb * 8 + kb + 2) * 512, 8192, bars + 8 * (B_O + kb + 2)); }
                }
            }
            unsigned ticket = 0;
            if (tl == 1 && tid == 512 + 96) ticket = atomicInc(&g_ticket, 127);
            wg_wait<0>();
            pin<32>(acc);
            uint32_t* po = reinterpret_cast<uint32_t*>(out + (size_t)(rb * 64 + wq * 16 + g) * DM + cb * 64) + t4;
#pragma unroll
            for (int i = 0; i < 16; i++) {
                const uint32_t r = pack_bf16(fmaf(acc[2 * i], bf_lo(gate[tl][i]), bf_lo(xr[i])), fmaf(acc[2 * i + 1], bf_hi(gate[tl][i]), bf_hi(xr[i])));
                po[(i & 1) * (8 * DM / 2) + (i >> 1) * 4] = r;
            }
            if (tl == 1 && wq == 3 && __any_sync(0xffffffffu, ticket == 127)) {
#pragma unroll 1
                for (int i = lane; i < C_NUM; i += 32) g_cnt[i * 8] = 0;
            }
            if (tid == 512) TSTAMP(23 + 2 * tl);
        }
    }
}

typedef CUresult (*EncodeFn)(CUtensorMap*, CUtensorMapDataType, cuuint32_t, void*, const cuuint64_t*, const cuuint64_t*, const cuuint32_t*,
                             const cuuint32_t*, CUtensorMapInterleave, CUtensorMapSwizzle, CUtensorMapL2promotion, CUtensorMapFloatOOBfill);

void make_map(EncodeFn fn, CUtensorMap* m, const void* p, int rows, int cols, int box_rows) {
    cuuint64_t dims[2] = {(cuuint64_t)cols, (cuuint64_t)rows};
    cuuint64_t strides[1] = {(cuuint64_t)cols * 2};
    cuuint32_t box[2] = {64, (cuuint32_t)box_rows};
    cuuint32_t es[2] = {1, 1};
    fn(m, CU_TENSOR_MAP_DATA_TYPE_BFLOAT16, 2, const_cast<void*>(p), dims, strides, box, es, CU_TENSOR_MAP_INTERLEAVE_NONE,
       CU_TENSOR_MAP_SWIZZLE_128B, CU_TENSOR_MAP_L2_PROMOTION_L2_128B, CU_TENSOR_MAP_FLOAT_OOB_FILL_NONE);
}

}

extern "C" void kernel_launch(void* const* d_in, const int* in_sizes, int n_in, void* d_out, int out_size) {
    const __nv_bfloat16* x = (const __nv_bfloat16*)d_in[0];
    static EncodeFn fn = nullptr;
    if (!fn) {
        cudaDriverEntryPointQueryResult qr;
        cudaGetDriverEntryPoint("cuTensorMapEncodeTiled", (void**)&fn, cudaEnableDefault, &qr);
        cudaFuncSetAttribute(mega_kernel, cudaFuncAttributeMaxDynamicSharedMemorySize, SMEM_BYTES);
    }
    CUtensorMap mx, mqkv, mw1, mw3, mw2, mwo;
    make_map(fn, &mx, d_in[0], SEQ, DM, 128);
    make_map(fn, &mqkv, d_in[1], DM, 3 * DM, 64);
    make_map(fn, &mwo, d_in[2], DM, DM, 64);
    make_map(fn, &mw1, d_in[4], DM, FF, 64);
    make_map(fn, &mw3, d_in[5], DM, FF, 64);
    make_map(fn, &mw2, d_in[6], FF, DM, 64);
    mega_kernel<<<128, 640, SMEM_BYTES, cudaStreamPerThread>>>(x, (__nv_bfloat16*)d_out, mx, mqkv, mw1, mw3, mw2, mwo, 0x3F003F00u);
}
```

```cpp
#include <cuda_runtime.h>
#include <cuda_bf16.h>
#include <cuda.h>
#include <stdint.h>

namespace {

constexpr int SEQ = 2048, DM = 512, FF = 1792;

__device__ uint4 g_q[32 * 128 * 32];
__device__ uint4 g_k[32 * 4096];
__device__ uint4 g_v[32 * 4096];
__device__ uint4 g_h[32 * 28 * 512];
__device__ uint4 g_o[32 * 8 * 512];
__device__ float4 g_cs[40 * 8 * 32];
__device__ float2 g_rs[SEQ];
constexpr int C_COL = 0, C_ROW = 16, C_QKV = 32, C_H = 44, C_O = 60, C_NUM = 92;
__device__ unsigned g_cnt[C_NUM * 8];
__device__ unsigned g_ticket;
#define TSTAMP(i)

__device__ __forceinline__ uint32_t smem_u32(const void* p) { return (uint32_t)__cvta_generic_to_shared(p); }
__device__ __forceinline__ void mbar_init(uint32_t a, int c) { asm volatile("mbarrier.init.shared::cta.b64 [%0], %1;" :: "r"(a), "r"(c)); }
__device__ __forceinline__ void mbar_expect(uint32_t a, int b) { asm volatile("mbarrier.arrive.expect_tx.shared::cta.b64 _, [%0], %1;" :: "r"(a), "r"(b) : "memory"); }
__device__ __forceinline__ void mbar_arrive(uint32_t a) { asm volatile("mbarrier.arrive.shared::cta.b64 _, [%0];" :: "r"(a) : "memory"); }
__device__ __forceinline__ void mbar_arrive_cluster(uint32_t a, uint32_t cta) {
    asm volatile("{\n.reg .b32 r;\nmapa.shared::cluster.u32 r, %0, %1;\nmbarrier.arrive.shared::cluster.b64 _, [r];\n}" :: "r"(a), "r"(cta) : "memory");
}
__device__ __forceinline__ bool mbar_try(uint32_t a, uint32_t ph) {
    uint32_t ok;
    asm volatile("{\n.reg .pred p;\nmbarrier.try_wait.parity.shared::cta.b64 p, [%1], %2;\nselp.u32 %0, 1, 0, p;\n}" : "=r"(ok) : "r"(a), "r"(ph) : "memory");
    return ok;
}
__device__ __forceinline__ void mbar_wait(uint32_t a, uint32_t ph) {
    for (int n = 0; !__all_sync(0xffffffffu, mbar_try(a, ph)); n++) if (n > 4000000) __trap();
}
__device__ __forceinline__ bool elect_one() {
    uint32_t p;
    asm volatile("{\n.reg .pred P;\nelect.sync _|P, 0xffffffff;\nselp.u32 %0, 1, 0, P;\n}" : "=r"(p));
    return p;
}
__device__ __forceinline__ void signal_cnt(int c) {
    asm volatile("fence.acq_rel.gpu;\nred.relaxed.gpu.global.add.u32 [%0], 1;" :: "l"(g_cnt + c * 8) : "memory");
}
__device__ __forceinline__ void wait_cnt(int c, unsigned target, int ns) {
    for (int n = 0;; n++) {
        unsigned v;
        asm volatile("ld.acquire.gpu.global.u32 %0, [%1];" : "=r"(v) : "l"(g_cnt + c * 8) : "memory");
        if (__all_sync(0xffffffffu, v >= target)) break;
        if (n > 2000000) __trap();
        __nanosleep(ns);
    }
}
__device__ __forceinline__ void tma2d(uint32_t dst, const CUtensorMap* m, int c0, int c1, uint32_t bar) {
    asm volatile("cp.async.bulk.tensor.2d.shared::cluster.global.mbarrier::complete_tx::bytes [%0], [%1, {%3, %4}], [%2];"
                 :: "r"(dst), "l"(m), "r"(bar), "r"(c0), "r"(c1) : "memory");
}
__device__ __forceinline__ void tma2d_mc(uint32_t dst, const CUtensorMap* m, int c0, int c1, uint32_t bar) {
    asm volatile("cp.async.bulk.tensor.2d.shared::cluster.global.mbarrier::complete_tx::bytes.multicast::cluster [%0], [%1, {%3, %4}], [%2], %5;"
                 :: "r"(dst), "l"(m), "r"(bar), "r"(c0), "r"(c1), "h"((uint16_t)3) : "memory");
}
__device__ __forceinline__ void bulk_load(uint32_t dst, const void* src, int bytes, uint32_t bar) {
    asm volatile("cp.async.bulk.shared::cluster.global.mbarrier::complete_tx::bytes [%0], [%1], %2, [%3];"
                 :: "r"(dst), "l"(src), "r"(bytes), "r"(bar) : "memory");
}
__device__ __forceinline__ void bar_sync(int id, int n) { asm volatile("bar.sync %0, %1;" :: "r"(id), "r"(n) : "memory"); }
__device__ __forceinline__ void fence_async_smem() { asm volatile("fence.proxy.async.shared::cta;" ::: "memory"); }
__device__ __forceinline__ void fence_async_all() { asm volatile("fence.proxy.async;" ::: "memory"); }
__device__ __forceinline__ void wg_fence() { asm volatile("wgmma.fence.sync.aligned;" ::: "memory"); }
__device__ __forceinline__ void wg_commit() { asm volatile("wgmma.commit_group.sync.aligned;" ::: "memory"); }
template <int N> __device__ __forceinline__ void wg_wait() { asm volatile("wgmma.wait_group.sync.aligned %0;" :: "n"(N) : "memory"); }
template <int N> __device__ __forceinline__ void pin(float* d) {
#pragma unroll
    for (int i = 0; i < N; i++) asm volatile("" : "+f"(d[i]) :: "memory");
}
template <int N> __device__ __forceinline__ void pin(uint32_t* d) {
#pragma unroll
    for (int i = 0; i < N; i++) asm volatile("" : "+r"(d[i]) :: "memory");
}
__device__ __forceinline__ uint64_t mkdesc(uint32_t addr, uint32_t lbo, uint32_t sbo, uint32_t swz) {
    return (uint64_t)((addr & 0x3FFFF) >> 4) | ((uint64_t)(lbo >> 4) << 16) | ((uint64_t)(sbo >> 4) << 32) | ((uint64_t)swz << 62);
}
__device__ __forceinline__ float ex2f(float x) { float y; asm("ex2.approx.ftz.f32 %0, %1;" : "=f"(y) : "f"(x)); return y; }
__device__ __forceinline__ float rcpf(float x) { float y; asm("rcp.approx.ftz.f32 %0, %1;" : "=f"(y) : "f"(x)); return y; }
__device__ __forceinline__ uint32_t pack_bf16(float lo, float hi) { uint32_t r; asm("cvt.rn.bf16x2.f32 %0, %1, %2;" : "=r"(r) : "f"(hi), "f"(lo)); return r; }
__device__ __forceinline__ float bf_lo(uint32_t v) { return __uint_as_float(v << 16); }
__device__ __forceinline__ float bf_hi(uint32_t v) { return __uint_as_float(v & 0xFFFF0000u); }
__device__ __forceinline__ float bf_round(float x) { return __bfloat162float(__float2bfloat16_rn(x)); }
__device__ __forceinline__ float siluf(float g) { return g * rcpf(1.0f + ex2f(g * -1.4426950408889634f)); }

__device__ __forceinline__ void wgmma_ss_n256(float* d, uint64_t da, uint64_t db, int acc) {
    asm volatile("{\n.reg .pred p;\nsetp.ne.b32 p, %130, 0;\nwgmma.mma_async.sync.aligned.m64n256k16.f32.bf16.bf16 {"
        "%0,%1,%2,%3,%4,%5,%6,%7,%8,%9,%10,%11,%12,%13,%14,%15,%16,%17,%18,%19,%20,%21,%22,%23,%24,%25,%26,%27,%28,%29,%30,%31,%32,%33,%34,%35,%36,%37,%38,%39,"
        "%40,%41,%42,%43,%44,%45,%46,%47,%48,%49,%50,%51,%52,%53,%54,%55,%56,%57,%58,%59,%60,%61,%62,%63,%64,%65,%66,%67,%68,%69,%70,%71,%72,%73,%74,%75,%76,"
        "%77,%78,%79,%80,%81,%82,%83,%84,%85,%86,%87,%88,%89,%90,%91,%92,%93,%94,%95,%96,%97,%98,%99,%100,%101,%102,%103,%104,%105,%106,%107,%108,%109,%110,"
        "%111,%112,%113,%114,%115,%116,%117,%118,%119,%120,%121,%122,%123,%124,%125,%126,%127"
        "}, %128, %129, p, 1, 1, 0, 1;\n}\n"
        : "+f"(d[0]),"+f"(d[1]),"+f"(d[2]),"+f"(d[3]),"+f"(d[4]),"+f"(d[5]),"+f"(d[6]),"+f"(d[7]),"+f"(d[8]),"+f"(d[9]),"+f"(d[10]),"+f"(d[11]),"+f"(d[12]),
          "+f"(d[13]),"+f"(d[14]),"+f"(d[15]),"+f"(d[16]),"+f"(d[17]),"+f"(d[18]),"+f"(d[19]),"+f"(d[20]),"+f"(d[21]),"+f"(d[22]),"+f"(d[23]),"+f"(d[24]),
          "+f"(d[25]),"+f"(d[26]),"+f"(d[27]),"+f"(d[28]),"+f"(d[29]),"+f"(d[30]),"+f"(d[31]),"+f"(d[32]),"+f"(d[33]),"+f"(d[34]),"+f"(d[35]),"+f"(d[36]),
          "+f"(d[37]),"+f"(d[38]),"+f"(d[39]),"+f"(d[40]),"+f"(d[41]),"+f"(d[42]),"+f"(d[43]),"+f"(d[44]),"+f"(d[45]),"+f"(d[46]),"+f"(d[47]),"+f"(d[48]),
          "+f"(d[49]),"+f"(d[50]),"+f"(d[51]),"+f"(d[52]),"+f"(d[53]),"+f"(d[54]),"+f"(d[55]),"+f"(d[56]),"+f"(d[57]),"+f"(d[58]),"+f"(d[59]),"+f"(d[60]),
          "+f"(d[61]),"+f"(d[62]),"+f"(d[63]),"+f"(d[64]),"+f"(d[65]),"+f"(d[66]),"+f"(d[67]),"+f"(d[68]),"+f"(d[69]),"+f"(d[70]),"+f"(d[71]),"+f"(d[72]),
          "+f"(d[73]),"+f"(d[74]),"+f"(d[75]),"+f"(d[76]),"+f"(d[77]),"+f"(d[78]),"+f"(d[79]),"+f"(d[80]),"+f"(d[81]),"+f"(d[82]),"+f"(d[83]),"+f"(d[84]),
          "+f"(d[85]),"+f"(d[86]),"+f"(d[87]),"+f"(d[88]),"+f"(d[89]),"+f"(d[90]),"+f"(d[91]),"+f"(d[92]),"+f"(d[93]),"+f"(d[94]),"+f"(d[95]),"+f"(d[96]),
          "+f"(d[97]),"+f"(d[98]),"+f"(d[99]),"+f"(d[100]),"+f"(d[101]),"+f"(d[102]),"+f"(d[103]),"+f"(d[104]),"+f"(d[105]),"+f"(d[106]),"+f"(d[107]),
          "+f"(d[108]),"+f"(d[109]),"+f"(d[110]),"+f"(d[111]),"+f"(d[112]),"+f"(d[113]),"+f"(d[114]),"+f"(d[115]),"+f"(d[116]),"+f"(d[117]),"+f"(d[118]),
          "+f"(d[119]),"+f"(d[120]),"+f"(d[121]),"+f"(d[122]),"+f"(d[123]),"+f"(d[124]),"+f"(d[125]),"+f"(d[126]),"+f"(d[127])
        : "l"(da), "l"(db), "r"(acc));
}
__device__ __forceinline__ void wgmma_ss_n128(float* d, uint64_t da, uint64_t db, int acc) {
    asm volatile("{\n.reg .pred p;\nsetp.ne.b32 p, %66, 0;\nwgmma.mma_async.sync.aligned.m64n128k16.f32.bf16.bf16 {"
        "%0,%1,%2,%3,%4,%5,%6,%7,%8,%9,%10,%11,%12,%13,%14,%15,%16,%17,%18,%19,%20,%21,%22,%23,%24,%25,%26,%27,%28,%29,%30,%31,%32,%33,%34,%35,%36,%37,%38,%39,"
        "%40,%41,%42,%43,%44,%45,%46,%47,%48,%49,%50,%51,%52,%53,%54,%55,%56,%57,%58,%59,%60,%61,%62,%63"
        "}, %64, %65, p, 1, 1, 0, 1;\n}\n"
        : "+f"(d[0]),"+f"(d[1]),"+f"(d[2]),"+f"(d[3]),"+f"(d[4]),"+f"(d[5]),"+f"(d[6]),"+f"(d[7]),"+f"(d[8]),"+f"(d[9]),"+f"(d[10]),"+f"(d[11]),"+f"(d[12]),
          "+f"(d[13]),"+f"(d[14]),"+f"(d[15]),"+f"(d[16]),"+f"(d[17]),"+f"(d[18]),"+f"(d[19]),"+f"(d[20]),"+f"(d[21]),"+f"(d[22]),"+f"(d[23]),"+f"(d[24]),
          "+f"(d[25]),"+f"(d[26]),"+f"(d[27]),"+f"(d[28]),"+f"(d[29]),"+f"(d[30]),"+f"(d[31]),"+f"(d[32]),"+f"(d[33]),"+f"(d[34]),"+f"(d[35]),"+f"(d[36]),
          "+f"(d[37]),"+f"(d[38]),"+f"(d[39]),"+f"(d[40]),"+f"(d[41]),"+f"(d[42]),"+f"(d[43]),"+f"(d[44]),"+f"(d[45]),"+f"(d[46]),"+f"(d[47]),"+f"(d[48]),
          "+f"(d[49]),"+f"(d[50]),"+f"(d[51]),"+f"(d[52]),"+f"(d[53]),"+f"(d[54]),"+f"(d[55]),"+f"(d[56]),"+f"(d[57]),"+f"(d[58]),"+f"(d[59]),"+f"(d[60]),
          "+f"(d[61]),"+f"(d[62]),"+f"(d[63])
        : "l"(da), "l"(db), "r"(acc));
}
__device__ __forceinline__ void wgmma_ss_n64(float* d, uint64_t da, uint64_t db, int acc) {
    asm volatile("{\n.reg .pred p;\nsetp.ne.b32 p, %34, 0;\nwgmma.mma_async.sync.aligned.m64n64k16.f32.bf16.bf16 {"
        "%0,%1,%2,%3,%4,%5,%6,%7,%8,%9,%10,%11,%12,%13,%14,%15,%16,%17,%18,%19,%20,%21,%22,%23,%24,%25,%26,%27,%28,%29,%30,%31"
        "}, %32, %33, p, 1, 1, 0, 1;\n}\n"
        : "+f"(d[0]),"+f"(d[1]),"+f"(d[2]),"+f"(d[3]),"+f"(d[4]),"+f"(d[5]),"+f"(d[6]),"+f"(d[7]),"+f"(d[8]),"+f"(d[9]),"+f"(d[10]),"+f"(d[11]),"+f"(d[12]),
          "+f"(d[13]),"+f"(d[14]),"+f"(d[15]),"+f"(d[16]),"+f"(d[17]),"+f"(d[18]),"+f"(d[19]),"+f"(d[20]),"+f"(d[21]),"+f"(d[22]),"+f"(d[23]),"+f"(d[24]),
          "+f"(d[25]),"+f"(d[26]),"+f"(d[27]),"+f"(d[28]),"+f"(d[29]),"+f"(d[30]),"+f"(d[31])
        : "l"(da), "l"(db), "r"(acc));
}
__device__ __forceinline__ void wgmma_rs_n64_zero(float* d, const uint32_t* a, uint64_t db) {
    asm volatile("wgmma.mma_async.sync.aligned.m64n64k16.f32.bf16.bf16 {"
        "%0,%1,%2,%3,%4,%5,%6,%7,%8,%9,%10,%11,%12,%13,%14,%15,%16,%17,%18,%19,%20,%21,%22,%23,%24,%25,%26,%27,%28,%29,%30,%31"
        "}, {%32,%33,%34,%35}, %36, 0, 1, 1, 0;\n"
        : "=f"(d[0]),"=f"(d[1]),"=f"(d[2]),"=f"(d[3]),"=f"(d[4]),"=f"(d[5]),"=f"(d[6]),"=f"(d[7]),"=f"(d[8]),"=f"(d[9]),"=f"(d[10]),"=f"(d[11]),"=f"(d[12]),
          "=f"(d[13]),"=f"(d[14]),"=f"(d[15]),"=f"(d[16]),"=f"(d[17]),"=f"(d[18]),"=f"(d[19]),"=f"(d[20]),"=f"(d[21]),"=f"(d[22]),"=f"(d[23]),"=f"(d[24]),
          "=f"(d[25]),"=f"(d[26]),"=f"(d[27]),"=f"(d[28]),"=f"(d[29]),"=f"(d[30]),"=f"(d[31])
        : "r"(a[0]), "r"(a[1]), "r"(a[2]), "r"(a[3]), "l"(db));
}
__device__ __forceinline__ void wgmma_rs_n64_acc(float* d, const uint32_t* a, uint64_t db) {
    asm volatile("wgmma.mma_async.sync.aligned.m64n64k16.f32.bf16.bf16 {"
        "%0,%1,%2,%3,%4,%5,%6,%7,%8,%9,%10,%11,%12,%13,%14,%15,%16,%17,%18,%19,%20,%21,%22,%23,%24,%25,%26,%27,%28,%29,%30,%31"
        "}, {%32,%33,%34,%35}, %36, 1, 1, 1, 0;\n"
        : "+f"(d[0]),"+f"(d[1]),"+f"(d[2]),"+f"(d[3]),"+f"(d[4]),"+f"(d[5]),"+f"(d[6]),"+f"(d[7]),"+f"(d[8]),"+f"(d[9]),"+f"(d[10]),"+f"(d[11]),"+f"(d[12]),
          "+f"(d[13]),"+f"(d[14]),"+f"(d[15]),"+f"(d[16]),"+f"(d[17]),"+f"(d[18]),"+f"(d[19]),"+f"(d[20]),"+f"(d[21]),"+f"(d[22]),"+f"(d[23]),"+f"(d[24]),
          "+f"(d[25]),"+f"(d[26]),"+f"(d[27]),"+f"(d[28]),"+f"(d[29]),"+f"(d[30]),"+f"(d[31])
        : "r"(a[0]), "r"(a[1]), "r"(a[2]), "r"(a[3]), "l"(db));
}
__device__ __forceinline__ void wgmma_rs_n24_acc(float* d, const uint32_t* a, uint64_t db) {
    asm volatile("wgmma.mma_async.sync.aligned.m64n24k16.f32.bf16.bf16 {"
        "%0,%1,%2,%3,%4,%5,%6,%7,%8,%9,%10,%11"
        "}, {%12,%13,%14,%15}, %16, 1, 1, 1, 1;\n"
        : "+f"(d[0]),"+f"(d[1]),"+f"(d[2]),"+f"(d[3]),"+f"(d[4]),"+f"(d[5]),"+f"(d[6]),"+f"(d[7]),"+f"(d[8]),"+f"(d[9]),"+f"(d[10]),"+f"(d[11])
        : "r"(a[0]), "r"(a[1]), "r"(a[2]), "r"(a[3]), "l"(db));
}
__device__ __forceinline__ void wgmma_rs_n24_zero(float* d, const uint32_t* a, uint64_t db) {
    asm volatile("wgmma.mma_async.sync.aligned.m64n24k16.f32.bf16.bf16 {"
        "%0,%1,%2,%3,%4,%5,%6,%7,%8,%9,%10,%11"
        "}, {%12,%13,%14,%15}, %16, 0, 1, 1, 1;\n"
        : "=f"(d[0]),"=f"(d[1]),"=f"(d[2]),"=f"(d[3]),"=f"(d[4]),"=f"(d[5]),"=f"(d[6]),"=f"(d[7]),"=f"(d[8]),"=f"(d[9]),"=f"(d[10]),"=f"(d[11])
        : "r"(a[0]), "r"(a[1]), "r"(a[2]), "r"(a[3]), "l"(db));
}

constexpr int OFF_ONES = 131072;
constexpr int OFF_RING = OFF_ONES + 4096;
constexpr int NRING = 5;
constexpr int OFF_B2 = OFF_RING + NRING * 16384;
constexpr int OFF_CS = OFF_B2 + 2048;
constexpr int OFF_RS = OFF_CS + 2560;
constexpr int OFF_BAR = OFF_RS + 1024;
enum { B_FULL = 0, B_A = 40, B_STATS = 48, B_QKV = 58, B_KV = 59, B_RING = 67, B_WO = 70, B_O = 71, B_CNT2 = 80,
       B_AFREE = 80, B_CNT4 = 85, B_EMPTY = 85, B_AFREE0 = 90, B_DONE = 91, B_CNT8 = 92, B_TILE = 92, B_PART = 97, B_OW = 98, B_NUM = 100 };
constexpr int SMEM_BYTES = OFF_BAR + B_NUM * 8 + 1024;
constexpr unsigned FIXED_MASK = 0xB5;
constexpr float P71 = 2361183241434822606848.0f, M71 = 4.235164736271502e-22f;

__device__ __forceinline__ uint32_t exp2_fixed(float lo, float hi, uint32_t half2) {
    uint32_t y, g, d;
    asm("cvt.pack.sat.s16.s32 %0, %1, %2;" : "=r"(y) : "r"(__float_as_uint(hi)), "r"(__float_as_uint(lo)));
    asm("lop3.b32 %0, %1, 0x007F007F, %2, 0xEA;" : "=r"(g) : "r"(y), "r"(half2));
    asm("fma.rn.bf16x2 %0, %1, %2, %3;" : "=r"(d) : "r"(y), "r"(g), "r"(y & 0xFF80FF80u));
    return d;
}
__device__ __forceinline__ uint32_t k_tile_addr(uint32_t base, int tile) {
    const int c = tile >> 2;
    return base + ((tile & 2) ? 98304 + c * 4096 : (2 * c + 1) * 4096) + (tile & 1) * 2048;
}
__device__ __forceinline__ int stage_of(int t, int j) { return t == 0 ? j + (j >> 1) : (t == 1 && j < 4) ? 3 * j + 2 : 8 * t + j; }
__device__ __forceinline__ int pos_of(int t, int j) { return t == 4 ? (0x37521640u >> (4 * j)) & 7 : j; }

__global__ void __cluster_dims__(2, 1, 1) __launch_bounds__(640, 1)
mega_kernel(const __nv_bfloat16* __restrict__ x, const __nv_bfloat16* __restrict__ wqkv, const __nv_bfloat16* __restrict__ w1,
            const __nv_bfloat16* __restrict__ w3, __nv_bfloat16* __restrict__ out,
            const __grid_constant__ CUtensorMap mx, const __grid_constant__ CUtensorMap mqkv, const __grid_constant__ CUtensorMap mw1,
            const __grid_constant__ CUtensorMap mw3, const __grid_constant__ CUtensorMap mw2, const __grid_constant__ CUtensorMap mwo,
            uint32_t half2) {
    extern __shared__ uint8_t smem_raw[];
    const uint32_t sb = (smem_u32(smem_raw) + 1023) & ~1023u;
    const uint32_t bars = sb + OFF_BAR, ring = sb + OFF_RING;
    const int tid = threadIdx.x, lane = tid & 31, g = lane >> 2, t4 = lane & 3;
    const int warp = __shfl_sync(0xffffffffu, tid >> 5, 0), wg = warp >> 2, wq = warp & 3;
    const int rank = blockIdx.x & 1, grp = (blockIdx.x >> 1) & 7, rot = blockIdx.x >> 4, mblk = rot * 2 + rank;
    const int nq = grp < 4 ? 2 : 1;
    const int qt0 = grp < 4 ? 2 * grp : 4 + grp;
    const int gu0 = (grp < 4 ? 3 * grp : 4 * grp - 4) - nq;
    const int head = blockIdx.x >> 2, qb = blockIdx.x & 3;

    if (tid == 512) TSTAMP(0);
    if (elect_one()) {
        if (warp == 16) {
            asm volatile("prefetch.tensormap [%0];" :: "l"(&mqkv) : "memory");
            asm volatile("prefetch.tensormap [%0];" :: "l"(rank ? &mw3 : &mw1) : "memory");
        }
#pragma unroll
        for (int i = 0; i < 5; i++) { const int b = warp * 5 + i; mbar_init(bars + 8 * b, b < B_CNT2 ? 1 : b < B_CNT4 ? 2 : b < B_CNT8 ? 4 : 8); }
        asm volatile("fence.mbarrier_init.release.cluster;" ::: "memory");
        if (warp == 8) {
            fence_async_smem();
#pragma unroll
            for (int j = 0; j < 2; j++) { mbar_expect(bars + 8 * (B_A + j), 16384); tma2d(sb + j * 16384, &mx, ((rot + j) & 7) * 64, mblk * 128, bars + 8 * (B_A + j)); }
        }
    }
    if (tid == 512) TSTAMP(26);
    if (tid < 256) {
        asm volatile("st.shared.v4.b32 [%0], {%1,%1,%1,%1};" :: "r"(sb + OFF_ONES + tid * 16), "r"(0x3F803F80u) : "memory");
        if (tid < 128) {
            const bool fx = (FIXED_MASK >> (tid >> 4)) & 1;
            uint32_t a = fx ? pack_bf16(M71, M71) : pack_bf16(P71, P71);
            uint32_t b = fx ? pack_bf16(M71, 47.0f * M71) : pack_bf16(P71, -79.5f * P71);
            uint32_t c = fx ? 0u : pack_bf16(0.08214f * P71, 0.f);
            if (tid & 8) a = b = c = 0;
            asm volatile("st.shared.v4.b32 [%0], {%1,%2,%3,%4};" :: "r"(sb + OFF_B2 + tid * 16), "r"(a), "r"(b), "r"(c), "r"(0) : "memory");
        }
        fence_async_smem();
    }
    __syncthreads();
    asm volatile("barrier.cluster.arrive.relaxed.aligned;" ::: "memory");

    if (wg < 4) {
        const int pair = wg >> 1, half = wg & 1;
        if (pair == 1) {
            const int row = mblk * 128 + grp * 16 + (warp - 8) * 2 + (lane >> 4);
            uint4 v[4];
            const uint32_t* w = reinterpret_cast<const uint32_t*>(v);
#pragma unroll
            for (int j = 0; j < 4; j++) v[j] = __ldg(reinterpret_cast<const uint4*>(x + (size_t)row * DM) + j * 16 + (lane & 15));
            float s0 = 0.f, v0 = 0.f;
#pragma unroll
            for (int j = 0; j < 16; j++) s0 += bf_lo(w[j]) + bf_hi(w[j]);
#pragma unroll
            for (int d = 1; d < 16; d <<= 1) s0 += __shfl_xor_sync(0xffffffffu, s0, d);
            const float mean = s0 * (1.0f / DM);
#pragma unroll
            for (int j = 0; j < 16; j++) { const float a = bf_lo(w[j]) - mean, b = bf_hi(w[j]) - mean; v0 += fmaf(a, a, b * b); }
#pragma unroll
            for (int d = 1; d < 16; d <<= 1) v0 += __shfl_xor_sync(0xffffffffu, v0, d);
            if ((lane & 15) == 0) g_rs[row] = make_float2(bf_round(mean), bf_round(sqrtf(bf_round(bf_round(v0 * (1.0f / DM)) + 1e-5f))));
            __syncwarp();
            if (elect_one()) mbar_arrive(bars + 8 * B_PART);
        }
        asm volatile("barrier.cluster.wait.aligned;" ::: "memory");

        uint32_t q[4], qn[6];
        {
            float acc[64];
            const int rowblk = mblk * 2 + half, tile16 = rowblk * 4 + wq;
#pragma unroll 1
            for (int t = pair; t < 5; t += 2) {
                int prev = 0;
#pragma unroll 1
                for (int j = 0; j < 8; j++) {
                    const int n = stage_of(t, j), kb = pos_of(t, j), slot = n % NRING;
                    if (t < 2) mbar_wait(bars + 8 * (B_A + kb), 0);
                    if (tid == 0 && n == 0) TSTAMP(30);
                    mbar_wait(bars + 8 * (B_FULL + n), 0);
                    if (tid == 0 && n == 0) TSTAMP(1);
                    const uint64_t da = mkdesc(sb + kb * 16384 + half * 8192, 16, 1024, 1), db = mkdesc(ring + slot * 16384, 8192, 1024, 1);
                    wg_fence();
#pragma unroll
                    for (int k = 0; k < 4; k++) wgmma_ss_n128(acc, da + k * 2, db + k * 128, (j | k) != 0);
                    wg_commit();
                    if (j > 0) {
                        wg_wait<1>();
                        if (wq < 2 && elect_one()) mbar_arrive_cluster(bars + 8 * (B_EMPTY + prev), wq);
                        if (t == 4 && wq == 2 && (j == 3 || j == 4 || j == 7) && elect_one()) mbar_arrive(bars + 8 * (j == 3 ? B_AFREE0 : j == 4 ? B_AFREE + 1 : B_AFREE + 2));
                    }
                    prev = slot;
                }
                if (t >= 3) {
                    mbar_wait(bars + 8 * B_QKV, 0);
                    const uint4* pq = g_q + (head * 128 + (qb * 8 + wg) * 4 + wq) * 32 + lane;
                    const uint4 v = __ldcg(pq), u = __ldcg(pq + 512);
                    qn[0] = v.x; qn[1] = v.y; qn[2] = v.z; qn[3] = v.w; q[0] = u.x; q[1] = u.y; q[2] = u.z; q[3] = u.w;
                }
                wg_wait<0>();
                if (wq < 2 && elect_one()) mbar_arrive_cluster(bars + 8 * (B_EMPTY + prev), wq);
                if (t >= 3 && wq == 2 && elect_one()) mbar_arrive(bars + 8 * (t == 4 ? B_AFREE + 3 : B_AFREE0));
                pin<64>(acc);
                if (wq == 0 && half == 0 && lane == 0) TSTAMP(2 + 2 * t);
                mbar_wait(bars + 8 * (B_STATS + t), 0);
                float m0, d0, m1, d1;
                asm volatile("ld.shared.v2.f32 {%0,%1}, [%2];" : "=f"(m0), "=f"(d0) : "r"(sb + OFF_RS + (half * 64 + wq * 16 + g) * 8));
                asm volatile("ld.shared.v2.f32 {%0,%1}, [%2];" : "=f"(m1), "=f"(d1) : "r"(sb + OFF_RS + (half * 64 + wq * 16 + g + 8) * 8));
#pragma unroll
                for (int j = 0; j < 16; j++) {
                    float c0, c1;
                    asm volatile("ld.shared.v2.f32 {%0,%1}, [%2];" : "=f"(c0), "=f"(c1) : "r"(sb + OFF_CS + (t * 128 + j * 8 + t4 * 2) * 4));
                    acc[4 * j] = fmaf(-m0, c0, acc[4 * j]); acc[4 * j + 1] = fmaf(-m0, c1, acc[4 * j + 1]);
                    acc[4 * j + 2] = fmaf(-m1, c0, acc[4 * j + 2]); acc[4 * j + 3] = fmaf(-m1, c1, acc[4 * j + 3]);
                }
                float r0 = 1.0f / d0, r1 = 1.0f / d1;
                if (t < nq) {
                    const int qt = qt0 + t, h0 = (qt & 3) * 8;
                    if (qt < 4) {
                        r0 *= 0.25f * 1.4426950408889634f * M71; r1 *= 0.25f * 1.4426950408889634f * M71;
                    } else if (qt < 8) {
                        r0 *= ((FIXED_MASK >> (2 * wq)) & 1) ? M71 : P71; r1 *= ((FIXED_MASK >> (2 * wq + 1)) & 1) ? M71 : P71;
                    }
                    uint32_t* p; int s8, sh;
                    if (qt < 8) { p = reinterpret_cast<uint32_t*>(g_k + h0 * 4096) + tile16 * 128 + lane; s8 = 64; sh = 32; }
                    else        { p = reinterpret_cast<uint32_t*>(g_v + h0 * 4096) + tile16 * 64 + lane;  s8 = 32; sh = 8192; }
#pragma unroll
                    for (int hh = 0; hh < 8; hh++) {
                        const float* a = acc + hh * 8;
                        const uint32_t e0 = pack_bf16(a[0] * r0, a[1] * r0), e1 = pack_bf16(a[2] * r1, a[3] * r1);
                        const uint32_t e2 = pack_bf16(a[4] * r0, a[5] * r0), e3 = pack_bf16(a[6] * r1, a[7] * r1);
                        if (qt < 4) g_q[((h0 + hh) * 128 + tile16) * 32 + lane] = make_uint4(e0, e1, e2, e3);
                        else { uint32_t* pp = p + hh * 16384; pp[0] = e0; pp[s8] = e1; pp[sh] = e2; pp[sh + s8] = e3; }
                    }
                } else {
                    uint32_t* p = reinterpret_cast<uint32_t*>(g_h + (rowblk * 28 + gu0 + t) * 512) + wq * 512 + lane;
                    r0 *= -1.4426950408889634f; r1 *= -1.4426950408889634f; d0 *= d0; d1 *= d1;
#pragma unroll
                    for (int j = 0; j < 8; j++) {
                        const float* a = acc + j * 4; const float* b = a + 32;
                        p[j * 32] = pack_bf16(a[0] * b[0] * rcpf(fmaf(ex2f(a[0] * r0), d0, d0)), a[1] * b[1] * rcpf(fmaf(ex2f(a[1] * r0), d0, d0)));
                        p[256 + j * 32] = pack_bf16(a[2] * b[2] * rcpf(fmaf(ex2f(a[2] * r1), d1, d1)), a[3] * b[3] * rcpf(fmaf(ex2f(a[3] * r1), d1, d1)));
                    }
                }
                __syncwarp();
                if (elect_one()) mbar_arrive(bars + 8 * (B_TILE + t));
                if (wq == 0 && half == 0 && lane == 0) TSTAMP(3 + 2 * t);
            }
        }
        const uint64_t db2 = mkdesc(sb + OFF_B2, 128, 256, 0);
        float s[32];
        auto ref_point = [&](int ntile, uint32_t& b0, uint32_t& b1) {
            float m0 = -INFINITY, m1 = -INFINITY, f0 = -INFINITY, f1 = -INFINITY;
#pragma unroll 1
            for (int t = 0; t < ntile; t++) {
                wg_fence();
                wgmma_rs_n64_zero(s, q, mkdesc(k_tile_addr(sb, t), 128, 256, 0));
                wg_commit();
                wg_wait<0>();
                pin<32>(s);
#pragma unroll
                for (int i = 0; i < 8; i++) {
                    if ((FIXED_MASK >> i) & 1) { f0 = fmaxf(f0, fmaxf(s[4 * i], s[4 * i + 1])); f1 = fmaxf(f1, fmaxf(s[4 * i + 2], s[4 * i + 3])); }
                    else                       { m0 = fmaxf(m0, fmaxf(s[4 * i], s[4 * i + 1])); m1 = fmaxf(m1, fmaxf(s[4 * i + 2], s[4 * i + 3])); }
                }
            }
            m0 = fmaxf(m0, f0 * P71 * P71); m1 = fmaxf(m1, f1 * P71 * P71);
            m0 = fmaxf(m0, __shfl_xor_sync(0xffffffffu, m0, 1)); m1 = fmaxf(m1, __shfl_xor_sync(0xffffffffu, m1, 1));
            m0 = fmaxf(m0, __shfl_xor_sync(0xffffffffu, m0, 2)); m1 = fmaxf(m1, __shfl_xor_sync(0xffffffffu, m1, 2));
#pragma unroll
            for (int r = 0; r < 2; r++) {
                const float m = -rintf(r ? m1 : m0), mh = bf_round(m), mm = bf_round(m - mh), ml = m - mh - mm;
                const float lo = t4 == 0 ? mh : t4 == 1 ? ml : t4 == 2 ? 1.f : 0.f, hi = t4 == 0 ? mm : t4 == 1 ? 1.f : 0.f;
                (r ? b1 : b0) = pack_bf16(lo * M71, hi * M71);
            }
        };
        uint32_t q2[4];
        int redo = 1;
        mbar_wait(bars + 8 * B_KV, 0);
#pragma unroll 1
        for (int round = -1; round < 2;) {
            if (redo) ref_point(redo, q2[0], q2[1]);
            if (round < 0) {
#pragma unroll
                for (int i = 0; i < 4; i++) { const uint32_t tq = q[i]; q[i] = qn[i]; qn[i] = tq; }
                qn[4] = q2[0]; qn[5] = q2[1];
                q2[2] = __shfl_sync(0xffffffffu, q2[0], 3); q2[3] = __shfl_sync(0xffffffffu, q2[1], 3);
                round = 0;
                continue;
            }
            float o[12]; uint32_t p[16];
#pragma unroll
            for (int i = 0; i < 12; i++) o[i] = 0.f;
            pin<12>(o); pin<4>(q2);
            if (wq == 0 && half == 0 && lane == 0) TSTAMP(12 + 4 * round + pair);
            uint64_t dk0 = mkdesc(sb + 4096, 128, 256, 0), dk1 = mkdesc(sb + 98304, 128, 256, 0), dv = mkdesc(sb, 128, 65536, 0);
#pragma unroll 1
            for (int c = 0; c < 8; c++, dk0 += 512, dk1 += 256, dv += 512 - (256ull << 32)) {
                if (round == 0) mbar_wait(bars + 8 * (B_KV + c), 0);
#pragma unroll
                for (int t = 0; t < 4; t++) {
                    wg_fence();
                    wgmma_rs_n64_zero(s, q, (t & 2 ? dk1 : dk0) + (t & 1) * 128);
                    wgmma_rs_n64_acc(s, q2, db2);
                    wg_commit();
                    wg_wait<0>();
                    pin<32>(s); pin<16>(p);
#pragma unroll
                    for (int i = 0; i < 16; i++) {
                        if ((FIXED_MASK >> (i >> 1)) & 1) p[i] = exp2_fixed(s[2 * i], s[2 * i + 1], half2);
                        else                              p[i] = pack_bf16(ex2f(s[2 * i]), ex2f(s[2 * i + 1]));
                    }
                    wg_fence();
#pragma unroll
                    for (int k = 0; k < 4; k++) wgmma_rs_n24_acc(o, p + 4 * k, dv + (t * 4 + k) * 16);
                    wg_commit();
                }
            }
            wg_wait<0>();
            pin<12>(o);
            if (redo != 32) {
                float chk = (o[8] + o[10]) * 256.f;
#pragma unroll
                for (int i = 0; i < 8; i++) chk += fabsf(o[i]);
                uint32_t bad;
                asm volatile("{\n.reg .pred p, q;\nsetp.geu.f32 q, %1, 0f7F800000;\nbar.red.or.pred p, %2, 128, q;\nselp.u32 %0, 1, 0, p;\n}" : "=r"(bad) : "f"(chk), "r"(1 + wg) : "memory");
                if (__any_sync(0xffffffffu, bad)) { redo = 32; continue; }
            }
            const int rowblk = qb * 8 + round * 4 + wg;
            const float r0 = rcpf(o[8]), r1 = rcpf(o[10]);
            uint32_t* po = reinterpret_cast<uint32_t*>(g_o + (rowblk * 8 + (head >> 2)) * 512) + wq * 512 + (head & 3) * 64 + lane;
            po[0] = pack_bf16(o[0] * r0, o[1] * r0); po[256] = pack_bf16(o[2] * r1, o[3] * r1);
            po[32] = pack_bf16(o[4] * r0, o[5] * r0); po[288] = pack_bf16(o[6] * r1, o[7] * r1);
            if (round == 0) {
                __syncwarp();
                if (elect_one()) mbar_arrive(bars + 8 * (B_OW + pair));
            } else {
                bar_sync(1 + wg, 128);
                if (wq == 0 && elect_one()) { mbar_arrive(bars + 8 * B_DONE); signal_cnt(C_O + rowblk); }
            }
#pragma unroll
            for (int i = 0; i < 4; i++) q[i] = qn[i];
            q2[0] = qn[4]; q2[1] = qn[5];
            redo = 0;
            if (wq == 0 && half == 0 && lane == 0) TSTAMP(14 + 4 * round + pair);
            round++;
        }
    } else {
        if (wq > 0) {
#pragma unroll 1
            for (int t = wq - 1; t < (wq == 3 ? 5 : wq); t++) {
                const __nv_bfloat16* src; int ld;
                if (t < nq) { src = wqkv + (qt0 + t) * 128 + rank * 64; ld = 3 * DM; }
                else        { src = (rank ? w3 : w1) + (gu0 + t) * 64; ld = FF; }
                src += (size_t)(rot * 64 + (lane >> 3)) * ld + (lane & 7) * 8;
                uint4 v[16];
                const uint32_t* w = reinterpret_cast<const uint32_t*>(v);
#pragma unroll
                for (int j = 0; j < 16; j++) v[j] = __ldg(reinterpret_cast<const uint4*>(src + (size_t)j * 4 * ld));
                float c[8];
#pragma unroll
                for (int e = 0; e < 4; e++) {
                    float a = 0.f, b = 0.f;
#pragma unroll
                    for (int j = 0; j < 16; j++) { a += bf_lo(w[4 * j + e]); b += bf_hi(w[4 * j + e]); }
                    a += __shfl_xor_sync(0xffffffffu, a, 8); b += __shfl_xor_sync(0xffffffffu, b, 8);
                    a += __shfl_xor_sync(0xffffffffu, a, 16); b += __shfl_xor_sync(0xffffffffu, b, 16);
                    c[2 * e] = a; c[2 * e + 1] = b;
                }
                if (lane < 16) g_cs[((grp * 5 + t) * 8 + rot) * 32 + rank * 16 + (lane & 7) * 2 + (lane >> 3)] =
                    lane < 8 ? make_float4(c[0], c[1], c[2], c[3]) : make_float4(c[4], c[5], c[6], c[7]);
            }
            if (wq == 2) mbar_wait(bars + 8 * B_PART, 0);
            __syncwarp();
            if (elect_one()) {
                signal_cnt(C_COL + grp * 2 + (wq == 3));
                if (wq == 2) asm volatile("red.relaxed.gpu.global.add.u32 [%0], 1;" :: "l"(g_cnt + (C_ROW + mblk) * 8) : "memory");
            }
        }
        asm volatile("barrier.cluster.wait.aligned;" ::: "memory");
        if (tid == 512) TSTAMP(27);
        if (wq == 0) {
#pragma unroll 1
            for (int n = 0; n < 40; n++) {
                int t, j;
                if (n < 12) { const int a = n / 3, b = n - 3 * a; t = b == 2; j = t ? a : 2 * a + b; } else { t = n >> 3; j = n & 7; }
                const int slot = n % NRING;
                if (n >= NRING) mbar_wait(bars + 8 * (B_EMPTY + slot), (n / NRING - 1) & 1);
                if (elect_one()) {
                    mbar_expect(bars + 8 * (B_FULL + n), 16384);
                    const CUtensorMap* m = t < nq ? &mqkv : rank ? &mw3 : &mw1;
                    const int col = t < nq ? (qt0 + t) * 128 + rank * 64 : (gu0 + t) * 64;
                    tma2d_mc(ring + slot * 16384 + rank * 8192, m, col, ((pos_of(t, j) + rot) & 7) * 64, bars + 8 * (B_FULL + n));
                    if (n < 3) {
#pragma unroll 1
                        for (int kb = 2 + 2 * n; kb < 4 + 2 * n; kb++) { mbar_expect(bars + 8 * (B_A + kb), 16384); tma2d(sb + kb * 16384, &mx, ((rot + kb) & 7) * 64, mblk * 128, bars + 8 * (B_A + kb)); }
                    }
                }
            }
        } else if (wq == 1) {
            wait_cnt(C_ROW + mblk, 8, 100);
#pragma unroll
            for (int i = 0; i < 2; i++) {
                const float4 a = __ldcg(reinterpret_cast<const float4*>(g_rs + mblk * 128) + i * 32 + lane);
                asm volatile("st.shared.v4.f32 [%0], {%1,%2,%3,%4};" :: "r"(sb + OFF_RS + (i * 32 + lane) * 16), "f"(a.x), "f"(a.y), "f"(a.z), "f"(a.w) : "memory");
            }
#pragma unroll 1
            for (int t = 0; t < 5; t++) {
                if (t == 0 || t == 2) wait_cnt(C_COL + grp * 2 + (t >> 1), t ? 16 : 32, 100);
                float4 a = make_float4(0.f, 0.f, 0.f, 0.f);
#pragma unroll
                for (int kp = 0; kp < 8; kp++) { const float4 b = __ldcg(g_cs + ((grp * 5 + t) * 8 + kp) * 32 + lane); a.x += b.x; a.y += b.y; a.z += b.z; a.w += b.w; }
                asm volatile("st.shared.v4.f32 [%0], {%1,%2,%3,%4};" :: "r"(sb + OFF_CS + (t * 32 + lane) * 16), "f"(a.x), "f"(a.y), "f"(a.z), "f"(a.w) : "memory");
                __syncwarp();
                if (elect_one()) { mbar_arrive(bars + 8 * (B_STATS + t)); if (t == 0) TSTAMP(28); if (t == 4) TSTAMP(31); }
            }
#pragma unroll 1
            for (int i = 0; i < 3; i++) wait_cnt(C_QKV + i * 4 + (head >> 3), 16, 100);
            if (elect_one()) { mbar_arrive(bars + 8 * B_QKV); TSTAMP(29); }
            fence_async_all();
            const uint8_t* gk = reinterpret_cast<const uint8_t*>(g_k + head * 4096);
            const uint8_t* gv = reinterpret_cast<const uint8_t*>(g_v + head * 4096);
#pragma unroll 1
            for (int c = 0; c < 8; c++) {
                if (!(c & 1)) mbar_wait(bars + 8 * (c ? B_AFREE + (c >> 1) : B_AFREE0), 0);
                if (elect_one()) {
                    const uint32_t b = bars + 8 * (B_KV + c);
                    mbar_expect(b, 16384);
                    bulk_load(sb + (2 * c + 1) * 4096, gk + c * 8192, 4096, b);
                    bulk_load(sb + 2 * c * 4096, gv + c * 4096, 4096, b);
                    bulk_load(sb + 65536 + c * 4096, gv + 32768 + c * 4096, 4096, b);
                    bulk_load(sb + 98304 + c * 4096, gk + c * 8192 + 4096, 4096, b);
                }
            }
        } else if (wq == 2) {
#pragma unroll 1
            for (int t = 0; t < 5; t++) {
                mbar_wait(bars + 8 * (B_TILE + t), 0);
                if (elect_one()) signal_cnt(t < nq ? C_QKV + qt0 + t : C_H + mblk);
            }
        }
        bar_sync(5, 128);
        const int cb = blockIdx.x & 7, pr = blockIdx.x >> 3;
        const int rb0 = (pr >> 2) * 8 + (pr & 3);
        uint32_t gate[2][16];
        {
            float dn[64];
            auto load_stage = [&](int kb, int st) {
                const uint32_t b = bars + 8 * (B_RING + st), dst = ring + st * 24576;
                mbar_expect(b, 24576);
                bulk_load(dst, g_h + (rb0 * 28 + kb) * 512, 8192, b);
                bulk_load(dst + 8192, g_h + ((rb0 + 4) * 28 + kb) * 512, 8192, b);
                tma2d(dst + 16384, &mw2, cb * 64, kb * 64, b);
            };
            if (wq == 0) {
                wait_cnt(C_H + (rb0 >> 1), 28, 200);
                wait_cnt(C_H + (rb0 >> 1) + 2, 28, 200);
                if (elect_one()) { TSTAMP(20); fence_async_all(); load_stage(0, 0); load_stage(1, 1); }
            }
            int st = 0; uint32_t ph = 0;
#pragma unroll 1
            for (int kb = 0; kb < 28; kb++) {
                mbar_wait(bars + 8 * (B_RING + st), ph);
                const uint64_t da = mkdesc(ring + st * 24576, 128, 1024, 0), db = mkdesc(ring + st * 24576 + 16384, 8192, 1024, 1);
                wg_fence();
#pragma unroll
                for (int k = 0; k < 4; k++) { wgmma_ss_n64(dn, da + k * 16, db + k * 128, (kb | k) != 0); wgmma_ss_n64(dn + 32, da + 512 + k * 16, db + k * 128, (kb | k) != 0); }
                wg_commit();
                wg_wait<1>();
                if (wq == 0 && kb < 26 && elect_one()) load_stage(kb + 2, st == 0 ? 2 : st - 1);
                if (++st == 3) { st = 0; ph ^= 1; }
            }
            wg_wait<0>();
            pin<64>(dn);
#pragma unroll
            for (int i = 0; i < 32; i++) gate[i >> 4][i & 15] = pack_bf16(siluf(dn[2 * i]), siluf(dn[2 * i + 1]));
        }
        float acc[32];
        if (tid == 512) TSTAMP(21);
        const uint32_t bar_wo = bars + 8 * B_WO;
        if (wq == 0 && elect_one()) {
            mbar_expect(bar_wo, 65536);
#pragma unroll 1
            for (int i = 0; i < 8; i++) tma2d(ring + i * 8192, &mwo, cb * 64, i * 64, bar_wo);
        }
        if (wq >= 2) {
            mbar_wait(bars + 8 * (B_OW + wq - 2), 0);
            if (elect_one()) {
                signal_cnt(C_O + qb * 8 + 2 * wq - 4);
                asm volatile("red.relaxed.gpu.global.add.u32 [%0], 1;" :: "l"(g_cnt + (C_O + qb * 8 + 2 * wq - 3) * 8) : "memory");
            }
        }
#pragma unroll
        for (int tl = 0; tl < 2; tl++) {
            const int rb = rb0 + 4 * tl;
            uint32_t xr[16];
            const uint32_t* px = reinterpret_cast<const uint32_t*>(x + (size_t)(rb * 64 + wq * 16 + g) * DM + cb * 64) + t4;
#pragma unroll
            for (int j = 0; j < 8; j++) { xr[2 * j] = __ldg(px + j * 4); xr[2 * j + 1] = __ldg(px + 8 * DM / 2 + j * 4); }
            if (wq == 0) {
                if (tl == 1) mbar_wait(bars + 8 * B_DONE, 0);
                wait_cnt(C_O + rb, 32, tl ? 20 : 200);
                if (elect_one()) {
                    fence_async_all();
                    TSTAMP(22 + 2 * tl);
#pragma unroll 1
                    for (int i = 0; i < (tl ? 8 : 2); i++) {
                        mbar_expect(bars + 8 * (B_O + i), 8192);
                        bulk_load((tl ? sb : ring + 65536) + i * 8192, g_o + (rb * 8 + i) * 512, 8192, bars + 8 * (B_O + i));
                    }
                }
            }
            if (tl == 0) mbar_wait(bar_wo, 0);
#pragma unroll 1
            for (int kb = 0; kb < 8; kb++) {
                mbar_wait(bars + 8 * (B_O + kb), tl);
                const uint32_t a = tl == 0 ? ring + 65536 + (kb & 1) * 8192 : sb + kb * 8192;
                const uint64_t da = mkdesc(a, 128, 1024, 0), db = mkdesc(ring + kb * 8192, 8192, 1024, 1);
                wg_fence();
#pragma unroll
                for (int k = 0; k < 4; k++) wgmma_ss_n64(acc, da + k * 16, db + k * 128, (kb | k) != 0);
                wg_commit();
                if (tl == 0) {
                    wg_wait<0>();
                    bar_sync(5, 128);
                    if (wq == 0 && kb < 6 && elect_one()) { mbar_expect(bars + 8 * (B_O + kb + 2), 8192); bulk_load(a, g_o + (rb * 8 + kb + 2) * 512, 8192, bars + 8 * (B_O + kb + 2)); }
                }
            }
            unsigned ticket = 0;
            if (tl == 1 && tid == 512 + 96) ticket = atomicInc(&g_ticket, 127);
            wg_wait<0>();
            pin<32>(acc);
            uint32_t* po = reinterpret_cast<uint32_t*>(out + (size_t)(rb * 64 + wq * 16 + g) * DM + cb * 64) + t4;
#pragma unroll
            for (int i = 0; i < 16; i++) {
                const uint32_t r = pack_bf16(fmaf(acc[2 * i], bf_lo(gate[tl][i]), bf_lo(xr[i])), fmaf(acc[2 * i + 1], bf_hi(gate[tl][i]), bf_hi(xr[i])));
                po[(i & 1) * (8 * DM / 2) + (i >> 1) * 4] = r;
            }
            if (tl == 1 && wq == 3 && __any_sync(0xffffffffu, ticket == 127)) {
#pragma unroll 1
                for (int i = lane; i < C_NUM; i += 32) g_cnt[i * 8] = 0;
            }
            if (tid == 512) TSTAMP(23 + 2 * tl);
        }
    }
}

typedef CUresult (*EncodeFn)(CUtensorMap*, CUtensorMapDataType, cuuint32_t, void*, const cuuint64_t*, const cuuint64_t*, const cuuint32_t*,
                             const cuuint32_t*, CUtensorMapInterleave, CUtensorMapSwizzle, CUtensorMapL2promotion, CUtensorMapFloatOOBfill);

void make_map(EncodeFn fn, CUtensorMap* m, const void* p, int rows, int cols, int box_rows) {
    cuuint64_t dims[2] = {(cuuint64_t)cols, (cuuint64_t)rows};
    cuuint64_t strides[1] = {(cuuint64_t)cols * 2};
    cuuint32_t box[2] = {64, (cuuint32_t)box_rows};
    cuuint32_t es[2] = {1, 1};
    fn(m, CU_TENSOR_MAP_DATA_TYPE_BFLOAT16, 2, const_cast<void*>(p), dims, strides, box, es, CU_TENSOR_MAP_INTERLEAVE_NONE,
       CU_TENSOR_MAP_SWIZZLE_128B, CU_TENSOR_MAP_L2_PROMOTION_L2_128B, CU_TENSOR_MAP_FLOAT_OOB_FILL_NONE);
}

}

extern "C" void kernel_launch(void* const* d_in, const int* in_sizes, int n_in, void* d_out, int out_size) {
    const __nv_bfloat16* x = (const __nv_bfloat16*)d_in[0];
    static EncodeFn fn = nullptr;
    if (!fn) {
        cudaDriverEntryPointQueryResult qr;
        cudaGetDriverEntryPoint("cuTensorMapEncodeTiled", (void**)&fn, cudaEnableDefault, &qr);
        cudaFuncSetAttribute(mega_kernel, cudaFuncAttributeMaxDynamicSharedMemorySize, SMEM_BYTES);
    }
    CUtensorMap mx, mqkv, mw1, mw3, mw2, mwo;
    make_map(fn, &mx, d_in[0], SEQ, DM, 128);
    make_map(fn, &mqkv, d_in[1], DM, 3 * DM, 64);
    make_map(fn, &mwo, d_in[2], DM, DM, 64);
    make_map(fn, &mw1, d_in[4], DM, FF, 64);
    make_map(fn, &mw3, d_in[5], DM, FF, 64);
    make_map(fn, &mw2, d_in[6], FF, DM, 64);
    mega_kernel<<<128, 640, SMEM_BYTES, cudaStreamPerThread>>>(x, (const __nv_bfloat16*)d_in[1], (const __nv_bfloat16*)d_in[4], (const __nv_bfloat16*)d_in[5],
                                                               (__nv_bfloat16*)d_out, mx, mqkv, mw1, mw3, mw2, mwo, 0x3F003F00u);
}
```

```cpp
#include <cuda_runtime.h>
#include <cuda_bf16.h>
#include <cuda.h>
#include <stdint.h>

namespace {

constexpr int SEQ = 2048, DM = 512, FF = 1792;

__device__ uint4 g_q[32 * 128 * 32];
__device__ uint4 g_k[32 * 4096];
__device__ uint4 g_v[32 * 4096];
__device__ uint4 g_h[32 * 28 * 512];
__device__ uint4 g_o[32 * 8 * 512];
__device__ float4 g_cs[40 * 8 * 32];
__device__ float2 g_rs[SEQ];
constexpr int C_COL = 0, C_ROW = 16, C_QKV = 32, C_H = 44, C_O = 60, C_NUM = 92;
__device__ unsigned g_cnt[C_NUM * 8];
__device__ unsigned g_ticket;
#define TSTAMP(i)
#define TS2(k, i)

__device__ __forceinline__ uint32_t smem_u32(const void* p) { return (uint32_t)__cvta_generic_to_shared(p); }
__device__ __forceinline__ void mbar_init(uint32_t a, int c) { asm volatile("mbarrier.init.shared::cta.b64 [%0], %1;" :: "r"(a), "r"(c)); }
__device__ __forceinline__ void mbar_expect(uint32_t a, int b) { asm volatile("mbarrier.arrive.expect_tx.shared::cta.b64 _, [%0], %1;" :: "r"(a), "r"(b) : "memory"); }
__device__ __forceinline__ void mbar_arrive(uint32_t a) { asm volatile("mbarrier.arrive.shared::cta.b64 _, [%0];" :: "r"(a) : "memory"); }
__device__ __forceinline__ void mbar_arrive_remote(uint32_t a) { asm volatile("mbarrier.arrive.shared::cluster.b64 _, [%0];" :: "r"(a) : "memory"); }
__device__ __forceinline__ bool mbar_try(uint32_t a, uint32_t ph) {
    uint32_t ok;
    asm volatile("{\n.reg .pred p;\nmbarrier.try_wait.parity.shared::cta.b64 p, [%1], %2;\nselp.u32 %0, 1, 0, p;\n}" : "=r"(ok) : "r"(a), "r"(ph) : "memory");
    return ok;
}
__device__ __forceinline__ void mbar_wait(uint32_t a, uint32_t ph) {
    for (int n = 0; !__all_sync(0xffffffffu, mbar_try(a, ph)); n++) if (n > 4000000) __trap();
}
__device__ __forceinline__ bool elect_one() {
    uint32_t p;
    asm volatile("{\n.reg .pred P;\nelect.sync _|P, 0xffffffff;\nselp.u32 %0, 1, 0, P;\n}" : "=r"(p));
    return p;
}
__device__ __forceinline__ void signal_cnt(int c) {
    asm volatile("fence.acq_rel.gpu;\nred.relaxed.gpu.global.add.u32 [%0], 1;" :: "l"(g_cnt + c * 8) : "memory");
}
__device__ __forceinline__ void wait_cnt(int c, unsigned target, int ns) {
    for (int n = 0;; n++) {
        unsigned v;
        asm volatile("ld.acquire.gpu.global.u32 %0, [%1];" : "=r"(v) : "l"(g_cnt + c * 8) : "memory");
        if (__all_sync(0xffffffffu, v >= target)) break;
        if (n > 2000000) __trap();
        __nanosleep(ns);
    }
}
__device__ __forceinline__ void tma2d(uint32_t dst, const CUtensorMap* m, int c0, int c1, uint32_t bar) {
    asm volatile("cp.async.bulk.tensor.2d.shared::cluster.global.mbarrier::complete_tx::bytes [%0], [%1, {%3, %4}], [%2];"
                 :: "r"(dst), "l"(m), "r"(bar), "r"(c0), "r"(c1) : "memory");
}
__device__ __forceinline__ void tma2d_mc(uint32_t dst, const CUtensorMap* m, int c0, int c1, uint32_t bar) {
    asm volatile("cp.async.bulk.tensor.2d.shared::cluster.global.mbarrier::complete_tx::bytes.multicast::cluster [%0], [%1, {%3, %4}], [%2], %5;"
                 :: "r"(dst), "l"(m), "r"(bar), "r"(c0), "r"(c1), "h"((uint16_t)3) : "memory");
}
__device__ __forceinline__ void bulk_load(uint32_t dst, const void* src, int bytes, uint32_t bar) {
    asm volatile("cp.async.bulk.shared::cluster.global.mbarrier::complete_tx::bytes [%0], [%1], %2, [%3];"
                 :: "r"(dst), "l"(src), "r"(bytes), "r"(bar) : "memory");
}
__device__ __forceinline__ void bar_sync(int id, int n) { asm volatile("bar.sync %0, %1;" :: "r"(id), "r"(n) : "memory"); }
__device__ __forceinline__ void fence_async_smem() { asm volatile("fence.proxy.async.shared::cta;" ::: "memory"); }
__device__ __forceinline__ void fence_async_all() { asm volatile("fence.proxy.async;" ::: "memory"); }
__device__ __forceinline__ void wg_fence() { asm volatile("wgmma.fence.sync.aligned;" ::: "memory"); }
__device__ __forceinline__ void wg_commit() { asm volatile("wgmma.commit_group.sync.aligned;" ::: "memory"); }
template <int N> __device__ __forceinline__ void wg_wait() { asm volatile("wgmma.wait_group.sync.aligned %0;" :: "n"(N) : "memory"); }
template <int N> __device__ __forceinline__ void pin(float* d) {
#pragma unroll
    for (int i = 0; i < N; i++) asm volatile("" : "+f"(d[i]) :: "memory");
}
template <int N> __device__ __forceinline__ void pin(uint32_t* d) {
#pragma unroll
    for (int i = 0; i < N; i++) asm volatile("" : "+r"(d[i]) :: "memory");
}
constexpr uint32_t SMEM_BASE = 1024;
__device__ __forceinline__ uint64_t mkdesc(uint32_t off, uint32_t lbo, uint32_t sbo, uint32_t swz) {
    return (uint64_t)((SMEM_BASE + off) >> 4) | ((uint64_t)(lbo >> 4) << 16) | ((uint64_t)(sbo >> 4) << 32) | ((uint64_t)swz << 62);
}
__device__ __forceinline__ float ex2f(float x) { float y; asm("ex2.approx.ftz.f32 %0, %1;" : "=f"(y) : "f"(x)); return y; }
__device__ __forceinline__ float rcpf(float x) { float y; asm("rcp.approx.ftz.f32 %0, %1;" : "=f"(y) : "f"(x)); return y; }
__device__ __forceinline__ uint32_t pack_bf16(float lo, float hi) { uint32_t r; asm("cvt.rn.bf16x2.f32 %0, %1, %2;" : "=r"(r) : "f"(hi), "f"(lo)); return r; }
__device__ __forceinline__ float bf_lo(uint32_t v) { return __uint_as_float(v << 16); }
__device__ __forceinline__ float bf_hi(uint32_t v) { return __uint_as_float(v & 0xFFFF0000u); }
__device__ __forceinline__ float bf_round(float x) { return __bfloat162float(__float2bfloat16_rn(x)); }
__device__ __forceinline__ float siluf(float g) { return g * rcpf(1.0f + ex2f(g * -1.4426950408889634f)); }

__device__ __forceinline__ void wgmma_ss_n256(float* d, uint64_t da, uint64_t db, int acc) {
    asm volatile("{\n.reg .pred p;\nsetp.ne.b32 p, %130, 0;\nwgmma.mma_async.sync.aligned.m64n256k16.f32.bf16.bf16 {"
        "%0,%1,%2,%3,%4,%5,%6,%7,%8,%9,%10,%11,%12,%13,%14,%15,%16,%17,%18,%19,%20,%21,%22,%23,%24,%25,%26,%27,%28,%29,%30,%31,%32,%33,%34,%35,%36,%37,%38,%39,"
        "%40,%41,%42,%43,%44,%45,%46,%47,%48,%49,%50,%51,%52,%53,%54,%55,%56,%57,%58,%59,%60,%61,%62,%63,%64,%65,%66,%67,%68,%69,%70,%71,%72,%73,%74,%75,%76,"
        "%77,%78,%79,%80,%81,%82,%83,%84,%85,%86,%87,%88,%89,%90,%91,%92,%93,%94,%95,%96,%97,%98,%99,%100,%101,%102,%103,%104,%105,%106,%107,%108,%109,%110,"
        "%111,%112,%113,%114,%115,%116,%117,%118,%119,%120,%121,%122,%123,%124,%125,%126,%127"
        "}, %128, %129, p, 1, 1, 0, 1;\n}\n"
        : "+f"(d[0]),"+f"(d[1]),"+f"(d[2]),"+f"(d[3]),"+f"(d[4]),"+f"(d[5]),"+f"(d[6]),"+f"(d[7]),"+f"(d[8]),"+f"(d[9]),"+f"(d[10]),"+f"(d[11]),"+f"(d[12]),
          "+f"(d[13]),"+f"(d[14]),"+f"(d[15]),"+f"(d[16]),"+f"(d[17]),"+f"(d[18]),"+f"(d[19]),"+f"(d[20]),"+f"(d[21]),"+f"(d[22]),"+f"(d[23]),"+f"(d[24]),
          "+f"(d[25]),"+f"(d[26]),"+f"(d[27]),"+f"(d[28]),"+f"(d[29]),"+f"(d[30]),"+f"(d[31]),"+f"(d[32]),"+f"(d[33]),"+f"(d[34]),"+f"(d[35]),"+f"(d[36]),
          "+f"(d[37]),"+f"(d[38]),"+f"(d[39]),"+f"(d[40]),"+f"(d[41]),"+f"(d[42]),"+f"(d[43]),"+f"(d[44]),"+f"(d[45]),"+f"(d[46]),"+f"(d[47]),"+f"(d[48]),
          "+f"(d[49]),"+f"(d[50]),"+f"(d[51]),"+f"(d[52]),"+f"(d[53]),"+f"(d[54]),"+f"(d[55]),"+f"(d[56]),"+f"(d[57]),"+f"(d[58]),"+f"(d[59]),"+f"(d[60]),
          "+f"(d[61]),"+f"(d[62]),"+f"(d[63]),"+f"(d[64]),"+f"(d[65]),"+f"(d[66]),"+f"(d[67]),"+f"(d[68]),"+f"(d[69]),"+f"(d[70]),"+f"(d[71]),"+f"(d[72]),
          "+f"(d[73]),"+f"(d[74]),"+f"(d[75]),"+f"(d[76]),"+f"(d[77]),"+f"(d[78]),"+f"(d[79]),"+f"(d[80]),"+f"(d[81]),"+f"(d[82]),"+f"(d[83]),"+f"(d[84]),
          "+f"(d[85]),"+f"(d[86]),"+f"(d[87]),"+f"(d[88]),"+f"(d[89]),"+f"(d[90]),"+f"(d[91]),"+f"(d[92]),"+f"(d[93]),"+f"(d[94]),"+f"(d[95]),"+f"(d[96]),
          "+f"(d[97]),"+f"(d[98]),"+f"(d[99]),"+f"(d[100]),"+f"(d[101]),"+f"(d[102]),"+f"(d[103]),"+f"(d[104]),"+f"(d[105]),"+f"(d[106]),"+f"(d[107]),
          "+f"(d[108]),"+f"(d[109]),"+f"(d[110]),"+f"(d[111]),"+f"(d[112]),"+f"(d[113]),"+f"(d[114]),"+f"(d[115]),"+f"(d[116]),"+f"(d[117]),"+f"(d[118]),
          "+f"(d[119]),"+f"(d[120]),"+f"(d[121]),"+f"(d[122]),"+f"(d[123]),"+f"(d[124]),"+f"(d[125]),"+f"(d[126]),"+f"(d[127])
        : "l"(da), "l"(db), "r"(acc));
}
__device__ __forceinline__ void wgmma_ss_n128(float* d, uint64_t da, uint64_t db, int acc) {
    asm volatile("{\n.reg .pred p;\nsetp.ne.b32 p, %66, 0;\nwgmma.mma_async.sync.aligned.m64n128k16.f32.bf16.bf16 {"
        "%0,%1,%2,%3,%4,%5,%6,%7,%8,%9,%10,%11,%12,%13,%14,%15,%16,%17,%18,%19,%20,%21,%22,%23,%24,%25,%26,%27,%28,%29,%30,%31,%32,%33,%34,%35,%36,%37,%38,%39,"
        "%40,%41,%42,%43,%44,%45,%46,%47,%48,%49,%50,%51,%52,%53,%54,%55,%56,%57,%58,%59,%60,%61,%62,%63"
        "}, %64, %65, p, 1, 1, 0, 1;\n}\n"
        : "+f"(d[0]),"+f"(d[1]),"+f"(d[2]),"+f"(d[3]),"+f"(d[4]),"+f"(d[5]),"+f"(d[6]),"+f"(d[7]),"+f"(d[8]),"+f"(d[9]),"+f"(d[10]),"+f"(d[11]),"+f"(d[12]),
          "+f"(d[13]),"+f"(d[14]),"+f"(d[15]),"+f"(d[16]),"+f"(d[17]),"+f"(d[18]),"+f"(d[19]),"+f"(d[20]),"+f"(d[21]),"+f"(d[22]),"+f"(d[23]),"+f"(d[24]),
          "+f"(d[25]),"+f"(d[26]),"+f"(d[27]),"+f"(d[28]),"+f"(d[29]),"+f"(d[30]),"+f"(d[31]),"+f"(d[32]),"+f"(d[33]),"+f"(d[34]),"+f"(d[35]),"+f"(d[36]),
          "+f"(d[37]),"+f"(d[38]),"+f"(d[39]),"+f"(d[40]),"+f"(d[41]),"+f"(d[42]),"+f"(d[43]),"+f"(d[44]),"+f"(d[45]),"+f"(d[46]),"+f"(d[47]),"+f"(d[48]),
          "+f"(d[49]),"+f"(d[50]),"+f"(d[51]),"+f"(d[52]),"+f"(d[53]),"+f"(d[54]),"+f"(d[55]),"+f"(d[56]),"+f"(d[57]),"+f"(d[58]),"+f"(d[59]),"+f"(d[60]),
          "+f"(d[61]),"+f"(d[62]),"+f"(d[63])
        : "l"(da), "l"(db), "r"(acc));
}
__device__ __forceinline__ void wgmma_ss_n64(float* d, uint64_t da, uint64_t db, int acc) {
    asm volatile("{\n.reg .pred p;\nsetp.ne.b32 p, %34, 0;\nwgmma.mma_async.sync.aligned.m64n64k16.f32.bf16.bf16 {"
        "%0,%1,%2,%3,%4,%5,%6,%7,%8,%9,%10,%11,%12,%13,%14,%15,%16,%17,%18,%19,%20,%21,%22,%23,%24,%25,%26,%27,%28,%29,%30,%31"
        "}, %32, %33, p, 1, 1, 0, 1;\n}\n"
        : "+f"(d[0]),"+f"(d[1]),"+f"(d[2]),"+f"(d[3]),"+f"(d[4]),"+f"(d[5]),"+f"(d[6]),"+f"(d[7]),"+f"(d[8]),"+f"(d[9]),"+f"(d[10]),"+f"(d[11]),"+f"(d[12]),
          "+f"(d[13]),"+f"(d[14]),"+f"(d[15]),"+f"(d[16]),"+f"(d[17]),"+f"(d[18]),"+f"(d[19]),"+f"(d[20]),"+f"(d[21]),"+f"(d[22]),"+f"(d[23]),"+f"(d[24]),
          "+f"(d[25]),"+f"(d[26]),"+f"(d[27]),"+f"(d[28]),"+f"(d[29]),"+f"(d[30]),"+f"(d[31])
        : "l"(da), "l"(db), "r"(acc));
}
__device__ __forceinline__ void wgmma_rs_n64_zero(float* d, const uint32_t* a, uint64_t db) {
    asm volatile("wgmma.mma_async.sync.aligned.m64n64k16.f32.bf16.bf16 {"
        "%0,%1,%2,%3,%4,%5,%6,%7,%8,%9,%10,%11,%12,%13,%14,%15,%16,%17,%18,%19,%20,%21,%22,%23,%24,%25,%26,%27,%28,%29,%30,%31"
        "}, {%32,%33,%34,%35}, %36, 0, 1, 1, 0;\n"
        : "=f"(d[0]),"=f"(d[1]),"=f"(d[2]),"=f"(d[3]),"=f"(d[4]),"=f"(d[5]),"=f"(d[6]),"=f"(d[7]),"=f"(d[8]),"=f"(d[9]),"=f"(d[10]),"=f"(d[11]),"=f"(d[12]),
          "=f"(d[13]),"=f"(d[14]),"=f"(d[15]),"=f"(d[16]),"=f"(d[17]),"=f"(d[18]),"=f"(d[19]),"=f"(d[20]),"=f"(d[21]),"=f"(d[22]),"=f"(d[23]),"=f"(d[24]),
          "=f"(d[25]),"=f"(d[26]),"=f"(d[27]),"=f"(d[28]),"=f"(d[29]),"=f"(d[30]),"=f"(d[31])
        : "r"(a[0]), "r"(a[1]), "r"(a[2]), "r"(a[3]), "l"(db));
}
__device__ __forceinline__ void wgmma_rs_n64_acc(float* d, const uint32_t* a, uint64_t db) {
    asm volatile("wgmma.mma_async.sync.aligned.m64n64k16.f32.bf16.bf16 {"
        "%0,%1,%2,%3,%4,%5,%6,%7,%8,%9,%10,%11,%12,%13,%14,%15,%16,%17,%18,%19,%20,%21,%22,%23,%24,%25,%26,%27,%28,%29,%30,%31"
        "}, {%32,%33,%34,%35}, %36, 1, 1, 1, 0;\n"
        : "+f"(d[0]),"+f"(d[1]),"+f"(d[2]),"+f"(d[3]),"+f"(d[4]),"+f"(d[5]),"+f"(d[6]),"+f"(d[7]),"+f"(d[8]),"+f"(d[9]),"+f"(d[10]),"+f"(d[11]),"+f"(d[12]),
          "+f"(d[13]),"+f"(d[14]),"+f"(d[15]),"+f"(d[16]),"+f"(d[17]),"+f"(d[18]),"+f"(d[19]),"+f"(d[20]),"+f"(d[21]),"+f"(d[22]),"+f"(d[23]),"+f"(d[24]),
          "+f"(d[25]),"+f"(d[26]),"+f"(d[27]),"+f"(d[28]),"+f"(d[29]),"+f"(d[30]),"+f"(d[31])
        : "r"(a[0]), "r"(a[1]), "r"(a[2]), "r"(a[3]), "l"(db));
}
__device__ __forceinline__ void wgmma_rs_n24_acc(float* d, const uint32_t* a, uint64_t db) {
    asm volatile("wgmma.mma_async.sync.aligned.m64n24k16.f32.bf16.bf16 {"
        "%0,%1,%2,%3,%4,%5,%6,%7,%8,%9,%10,%11"
        "}, {%12,%13,%14,%15}, %16, 1, 1, 1, 1;\n"
        : "+f"(d[0]),"+f"(d[1]),"+f"(d[2]),"+f"(d[3]),"+f"(d[4]),"+f"(d[5]),"+f"(d[6]),"+f"(d[7]),"+f"(d[8]),"+f"(d[9]),"+f"(d[10]),"+f"(d[11])
        : "r"(a[0]), "r"(a[1]), "r"(a[2]), "r"(a[3]), "l"(db));
}
__device__ __forceinline__ void wgmma_rs_n24_zero(float* d, const uint32_t* a, uint64_t db) {
    asm volatile("wgmma.mma_async.sync.aligned.m64n24k16.f32.bf16.bf16 {"
        "%0,%1,%2,%3,%4,%5,%6,%7,%8,%9,%10,%11"
        "}, {%12,%13,%14,%15}, %16, 0, 1, 1, 1;\n"
        : "=f"(d[0]),"=f"(d[1]),"=f"(d[2]),"=f"(d[3]),"=f"(d[4]),"=f"(d[5]),"=f"(d[6]),"=f"(d[7]),"=f"(d[8]),"=f"(d[9]),"=f"(d[10]),"=f"(d[11])
        : "r"(a[0]), "r"(a[1]), "r"(a[2]), "r"(a[3]), "l"(db));
}

constexpr int OFF_ONES = 131072;
constexpr int OFF_RING = OFF_ONES + 4096;
constexpr int NRING = 5;
constexpr int OFF_B2 = OFF_RING + NRING * 16384;
constexpr int OFF_CS = OFF_B2 + 2048;
constexpr int OFF_RS = OFF_CS + 2560;
constexpr int OFF_BAR = OFF_RS + 1024;
enum { B_FULL = 0, B_STATS = 48, B_QKV = 58, B_KV = 59, B_RING = 67, B_WO = 70, B_O = 71, B_CNT2 = 80,
       B_AFREE = 80, B_CNT4 = 85, B_EMPTY = 85, B_AFREE0 = 90, B_DONE = 91, B_CNT8 = 92, B_TILE = 92, B_PART = 97, B_OW = 98, B_NUM = 100 };
constexpr int SMEM_BYTES = OFF_BAR + B_NUM * 8;
constexpr unsigned FIXED_MASK = 0xB5;
constexpr float P71 = 2361183241434822606848.0f, M71 = 4.235164736271502e-22f;

__device__ __forceinline__ uint32_t exp2_fixed(float lo, float hi, uint32_t half2) {
    uint32_t y, g, d;
    asm("cvt.pack.sat.s16.s32 %0, %1, %2;" : "=r"(y) : "r"(__float_as_uint(hi)), "r"(__float_as_uint(lo)));
    asm("lop3.b32 %0, %1, 0x007F007F, %2, 0xEA;" : "=r"(g) : "r"(y), "r"(half2));
    asm("fma.rn.bf16x2 %0, %1, %2, %3;" : "=r"(d) : "r"(y), "r"(g), "r"(y & 0xFF80FF80u));
    return d;
}
__device__ __forceinline__ uint32_t k_tile_addr(uint32_t base, int tile) {
    const int c = tile >> 2;
    return base + ((tile & 2) ? 98304 + c * 4096 : (2 * c + 1) * 4096) + (tile & 1) * 2048;
}
__host__ __device__ constexpr int stage_of(int t, int j) { return t == 0 ? j + (j >> 1) : (t == 1 && j < 4) ? 3 * j + 2 : 8 * t + j; }
__host__ __device__ constexpr uint32_t slots_of(int t) { uint32_t v = 0; for (int j = 0; j < 8; j++) v |= (uint32_t)(stage_of(t, j) % NRING) << (4 * j); return v; }
__host__ __device__ constexpr uint64_t first16() { uint64_t v = 0; for (int i = 0; i < 16; i++) v |= (uint64_t)i << (4 * stage_of(i >> 3, i & 7)); return v; }
constexpr uint32_t POS_STD = 0x76543210u, POS_LAST = 0x37521640u;

__global__ void __cluster_dims__(2, 1, 1) __launch_bounds__(640, 1)
mega_kernel(const __nv_bfloat16* __restrict__ x, const __nv_bfloat16* __restrict__ wqkv, const __nv_bfloat16* __restrict__ w1,
            const __nv_bfloat16* __restrict__ w3, __nv_bfloat16* __restrict__ out,
            const __grid_constant__ CUtensorMap mx, const __grid_constant__ CUtensorMap mqkv, const __grid_constant__ CUtensorMap mw1,
            const __grid_constant__ CUtensorMap mw3, const __grid_constant__ CUtensorMap mw2, const __grid_constant__ CUtensorMap mwo,
            uint32_t half2) {
    extern __shared__ __align__(1024) uint8_t smem_raw[];
    const uint32_t sb = __shfl_sync(0xffffffffu, smem_u32(smem_raw), 0);
    if ((sb & 0xFFFFFF) != SMEM_BASE) __trap();
    const uint32_t bars = sb + OFF_BAR, ring = sb + OFF_RING;
    const int tid = threadIdx.x, lane = tid & 31, g = lane >> 2, t4 = lane & 3;
    const int warp = __shfl_sync(0xffffffffu, tid >> 5, 0), wg = warp >> 2, wq = warp & 3;
    const int rank = blockIdx.x & 1, cl = blockIdx.x >> 1;
    const int grp = cl < 4 ? 4 + cl : cl < 36 ? (cl - 4) >> 3 : 4 + (cl - 36) / 7;
    const int rot = cl < 4 ? 7 : cl < 36 ? (cl - 4) & 7 : (cl - 36) % 7;
    const int mblk = rot * 2 + rank;
    const int nq = grp < 4 ? 2 : 1;
    const int qt0 = grp < 4 ? 2 * grp : 4 + grp;
    const int gu0 = (grp < 4 ? 3 * grp : 4 * grp - 4) - nq;
    const int head = blockIdx.x >> 2, qb = blockIdx.x & 3;

    if (tid == 512) TSTAMP(0);
    if (elect_one()) {
        if (warp == 16) {
            asm volatile("prefetch.tensormap [%0];" :: "l"(&mqkv) : "memory");
            asm volatile("prefetch.tensormap [%0];" :: "l"(rank ? &mw3 : &mw1) : "memory");
        }
#pragma unroll
        for (int i = 0; i < 5; i++) { const int b = warp * 5 + i; mbar_init(bars + 8 * b, b < B_CNT2 ? 1 : b < B_CNT4 ? 2 : b < B_CNT8 ? 4 : 8); }
        if (warp < 8) {
#pragma unroll
            for (int i = 0; i < 5; i++) mbar_expect(bars + 8 * (warp * 5 + i), warp * 5 + i < 8 ? 32768 : 16384);
        }
        asm volatile("fence.mbarrier_init.release.cluster;" ::: "memory");
        if (warp == 0) {
            fence_async_smem();
#pragma unroll
            for (int j = 0; j < 2; j++) tma2d(sb + j * 16384, &mx, ((rot + j) & 7) * 64, mblk * 128, bars + 8 * (B_FULL + j));
        }
    }
    if (tid == 512) TSTAMP(26);
    if (tid < 256) {
        asm volatile("st.shared.v4.b32 [%0], {%1,%1,%1,%1};" :: "r"(sb + OFF_ONES + tid * 16), "r"(0x3F803F80u) : "memory");
        if (tid < 128) {
            const bool fx = (FIXED_MASK >> (tid >> 4)) & 1;
            uint32_t a = fx ? pack_bf16(M71, M71) : pack_bf16(P71, P71);
            uint32_t b = fx ? pack_bf16(M71, 47.0f * M71) : pack_bf16(P71, -79.5f * P71);
            uint32_t c = fx ? 0u : pack_bf16(0.08214f * P71, 0.f);
            if (tid & 8) a = b = c = 0;
            asm volatile("st.shared.v4.b32 [%0], {%1,%2,%3,%4};" :: "r"(sb + OFF_B2 + tid * 16), "r"(a), "r"(b), "r"(c), "r"(0) : "memory");
        }
        fence_async_smem();
    }
    __syncthreads();
    asm volatile("barrier.cluster.arrive.relaxed.aligned;" ::: "memory");

    if (wg < 4) {
        const int pair = wg >> 1, half = wg & 1;
        if (pair == 1) {
            const int row = mblk * 128 + grp * 16 + (warp - 8) * 2 + (lane >> 4);
            uint4 v[4];
            const uint32_t* w = reinterpret_cast<const uint32_t*>(v);
#pragma unroll
            for (int j = 0; j < 4; j++) v[j] = __ldg(reinterpret_cast<const uint4*>(x + (size_t)row * DM) + j * 16 + (lane & 15));
            float s0 = 0.f, v0 = 0.f;
#pragma unroll
            for (int j = 0; j < 16; j++) s0 += bf_lo(w[j]) + bf_hi(w[j]);
#pragma unroll
            for (int d = 1; d < 16; d <<= 1) s0 += __shfl_xor_sync(0xffffffffu, s0, d);
            const float mean = s0 * (1.0f / DM);
#pragma unroll
            for (int j = 0; j < 16; j++) { const float a = bf_lo(w[j]) - mean, b = bf_hi(w[j]) - mean; v0 += fmaf(a, a, b * b); }
#pragma unroll
            for (int d = 1; d < 16; d <<= 1) v0 += __shfl_xor_sync(0xffffffffu, v0, d);
            if ((lane & 15) == 0) g_rs[row] = make_float2(bf_round(mean), bf_round(sqrtf(bf_round(bf_round(v0 * (1.0f / DM)) + 1e-5f))));
            __syncwarp();
            if (elect_one()) mbar_arrive(bars + 8 * B_PART);
        }
        asm volatile("barrier.cluster.wait.aligned;" ::: "memory");

        uint32_t q[4], qn[6];
        {
            float acc[64];
            const int rowblk = mblk * 2 + half, tile16 = rowblk * 4 + wq;
            const bool rel = wq < 2 && lane == 0, rel2 = wq == 2 && lane == 0;
            uint32_t empty;
            asm("mapa.shared::cluster.u32 %0, %1, %2;" : "=r"(empty) : "r"(bars + 8 * B_EMPTY), "r"(wq & 1));
#pragma unroll 1
            for (int t = pair; t < 5; t += 2) {
                const uint32_t sl = t == 0 ? slots_of(0) : t == 1 ? slots_of(1) : t == 2 ? slots_of(2) : t == 3 ? slots_of(3) : slots_of(4);
                const uint32_t po = t == 4 ? POS_LAST : POS_STD, full = bars + 8 * (B_FULL + 8 * t);
                if (t == 1) mbar_wait(full - 64, 0);
                mbar_wait(full, 0);
                if (tid == 0 && t == 0) TSTAMP(1);
#pragma unroll
                for (int j = 0; j < 8; j++) {
                    const uint64_t da = mkdesc(half * 8192, 16, 1024, 1) + ((po >> (4 * j)) & 7) * 1024;
                    const uint64_t db = mkdesc(OFF_RING, 8192, 1024, 1) + ((sl >> (4 * j)) & 7) * 1024;
                    wg_fence();
#pragma unroll
                    for (int k = 0; k < 4; k++) wgmma_ss_n128(acc, da + k * 2, db + k * 128, (j | k) != 0);
                    wg_commit();
                    if (j > 0) {
                        wg_wait<1>();
                        if (rel) mbar_arrive_remote(empty + ((sl >> (4 * j - 4)) & 7) * 8);
                        if ((j == 3 || j == 4 || j == 7) && t == 4 && rel2) mbar_arrive(bars + 8 * (j == 3 ? B_AFREE0 : j == 4 ? B_AFREE + 1 : B_AFREE + 2));
                    }
                    if (j < 7) {
                        if (t == 1) mbar_wait(full - 64 + 8 * (j + 1), 0);
                        mbar_wait(full + 8 * (j + 1), 0);
                    }
                }
                if (t >= 3) {
                    mbar_wait(bars + 8 * B_QKV, 0);
                    const uint4* pq = g_q + (head * 128 + (qb * 8 + wg) * 4 + wq) * 32 + lane;
                    const uint4 v = __ldcg(pq), u = __ldcg(pq + 512);
                    qn[0] = v.x; qn[1] = v.y; qn[2] = v.z; qn[3] = v.w; q[0] = u.x; q[1] = u.y; q[2] = u.z; q[3] = u.w;
                }
                wg_wait<0>();
                if (rel) mbar_arrive_remote(empty + (sl >> 28) * 8);
                if (t >= 3 && rel2) mbar_arrive(bars + 8 * (t == 4 ? B_AFREE + 3 : B_AFREE0));
                pin<64>(acc);
                if (wq == 0 && half == 0 && lane == 0) TSTAMP(2 + 2 * t);
                mbar_wait(bars + 8 * (B_STATS + t), 0);
                float m0, d0, m1, d1;
                asm volatile("ld.shared.v2.f32 {%0,%1}, [%2];" : "=f"(m0), "=f"(d0) : "r"(sb + OFF_RS + (half * 64 + wq * 16 + g) * 8));
                asm volatile("ld.shared.v2.f32 {%0,%1}, [%2];" : "=f"(m1), "=f"(d1) : "r"(sb + OFF_RS + (half * 64 + wq * 16 + g + 8) * 8));
#pragma unroll
                for (int j = 0; j < 16; j++) {
                    float c0, c1;
                    asm volatile("ld.shared.v2.f32 {%0,%1}, [%2];" : "=f"(c0), "=f"(c1) : "r"(sb + OFF_CS + (t * 128 + j * 8 + t4 * 2) * 4));
                    acc[4 * j] = fmaf(-m0, c0, acc[4 * j]); acc[4 * j + 1] = fmaf(-m0, c1, acc[4 * j + 1]);
                    acc[4 * j + 2] = fmaf(-m1, c0, acc[4 * j + 2]); acc[4 * j + 3] = fmaf(-m1, c1, acc[4 * j + 3]);
                }
                float r0 = 1.0f / d0, r1 = 1.0f / d1;
                if (t < nq) {
                    const int qt = qt0 + t, h0 = (qt & 3) * 8;
                    if (qt < 4) {
                        r0 *= 0.25f * 1.4426950408889634f * M71; r1 *= 0.25f * 1.4426950408889634f * M71;
                    } else if (qt < 8) {
                        r0 *= ((FIXED_MASK >> (2 * wq)) & 1) ? M71 : P71; r1 *= ((FIXED_MASK >> (2 * wq + 1)) & 1) ? M71 : P71;
                    }
                    uint32_t* p; int s8, sh;
                    if (qt < 8) { p = reinterpret_cast<uint32_t*>(g_k + h0 * 4096) + tile16 * 128 + lane; s8 = 64; sh = 32; }
                    else        { p = reinterpret_cast<uint32_t*>(g_v + h0 * 4096) + tile16 * 64 + lane;  s8 = 32; sh = 8192; }
#pragma unroll
                    for (int hh = 0; hh < 8; hh++) {
                        const float* a = acc + hh * 8;
                        const uint32_t e0 = pack_bf16(a[0] * r0, a[1] * r0), e1 = pack_bf16(a[2] * r1, a[3] * r1);
                        const uint32_t e2 = pack_bf16(a[4] * r0, a[5] * r0), e3 = pack_bf16(a[6] * r1, a[7] * r1);
                        if (qt < 4) g_q[((h0 + hh) * 128 + tile16) * 32 + lane] = make_uint4(e0, e1, e2, e3);
                        else { uint32_t* pp = p + hh * 16384; pp[0] = e0; pp[s8] = e1; pp[sh] = e2; pp[sh + s8] = e3; }
                    }
                } else {
                    uint32_t* p = reinterpret_cast<uint32_t*>(g_h + (rowblk * 28 + gu0 + t) * 512) + wq * 512 + lane;
                    r0 *= -1.4426950408889634f; r1 *= -1.4426950408889634f; d0 *= d0; d1 *= d1;
#pragma unroll
                    for (int j = 0; j < 8; j++) {
                        const float* a = acc + j * 4; const float* b = a + 32;
                        p[j * 32] = pack_bf16(a[0] * b[0] * rcpf(fmaf(ex2f(a[0] * r0), d0, d0)), a[1] * b[1] * rcpf(fmaf(ex2f(a[1] * r0), d0, d0)));
                        p[256 + j * 32] = pack_bf16(a[2] * b[2] * rcpf(fmaf(ex2f(a[2] * r1), d1, d1)), a[3] * b[3] * rcpf(fmaf(ex2f(a[3] * r1), d1, d1)));
                    }
                }
                __syncwarp();
                if (elect_one()) mbar_arrive(bars + 8 * (B_TILE + t));
                if (wq == 0 && half == 0 && lane == 0) TSTAMP(3 + 2 * t);
            }
        }
        const uint64_t db2 = mkdesc(OFF_B2, 128, 256, 0);
        float s[32];
        auto ref_point = [&](int ntile, uint32_t& b0, uint32_t& b1) {
            float m0 = -INFINITY, m1 = -INFINITY, f0 = -INFINITY, f1 = -INFINITY;
#pragma unroll 1
            for (int t = 0; t < ntile; t++) {
                wg_fence();
                wgmma_rs_n64_zero(s, q, mkdesc(k_tile_addr(0, t), 128, 256, 0));
                wg_commit();
                wg_wait<0>();
                pin<32>(s);
#pragma unroll
                for (int i = 0; i < 8; i++) {
                    if ((FIXED_MASK >> i) & 1) { f0 = fmaxf(f0, fmaxf(s[4 * i], s[4 * i + 1])); f1 = fmaxf(f1, fmaxf(s[4 * i + 2], s[4 * i + 3])); }
                    else                       { m0 = fmaxf(m0, fmaxf(s[4 * i], s[4 * i + 1])); m1 = fmaxf(m1, fmaxf(s[4 * i + 2], s[4 * i + 3])); }
                }
            }
            m0 = fmaxf(m0, f0 * P71 * P71); m1 = fmaxf(m1, f1 * P71 * P71);
            m0 = fmaxf(m0, __shfl_xor_sync(0xffffffffu, m0, 1)); m1 = fmaxf(m1, __shfl_xor_sync(0xffffffffu, m1, 1));
            m0 = fmaxf(m0, __shfl_xor_sync(0xffffffffu, m0, 2)); m1 = fmaxf(m1, __shfl_xor_sync(0xffffffffu, m1, 2));
#pragma unroll
            for (int r = 0; r < 2; r++) {
                const float m = -rintf(r ? m1 : m0), mh = bf_round(m), mm = bf_round(m - mh), ml = m - mh - mm;
                const float lo = t4 == 0 ? mh : t4 == 1 ? ml : t4 == 2 ? 1.f : 0.f, hi = t4 == 0 ? mm : t4 == 1 ? 1.f : 0.f;
                (r ? b1 : b0) = pack_bf16(lo * M71, hi * M71);
            }
        };
        uint32_t q2[4];
        int redo = 1;
        mbar_wait(bars + 8 * B_KV, 0);
#pragma unroll 1
        for (int round = -1; round < 2;) {
            if (redo) ref_point(redo, q2[0], q2[1]);
            if (round < 0) {
#pragma unroll
                for (int i = 0; i < 4; i++) { const uint32_t tq = q[i]; q[i] = qn[i]; qn[i] = tq; }
                qn[4] = q2[0]; qn[5] = q2[1];
                q2[2] = __shfl_sync(0xffffffffu, q2[0], 3); q2[3] = __shfl_sync(0xffffffffu, q2[1], 3);
                round = 0;
                continue;
            }
            float o[12]; uint32_t p[16];
#pragma unroll
            for (int i = 0; i < 12; i++) o[i] = 0.f;
            pin<12>(o); pin<4>(q2);
            if (wq == 0 && half == 0 && lane == 0) TSTAMP(12 + 4 * round + pair);
            uint64_t dk0 = mkdesc(4096, 128, 256, 0), dk1 = mkdesc(98304, 128, 256, 0), dv = mkdesc(0, 128, 65536, 0);
#pragma unroll 1
            for (int c = 0; c < 8; c++, dk0 += 512, dk1 += 256, dv += 512 - (256ull << 32)) {
                if (round == 0) mbar_wait(bars + 8 * (B_KV + c), 0);
#pragma unroll
                for (int t = 0; t < 4; t++) {
                    wg_fence();
                    wgmma_rs_n64_zero(s, q, (t & 2 ? dk1 : dk0) + (t & 1) * 128);
                    wgmma_rs_n64_acc(s, q2, db2);
                    wg_commit();
                    wg_wait<0>();
                    pin<32>(s); pin<16>(p);
#pragma unroll
                    for (int i = 0; i < 16; i++) {
                        if ((FIXED_MASK >> (i >> 1)) & 1) p[i] = exp2_fixed(s[2 * i], s[2 * i + 1], half2);
                        else                              p[i] = pack_bf16(ex2f(s[2 * i]), ex2f(s[2 * i + 1]));
                    }
                    wg_fence();
#pragma unroll
                    for (int k = 0; k < 4; k++) wgmma_rs_n24_acc(o, p + 4 * k, dv + (t * 4 + k) * 16);
                    wg_commit();
                }
            }
            wg_wait<0>();
            pin<12>(o);
            if (redo != 32) {
                float chk = (o[8] + o[10]) * 256.f;
#pragma unroll
                for (int i = 0; i < 8; i++) chk += fabsf(o[i]);
                uint32_t bad;
                asm volatile("{\n.reg .pred p, q;\nsetp.geu.f32 q, %1, 0f7F800000;\nbar.red.or.pred p, %2, 128, q;\nselp.u32 %0, 1, 0, p;\n}" : "=r"(bad) : "f"(chk), "r"(1 + wg) : "memory");
                if (__any_sync(0xffffffffu, bad)) { redo = 32; continue; }
            }
            const int rowblk = qb * 8 + round * 4 + wg;
            const float r0 = rcpf(o[8]), r1 = rcpf(o[10]);
            uint32_t* po = reinterpret_cast<uint32_t*>(g_o + (rowblk * 8 + (head >> 2)) * 512) + wq * 512 + (head & 3) * 64 + lane;
            po[0] = pack_bf16(o[0] * r0, o[1] * r0); po[256] = pack_bf16(o[2] * r1, o[3] * r1);
            po[32] = pack_bf16(o[4] * r0, o[5] * r0); po[288] = pack_bf16(o[6] * r1, o[7] * r1);
            if (round == 0) {
                __syncwarp();
                if (elect_one()) mbar_arrive(bars + 8 * (B_OW + pair));
            } else {
                bar_sync(1 + wg, 128);
                if (wq == 0 && elect_one()) { mbar_arrive(bars + 8 * B_DONE); signal_cnt(C_O + rowblk); }
            }
#pragma unroll
            for (int i = 0; i < 4; i++) q[i] = qn[i];
            q2[0] = qn[4]; q2[1] = qn[5];
            redo = 0;
            if (wq == 0 && half == 0 && lane == 0) TSTAMP(14 + 4 * round + pair);
            round++;
        }
    } else {
        if (wq > 0) {
#pragma unroll 1
            for (int t = wq - 1; t < (wq == 3 ? 5 : wq); t++) {
                const __nv_bfloat16* src; int ld;
                if (t < nq) { src = wqkv + (qt0 + t) * 128 + rank * 64; ld = 3 * DM; }
                else        { src = (rank ? w3 : w1) + (gu0 + t) * 64; ld = FF; }
                src += (size_t)(rot * 64 + (lane >> 3)) * ld + (lane & 7) * 8;
                uint4 v[16];
                const uint32_t* w = reinterpret_cast<const uint32_t*>(v);
#pragma unroll
                for (int j = 0; j < 16; j++) v[j] = __ldg(reinterpret_cast<const uint4*>(src + (size_t)j * 4 * ld));
                float c[8];
#pragma unroll
                for (int e = 0; e < 4; e++) {
                    float a = 0.f, b = 0.f;
#pragma unroll
                    for (int j = 0; j < 16; j++) { a += bf_lo(w[4 * j + e]); b += bf_hi(w[4 * j + e]); }
                    a += __shfl_xor_sync(0xffffffffu, a, 8); b += __shfl_xor_sync(0xffffffffu, b, 8);
                    a += __shfl_xor_sync(0xffffffffu, a, 16); b += __shfl_xor_sync(0xffffffffu, b, 16);
                    c[2 * e] = a; c[2 * e + 1] = b;
                }
                if (lane < 16) g_cs[((grp * 5 + t) * 8 + rot) * 32 + rank * 16 + (lane & 7) * 2 + (lane >> 3)] =
                    lane < 8 ? make_float4(c[0], c[1], c[2], c[3]) : make_float4(c[4], c[5], c[6], c[7]);
            }
            if (wq == 2) mbar_wait(bars + 8 * B_PART, 0);
            __syncwarp();
            if (elect_one()) {
                signal_cnt(C_COL + grp * 2 + (wq == 3));
                if (wq == 2) asm volatile("red.relaxed.gpu.global.add.u32 [%0], 1;" :: "l"(g_cnt + (C_ROW + mblk) * 8) : "memory");
            }
        }
        asm volatile("barrier.cluster.wait.aligned;" ::: "memory");
        if (tid == 512) TSTAMP(27);
        if (wq == 0) {
            const CUtensorMap* mgu = rank ? &mw3 : &mw1;
            const CUtensorMap* m1 = nq == 2 ? &mqkv : mgu;
            const int col0 = qt0 * 128 + rank * 64, col1 = nq == 2 ? col0 + 128 : (gu0 + 1) * 64;
            uint64_t order = first16();
            uint32_t slot = 0, ph = 1;
#pragma unroll 1
            for (int n = 0; n < 40; n++) {
                const int id = n < 16 ? (int)order & 15 : n, j = id & 7;
                const int kc = ((n < 32 ? j : (POS_LAST >> (4 * j))) + rot & 7) * 64;
                const CUtensorMap* m = id < 8 ? &mqkv : id < 16 ? m1 : mgu;
                const int col = id < 8 ? col0 : id < 16 ? col1 : (gu0 + (id >> 3)) * 64;
                const uint32_t dst = ring + slot * 16384 + rank * 8192, fb = bars + 8 * (B_FULL + id);
                order >>= 4;
                if (id >= 2 && id < 8 && elect_one()) tma2d(sb + id * 16384, &mx, kc, mblk * 128, fb);
                mbar_wait(bars + 8 * (B_EMPTY + slot), ph);
                if (elect_one()) { TS2(0, n); tma2d_mc(dst, m, col, kc, fb); }
                if (++slot == NRING) { slot = 0; ph ^= 1; }
            }
        } else if (wq == 1) {
            wait_cnt(C_ROW + mblk, 8, 100);
#pragma unroll
            for (int i = 0; i < 2; i++) {
                const float4 a = __ldcg(reinterpret_cast<const float4*>(g_rs + mblk * 128) + i * 32 + lane);
                asm volatile("st.shared.v4.f32 [%0], {%1,%2,%3,%4};" :: "r"(sb + OFF_RS + (i * 32 + lane) * 16), "f"(a.x), "f"(a.y), "f"(a.z), "f"(a.w) : "memory");
            }
#pragma unroll 1
            for (int t = 0; t < 5; t++) {
                if (t == 0 || t == 2) wait_cnt(C_COL + grp * 2 + (t >> 1), t ? 16 : 32, 100);
                float4 a = make_float4(0.f, 0.f, 0.f, 0.f);
#pragma unroll
                for (int kp = 0; kp < 8; kp++) { const float4 b = __ldcg(g_cs + ((grp * 5 + t) * 8 + kp) * 32 + lane); a.x += b.x; a.y += b.y; a.z += b.z; a.w += b.w; }
                asm volatile("st.shared.v4.f32 [%0], {%1,%2,%3,%4};" :: "r"(sb + OFF_CS + (t * 32 + lane) * 16), "f"(a.x), "f"(a.y), "f"(a.z), "f"(a.w) : "memory");
                __syncwarp();
                if (elect_one()) { mbar_arrive(bars + 8 * (B_STATS + t)); if (t == 0) TSTAMP(28); if (t == 4) TSTAMP(31); }
            }
#pragma unroll 1
            for (int i = 0; i < 3; i++) wait_cnt(C_QKV + i * 4 + (head >> 3), 16, 100);
            if (elect_one()) { mbar_arrive(bars + 8 * B_QKV); TSTAMP(29); }
            fence_async_all();
            const uint8_t* gk = reinterpret_cast<const uint8_t*>(g_k + head * 4096);
            const uint8_t* gv = reinterpret_cast<const uint8_t*>(g_v + head * 4096);
#pragma unroll 1
            for (int c = 0; c < 8; c++) {
                if (!(c & 1)) mbar_wait(bars + 8 * (c ? B_AFREE + (c >> 1) : B_AFREE0), 0);
                if (elect_one()) {
                    const uint32_t b = bars + 8 * (B_KV + c);
                    mbar_expect(b, 16384);
                    bulk_load(sb + (2 * c + 1) * 4096, gk + c * 8192, 4096, b);
                    bulk_load(sb + 2 * c * 4096, gv + c * 4096, 4096, b);
                    bulk_load(sb + 65536 + c * 4096, gv + 32768 + c * 4096, 4096, b);
                    bulk_load(sb + 98304 + c * 4096, gk + c * 8192 + 4096, 4096, b);
                }
            }
        } else if (wq == 2) {
#pragma unroll 1
            for (int t = 0; t < 5; t++) {
                mbar_wait(bars + 8 * (B_TILE + t), 0);
                if (elect_one()) signal_cnt(t < nq ? C_QKV + qt0 + t : C_H + mblk);
            }
        }
        bar_sync(5, 128);
        const int cb = blockIdx.x & 7, pr = blockIdx.x >> 3;
        const int rb0 = (pr >> 2) * 8 + (pr & 3);
        uint32_t gate[2][16];
        {
            float dn[64];
            auto load_stage = [&](int kb, int st) {
                const uint32_t b = bars + 8 * (B_RING + st), dst = ring + st * 24576;
                mbar_expect(b, 24576);
                bulk_load(dst, g_h + (rb0 * 28 + kb) * 512, 8192, b);
                bulk_load(dst + 8192, g_h + ((rb0 + 4) * 28 + kb) * 512, 8192, b);
                tma2d(dst + 16384, &mw2, cb * 64, kb * 64, b);
            };
            if (wq == 0) {
                wait_cnt(C_H + (rb0 >> 1), 28, 200);
                wait_cnt(C_H + (rb0 >> 1) + 2, 28, 200);
                if (elect_one()) { TSTAMP(20); fence_async_all(); load_stage(0, 0); load_stage(1, 1); }
            }
            int st = 0; uint32_t ph = 0;
#pragma unroll 1
            for (int kb = 0; kb < 28; kb++) {
                mbar_wait(bars + 8 * (B_RING + st), ph);
                const uint64_t da = mkdesc(OFF_RING + st * 24576, 128, 1024, 0), db = mkdesc(OFF_RING + st * 24576 + 16384, 8192, 1024, 1);
                wg_fence();
#pragma unroll
                for (int k = 0; k < 4; k++) { wgmma_ss_n64(dn, da + k * 16, db + k * 128, (kb | k) != 0); wgmma_ss_n64(dn + 32, da + 512 + k * 16, db + k * 128, (kb | k) != 0); }
                wg_commit();
                wg_wait<1>();
                if (wq == 0 && kb < 26 && elect_one()) load_stage(kb + 2, st == 0 ? 2 : st - 1);
                if (++st == 3) { st = 0; ph ^= 1; }
            }
            wg_wait<0>();
            pin<64>(dn);
#pragma unroll
            for (int i = 0; i < 32; i++) gate[i >> 4][i & 15] = pack_bf16(siluf(dn[2 * i]), siluf(dn[2 * i + 1]));
        }
        float acc[32];
        if (tid == 512) TSTAMP(21);
        const uint32_t bar_wo = bars + 8 * B_WO;
        if (wq == 0 && elect_one()) {
            mbar_expect(bar_wo, 65536);
#pragma unroll 1
            for (int i = 0; i < 8; i++) tma2d(ring + i * 8192, &mwo, cb * 64, i * 64, bar_wo);
        }
        if (wq >= 2) {
            mbar_wait(bars + 8 * (B_OW + wq - 2), 0);
            if (elect_one()) {
                signal_cnt(C_O + qb * 8 + 2 * wq - 4);
                asm volatile("red.relaxed.gpu.global.add.u32 [%0], 1;" :: "l"(g_cnt + (C_O + qb * 8 + 2 * wq - 3) * 8) : "memory");
            }
        }
#pragma unroll
        for (int tl = 0; tl < 2; tl++) {
            const int rb = rb0 + 4 * tl;
            uint32_t xr[16];
            const uint32_t* px = reinterpret_cast<const uint32_t*>(x + (size_t)(rb * 64 + wq * 16 + g) * DM + cb * 64) + t4;
#pragma unroll
            for (int j = 0; j < 8; j++) { xr[2 * j] = __ldg(px + j * 4); xr[2 * j + 1] = __ldg(px + 8 * DM / 2 + j * 4); }
            if (wq == 0) {
                if (tl == 1) mbar_wait(bars + 8 * B_DONE, 0);
                wait_cnt(C_O + rb, 32, tl ? 20 : 200);
                if (elect_one()) {
                    fence_async_all();
                    TSTAMP(22 + 2 * tl);
#pragma unroll 1
                    for (int i = 0; i < (tl ? 8 : 2); i++) {
                        mbar_expect(bars + 8 * (B_O + i), 8192);
                        bulk_load((tl ? sb : ring + 65536) + i * 8192, g_o + (rb * 8 + i) * 512, 8192, bars + 8 * (B_O + i));
                    }
                }
            }
            if (tl == 0) mbar_wait(bar_wo, 0);
#pragma unroll 1
            for (int kb = 0; kb < 8; kb++) {
                mbar_wait(bars + 8 * (B_O + kb), tl);
                const uint32_t a = tl == 0 ? OFF_RING + 65536 + (kb & 1) * 8192 : kb * 8192;
                const uint64_t da = mkdesc(a, 128, 1024, 0), db = mkdesc(OFF_RING + kb * 8192, 8192, 1024, 1);
                wg_fence();
#pragma unroll
                for (int k = 0; k < 4; k++) wgmma_ss_n64(acc, da + k * 16, db + k * 128, (kb | k) != 0);
                wg_commit();
                if (tl == 0) {
                    wg_wait<0>();
                    bar_sync(5, 128);
                    if (wq == 0 && kb < 6 && elect_one()) { mbar_expect(bars + 8 * (B_O + kb + 2), 8192); bulk_load(sb + a, g_o + (rb * 8 + kb + 2) * 512, 8192, bars + 8 * (B_O + kb + 2)); }
                }
            }
            unsigned ticket = 0;
            if (tl == 1 && tid == 512 + 96) ticket = atomicInc(&g_ticket, 127);
            wg_wait<0>();
            pin<32>(acc);
            uint32_t* po = reinterpret_cast<uint32_t*>(out + (size_t)(rb * 64 + wq * 16 + g) * DM + cb * 64) + t4;
#pragma unroll
            for (int i = 0; i < 16; i++) {
                const uint32_t r = pack_bf16(fmaf(acc[2 * i], bf_lo(gate[tl][i]), bf_lo(xr[i])), fmaf(acc[2 * i + 1], bf_hi(gate[tl][i]), bf_hi(xr[i])));
                po[(i & 1) * (8 * DM / 2) + (i >> 1) * 4] = r;
            }
            if (tl == 1 && wq == 3 && __any_sync(0xffffffffu, ticket == 127)) {
#pragma unroll 1
                for (int i = lane; i < C_NUM; i += 32) g_cnt[i * 8] = 0;
            }
            if (tid == 512) TSTAMP(23 + 2 * tl);
        }
    }
}

typedef CUresult (*EncodeFn)(CUtensorMap*, CUtensorMapDataType, cuuint32_t, void*, const cuuint64_t*, const cuuint64_t*, const cuuint32_t*,
                             const cuuint32_t*, CUtensorMapInterleave, CUtensorMapSwizzle, CUtensorMapL2promotion, CUtensorMapFloatOOBfill);

void make_map(EncodeFn fn, CUtensorMap* m, const void* p, int rows, int cols, int box_rows) {
    cuuint64_t dims[2] = {(cuuint64_t)cols, (cuuint64_t)rows};
    cuuint64_t strides[1] = {(cuuint64_t)cols * 2};
    cuuint32_t box[2] = {64, (cuuint32_t)box_rows};
    cuuint32_t es[2] = {1, 1};
    fn(m, CU_TENSOR_MAP_DATA_TYPE_BFLOAT16, 2, const_cast<void*>(p), dims, strides, box, es, CU_TENSOR_MAP_INTERLEAVE_NONE,
       CU_TENSOR_MAP_SWIZZLE_128B, CU_TENSOR_MAP_L2_PROMOTION_L2_128B, CU_TENSOR_MAP_FLOAT_OOB_FILL_NONE);
}

}

extern "C" void kernel_launch(void* const* d_in, const int* in_sizes, int n_in, void* d_out, int out_size) {
    const __nv_bfloat16* x = (const __nv_bfloat16*)d_in[0];
    static EncodeFn fn = nullptr;
    if (!fn) {
        cudaDriverEntryPointQueryResult qr;
        cudaGetDriverEntryPoint("cuTensorMapEncodeTiled", (void**)&fn, cudaEnableDefault, &qr);
        cudaFuncSetAttribute(mega_kernel, cudaFuncAttributeMaxDynamicSharedMemorySize, SMEM_BYTES);
    }
    CUtensorMap mx, mqkv, mw1, mw3, mw2, mwo;
    make_map(fn, &mx, d_in[0], SEQ, DM, 128);
    make_map(fn, &mqkv, d_in[1], DM, 3 * DM, 64);
    make_map(fn, &mwo, d_in[2], DM, DM, 64);
    make_map(fn, &mw1, d_in[4], DM, FF, 64);
    make_map(fn, &mw3, d_in[5], DM, FF, 64);
    make_map(fn, &mw2, d_in[6], FF, DM, 64);
    mega_kernel<<<128, 640, SMEM_BYTES, cudaStreamPerThread>>>(x, (const __nv_bfloat16*)d_in[1], (const __nv_bfloat16*)d_in[4], (const __nv_bfloat16*)d_in[5],
                                                               (__nv_bfloat16*)d_out, mx, mqkv, mw1, mw3, mw2, mwo, 0x3F003F00u);
}
```

```cpp
#include <cuda_runtime.h>
#include <cuda_bf16.h>
#include <cuda.h>
#include <stdint.h>

namespace {

constexpr int SEQ = 2048, DM = 512, FF = 1792;

__device__ uint4 g_q[32 * 128 * 32];
__device__ uint4 g_k[32 * 4096];
__device__ uint4 g_v[32 * 4096];
__device__ uint4 g_h[32 * 28 * 512];
__device__ uint4 g_o[32 * 8 * 512];
__device__ ulonglong2 g_cs[40 * 8 * 64];
__device__ ulonglong2 g_rs[SEQ / 2];
constexpr int C_QKV = 0, C_H = 12, C_O = 28, C_NUM = 60;
__device__ unsigned g_cnt[C_NUM * 8];
__device__ unsigned g_epoch[128];
#define TSTAMP(i)
#define TS2(k, i)

__device__ __forceinline__ uint32_t smem_u32(const void* p) { return (uint32_t)__cvta_generic_to_shared(p); }
__device__ __forceinline__ void mbar_init(uint32_t a, int c) { asm volatile("mbarrier.init.shared::cta.b64 [%0], %1;" :: "r"(a), "r"(c)); }
__device__ __forceinline__ void mbar_expect(uint32_t a, int b) { asm volatile("mbarrier.arrive.expect_tx.shared::cta.b64 _, [%0], %1;" :: "r"(a), "r"(b) : "memory"); }
__device__ __forceinline__ void mbar_arrive(uint32_t a) { asm volatile("mbarrier.arrive.shared::cta.b64 _, [%0];" :: "r"(a) : "memory"); }
__device__ __forceinline__ void mbar_arrive_remote(uint32_t a) { asm volatile("mbarrier.arrive.shared::cluster.b64 _, [%0];" :: "r"(a) : "memory"); }
__device__ __forceinline__ bool mbar_try(uint32_t a, uint32_t ph) {
    uint32_t ok;
    asm volatile("{\n.reg .pred p;\nmbarrier.try_wait.parity.shared::cta.b64 p, [%1], %2;\nselp.u32 %0, 1, 0, p;\n}" : "=r"(ok) : "r"(a), "r"(ph) : "memory");
    return ok;
}
__device__ __forceinline__ void mbar_wait(uint32_t a, uint32_t ph) {
    for (int n = 0; !__all_sync(0xffffffffu, mbar_try(a, ph)); n++) if (n > 4000000) __trap();
}
__device__ __forceinline__ bool elect_one() {
    uint32_t p;
    asm volatile("{\n.reg .pred P;\nelect.sync _|P, 0xffffffff;\nselp.u32 %0, 1, 0, P;\n}" : "=r"(p));
    return p;
}
__device__ __forceinline__ void signal_cnt(int c) {
    asm volatile("fence.acq_rel.gpu;\nred.relaxed.gpu.global.add.u32 [%0], 1;" :: "l"(g_cnt + c * 8) : "memory");
}
__device__ __forceinline__ void wait_cnt(int c, unsigned target, int ns) {
    for (int n = 0;; n++) {
        unsigned v;
        asm volatile("ld.acquire.gpu.global.u32 %0, [%1];" : "=r"(v) : "l"(g_cnt + c * 8) : "memory");
        if (__all_sync(0xffffffffu, (int)(v - target) >= 0)) break;
        if (n > 2000000) __trap();
        __nanosleep(ns);
    }
}
__device__ __forceinline__ void st_tagged(void* p, uint32_t v, uint32_t tag) {
    asm volatile("st.relaxed.gpu.global.b64 [%0], %1;" :: "l"(p), "l"((unsigned long long)tag << 32 | v) : "memory");
}
__device__ __forceinline__ uint32_t ld_tagged2(const ulonglong2* p, uint32_t tag, uint32_t& a, uint32_t& b) {
    unsigned long long u, v;
    asm volatile("ld.relaxed.gpu.global.v2.b64 {%0,%1}, [%2];" : "=l"(u), "=l"(v) : "l"(p) : "memory");
    a = (uint32_t)u; b = (uint32_t)v;
    return ((uint32_t)(u >> 32) ^ tag) | ((uint32_t)(v >> 32) ^ tag);
}
__device__ __forceinline__ void tma2d(uint32_t dst, const CUtensorMap* m, int c0, int c1, uint32_t bar) {
    asm volatile("cp.async.bulk.tensor.2d.shared::cluster.global.mbarrier::complete_tx::bytes [%0], [%1, {%3, %4}], [%2];"
                 :: "r"(dst), "l"(m), "r"(bar), "r"(c0), "r"(c1) : "memory");
}
__device__ __forceinline__ void tma2d_mc(uint32_t dst, const CUtensorMap* m, int c0, int c1, uint32_t bar) {
    asm volatile("cp.async.bulk.tensor.2d.shared::cluster.global.mbarrier::complete_tx::bytes.multicast::cluster [%0], [%1, {%3, %4}], [%2], %5;"
                 :: "r"(dst), "l"(m), "r"(bar), "r"(c0), "r"(c1), "h"((uint16_t)3) : "memory");
}
__device__ __forceinline__ void bulk_load(uint32_t dst, const void* src, int bytes, uint32_t bar) {
    asm volatile("cp.async.bulk.shared::cluster.global.mbarrier::complete_tx::bytes [%0], [%1], %2, [%3];"
                 :: "r"(dst), "l"(src), "r"(bytes), "r"(bar) : "memory");
}
__device__ __forceinline__ void bar_sync(int id, int n) { asm volatile("bar.sync %0, %1;" :: "r"(id), "r"(n) : "memory"); }
__device__ __forceinline__ void fence_async_smem() { asm volatile("fence.proxy.async.shared::cta;" ::: "memory"); }
__device__ __forceinline__ void fence_async_all() { asm volatile("fence.proxy.async;" ::: "memory"); }
__device__ __forceinline__ void wg_fence() { asm volatile("wgmma.fence.sync.aligned;" ::: "memory"); }
__device__ __forceinline__ void wg_commit() { asm volatile("wgmma.commit_group.sync.aligned;" ::: "memory"); }
template <int N> __device__ __forceinline__ void wg_wait() { asm volatile("wgmma.wait_group.sync.aligned %0;" :: "n"(N) : "memory"); }
template <int N> __device__ __forceinline__ void pin(float* d) {
#pragma unroll
    for (int i = 0; i < N; i++) asm volatile("" : "+f"(d[i]) :: "memory");
}
template <int N> __device__ __forceinline__ void pin(uint32_t* d) {
#pragma unroll
    for (int i = 0; i < N; i++) asm volatile("" : "+r"(d[i]) :: "memory");
}
constexpr uint32_t SMEM_BASE = 1024;
__device__ __forceinline__ uint64_t mkdesc(uint32_t off, uint32_t lbo, uint32_t sbo, uint32_t swz) {
    return (uint64_t)((SMEM_BASE + off) >> 4) | ((uint64_t)(lbo >> 4) << 16) | ((uint64_t)(sbo >> 4) << 32) | ((uint64_t)swz << 62);
}
__device__ __forceinline__ float ex2f(float x) { float y; asm("ex2.approx.ftz.f32 %0, %1;" : "=f"(y) : "f"(x)); return y; }
__device__ __forceinline__ float rcpf(float x) { float y; asm("rcp.approx.ftz.f32 %0, %1;" : "=f"(y) : "f"(x)); return y; }
__device__ __forceinline__ uint32_t pack_bf16(float lo, float hi) { uint32_t r; asm("cvt.rn.bf16x2.f32 %0, %1, %2;" : "=r"(r) : "f"(hi), "f"(lo)); return r; }
__device__ __forceinline__ float bf_lo(uint32_t v) { return __uint_as_float(v << 16); }
__device__ __forceinline__ float bf_hi(uint32_t v) { return __uint_as_float(v & 0xFFFF0000u); }
__device__ __forceinline__ float bf_round(float x) { return __bfloat162float(__float2bfloat16_rn(x)); }
__device__ __forceinline__ float siluf(float g) { return g * rcpf(1.0f + ex2f(g * -1.4426950408889634f)); }

__device__ __forceinline__ void wgmma_ss_n256(float* d, uint64_t da, uint64_t db, int acc) {
    asm volatile("{\n.reg .pred p;\nsetp.ne.b32 p, %130, 0;\nwgmma.mma_async.sync.aligned.m64n256k16.f32.bf16.bf16 {"
        "%0,%1,%2,%3,%4,%5,%6,%7,%8,%9,%10,%11,%12,%13,%14,%15,%16,%17,%18,%19,%20,%21,%22,%23,%24,%25,%26,%27,%28,%29,%30,%31,%32,%33,%34,%35,%36,%37,%38,%39,"
        "%40,%41,%42,%43,%44,%45,%46,%47,%48,%49,%50,%51,%52,%53,%54,%55,%56,%57,%58,%59,%60,%61,%62,%63,%64,%65,%66,%67,%68,%69,%70,%71,%72,%73,%74,%75,%76,"
        "%77,%78,%79,%80,%81,%82,%83,%84,%85,%86,%87,%88,%89,%90,%91,%92,%93,%94,%95,%96,%97,%98,%99,%100,%101,%102,%103,%104,%105,%106,%107,%108,%109,%110,"
        "%111,%112,%113,%114,%115,%116,%117,%118,%119,%120,%121,%122,%123,%124,%125,%126,%127"
        "}, %128, %129, p, 1, 1, 0, 1;\n}\n"
        : "+f"(d[0]),"+f"(d[1]),"+f"(d[2]),"+f"(d[3]),"+f"(d[4]),"+f"(d[5]),"+f"(d[6]),"+f"(d[7]),"+f"(d[8]),"+f"(d[9]),"+f"(d[10]),"+f"(d[11]),"+f"(d[12]),
          "+f"(d[13]),"+f"(d[14]),"+f"(d[15]),"+f"(d[16]),"+f"(d[17]),"+f"(d[18]),"+f"(d[19]),"+f"(d[20]),"+f"(d[21]),"+f"(d[22]),"+f"(d[23]),"+f"(d[24]),
          "+f"(d[25]),"+f"(d[26]),"+f"(d[27]),"+f"(d[28]),"+f"(d[29]),"+f"(d[30]),"+f"(d[31]),"+f"(d[32]),"+f"(d[33]),"+f"(d[34]),"+f"(d[35]),"+f"(d[36]),
          "+f"(d[37]),"+f"(d[38]),"+f"(d[39]),"+f"(d[40]),"+f"(d[41]),"+f"(d[42]),"+f"(d[43]),"+f"(d[44]),"+f"(d[45]),"+f"(d[46]),"+f"(d[47]),"+f"(d[48]),
          "+f"(d[49]),"+f"(d[50]),"+f"(d[51]),"+f"(d[52]),"+f"(d[53]),"+f"(d[54]),"+f"(d[55]),"+f"(d[56]),"+f"(d[57]),"+f"(d[58]),"+f"(d[59]),"+f"(d[60]),
          "+f"(d[61]),"+f"(d[62]),"+f"(d[63]),"+f"(d[64]),"+f"(d[65]),"+f"(d[66]),"+f"(d[67]),"+f"(d[68]),"+f"(d[69]),"+f"(d[70]),"+f"(d[71]),"+f"(d[72]),
          "+f"(d[73]),"+f"(d[74]),"+f"(d[75]),"+f"(d[76]),"+f"(d[77]),"+f"(d[78]),"+f"(d[79]),"+f"(d[80]),"+f"(d[81]),"+f"(d[82]),"+f"(d[83]),"+f"(d[84]),
          "+f"(d[85]),"+f"(d[86]),"+f"(d[87]),"+f"(d[88]),"+f"(d[89]),"+f"(d[90]),"+f"(d[91]),"+f"(d[92]),"+f"(d[93]),"+f"(d[94]),"+f"(d[95]),"+f"(d[96]),
          "+f"(d[97]),"+f"(d[98]),"+f"(d[99]),"+f"(d[100]),"+f"(d[101]),"+f"(d[102]),"+f"(d[103]),"+f"(d[104]),"+f"(d[105]),"+f"(d[106]),"+f"(d[107]),
          "+f"(d[108]),"+f"(d[109]),"+f"(d[110]),"+f"(d[111]),"+f"(d[112]),"+f"(d[113]),"+f"(d[114]),"+f"(d[115]),"+f"(d[116]),"+f"(d[117]),"+f"(d[118]),
          "+f"(d[119]),"+f"(d[120]),"+f"(d[121]),"+f"(d[122]),"+f"(d[123]),"+f"(d[124]),"+f"(d[125]),"+f"(d[126]),"+f"(d[127])
        : "l"(da), "l"(db), "r"(acc));
}
__device__ __forceinline__ void wgmma_ss_n128(float* d, uint64_t da, uint64_t db, int acc) {
    asm volatile("{\n.reg .pred p;\nsetp.ne.b32 p, %66, 0;\nwgmma.mma_async.sync.aligned.m64n128k16.f32.bf16.bf16 {"
        "%0,%1,%2,%3,%4,%5,%6,%7,%8,%9,%10,%11,%12,%13,%14,%15,%16,%17,%18,%19,%20,%21,%22,%23,%24,%25,%26,%27,%28,%29,%30,%31,%32,%33,%34,%35,%36,%37,%38,%39,"
        "%40,%41,%42,%43,%44,%45,%46,%47,%48,%49,%50,%51,%52,%53,%54,%55,%56,%57,%58,%59,%60,%61,%62,%63"
        "}, %64, %65, p, 1, 1, 0, 1;\n}\n"
        : "+f"(d[0]),"+f"(d[1]),"+f"(d[2]),"+f"(d[3]),"+f"(d[4]),"+f"(d[5]),"+f"(d[6]),"+f"(d[7]),"+f"(d[8]),"+f"(d[9]),"+f"(d[10]),"+f"(d[11]),"+f"(d[12]),
          "+f"(d[13]),"+f"(d[14]),"+f"(d[15]),"+f"(d[16]),"+f"(d[17]),"+f"(d[18]),"+f"(d[19]),"+f"(d[20]),"+f"(d[21]),"+f"(d[22]),"+f"(d[23]),"+f"(d[24]),
          "+f"(d[25]),"+f"(d[26]),"+f"(d[27]),"+f"(d[28]),"+f"(d[29]),"+f"(d[30]),"+f"(d[31]),"+f"(d[32]),"+f"(d[33]),"+f"(d[34]),"+f"(d[35]),"+f"(d[36]),
          "+f"(d[37]),"+f"(d[38]),"+f"(d[39]),"+f"(d[40]),"+f"(d[41]),"+f"(d[42]),"+f"(d[43]),"+f"(d[44]),"+f"(d[45]),"+f"(d[46]),"+f"(d[47]),"+f"(d[48]),
          "+f"(d[49]),"+f"(d[50]),"+f"(d[51]),"+f"(d[52]),"+f"(d[53]),"+f"(d[54]),"+f"(d[55]),"+f"(d[56]),"+f"(d[57]),"+f"(d[58]),"+f"(d[59]),"+f"(d[60]),
          "+f"(d[61]),"+f"(d[62]),"+f"(d[63])
        : "l"(da), "l"(db), "r"(acc));
}
__device__ __forceinline__ void wgmma_ss_n64(float* d, uint64_t da, uint64_t db, int acc) {
    asm volatile("{\n.reg .pred p;\nsetp.ne.b32 p, %34, 0;\nwgmma.mma_async.sync.aligned.m64n64k16.f32.bf16.bf16 {"
        "%0,%1,%2,%3,%4,%5,%6,%7,%8,%9,%10,%11,%12,%13,%14,%15,%16,%17,%18,%19,%20,%21,%22,%23,%24,%25,%26,%27,%28,%29,%30,%31"
        "}, %32, %33, p, 1, 1, 0, 1;\n}\n"
        : "+f"(d[0]),"+f"(d[1]),"+f"(d[2]),"+f"(d[3]),"+f"(d[4]),"+f"(d[5]),"+f"(d[6]),"+f"(d[7]),"+f"(d[8]),"+f"(d[9]),"+f"(d[10]),"+f"(d[11]),"+f"(d[12]),
          "+f"(d[13]),"+f"(d[14]),"+f"(d[15]),"+f"(d[16]),"+f"(d[17]),"+f"(d[18]),"+f"(d[19]),"+f"(d[20]),"+f"(d[21]),"+f"(d[22]),"+f"(d[23]),"+f"(d[24]),
          "+f"(d[25]),"+f"(d[26]),"+f"(d[27]),"+f"(d[28]),"+f"(d[29]),"+f"(d[30]),"+f"(d[31])
        : "l"(da), "l"(db), "r"(acc));
}
__device__ __forceinline__ void wgmma_rs_n64_zero(float* d, const uint32_t* a, uint64_t db) {
    asm volatile("wgmma.mma_async.sync.aligned.m64n64k16.f32.bf16.bf16 {"
        "%0,%1,%2,%3,%4,%5,%6,%7,%8,%9,%10,%11,%12,%13,%14,%15,%16,%17,%18,%19,%20,%21,%22,%23,%24,%25,%26,%27,%28,%29,%30,%31"
        "}, {%32,%33,%34,%35}, %36, 0, 1, 1, 0;\n"
        : "=f"(d[0]),"=f"(d[1]),"=f"(d[2]),"=f"(d[3]),"=f"(d[4]),"=f"(d[5]),"=f"(d[6]),"=f"(d[7]),"=f"(d[8]),"=f"(d[9]),"=f"(d[10]),"=f"(d[11]),"=f"(d[12]),
          "=f"(d[13]),"=f"(d[14]),"=f"(d[15]),"=f"(d[16]),"=f"(d[17]),"=f"(d[18]),"=f"(d[19]),"=f"(d[20]),"=f"(d[21]),"=f"(d[22]),"=f"(d[23]),"=f"(d[24]),
          "=f"(d[25]),"=f"(d[26]),"=f"(d[27]),"=f"(d[28]),"=f"(d[29]),"=f"(d[30]),"=f"(d[31])
        : "r"(a[0]), "r"(a[1]), "r"(a[2]), "r"(a[3]), "l"(db));
}
__device__ __forceinline__ void wgmma_rs_n64_acc(float* d, const uint32_t* a, uint64_t db) {
    asm volatile("wgmma.mma_async.sync.aligned.m64n64k16.f32.bf16.bf16 {"
        "%0,%1,%2,%3,%4,%5,%6,%7,%8,%9,%10,%11,%12,%13,%14,%15,%16,%17,%18,%19,%20,%21,%22,%23,%24,%25,%26,%27,%28,%29,%30,%31"
        "}, {%32,%33,%34,%35}, %36, 1, 1, 1, 0;\n"
        : "+f"(d[0]),"+f"(d[1]),"+f"(d[2]),"+f"(d[3]),"+f"(d[4]),"+f"(d[5]),"+f"(d[6]),"+f"(d[7]),"+f"(d[8]),"+f"(d[9]),"+f"(d[10]),"+f"(d[11]),"+f"(d[12]),
          "+f"(d[13]),"+f"(d[14]),"+f"(d[15]),"+f"(d[16]),"+f"(d[17]),"+f"(d[18]),"+f"(d[19]),"+f"(d[20]),"+f"(d[21]),"+f"(d[22]),"+f"(d[23]),"+f"(d[24]),
          "+f"(d[25]),"+f"(d[26]),"+f"(d[27]),"+f"(d[28]),"+f"(d[29]),"+f"(d[30]),"+f"(d[31])
        : "r"(a[0]), "r"(a[1]), "r"(a[2]), "r"(a[3]), "l"(db));
}
__device__ __forceinline__ void wgmma_rs_n24_acc(float* d, const uint32_t* a, uint64_t db) {
    asm volatile("wgmma.mma_async.sync.aligned.m64n24k16.f32.bf16.bf16 {"
        "%0,%1,%2,%3,%4,%5,%6,%7,%8,%9,%10,%11"
        "}, {%12,%13,%14,%15}, %16, 1, 1, 1, 1;\n"
        : "+f"(d[0]),"+f"(d[1]),"+f"(d[2]),"+f"(d[3]),"+f"(d[4]),"+f"(d[5]),"+f"(d[6]),"+f"(d[7]),"+f"(d[8]),"+f"(d[9]),"+f"(d[10]),"+f"(d[11])
        : "r"(a[0]), "r"(a[1]), "r"(a[2]), "r"(a[3]), "l"(db));
}
__device__ __forceinline__ void wgmma_rs_n24_zero(float* d, const uint32_t* a, uint64_t db) {
    asm volatile("wgmma.mma_async.sync.aligned.m64n24k16.f32.bf16.bf16 {"
        "%0,%1,%2,%3,%4,%5,%6,%7,%8,%9,%10,%11"
        "}, {%12,%13,%14,%15}, %16, 0, 1, 1, 1;\n"
        : "=f"(d[0]),"=f"(d[1]),"=f"(d[2]),"=f"(d[3]),"=f"(d[4]),"=f"(d[5]),"=f"(d[6]),"=f"(d[7]),"=f"(d[8]),"=f"(d[9]),"=f"(d[10]),"=f"(d[11])
        : "r"(a[0]), "r"(a[1]), "r"(a[2]), "r"(a[3]), "l"(db));
}

constexpr int OFF_ONES = 131072;
constexpr int OFF_RING = OFF_ONES + 4096;
constexpr int NRING = 5;
constexpr int OFF_B2 = OFF_RING + NRING * 16384;
constexpr int OFF_CS = OFF_B2 + 2048;
constexpr int OFF_RS = OFF_CS + 2560;
constexpr int OFF_BAR = OFF_RS + 1024;
enum { B_FULL = 0, B_STATS = 40, B_KV = 45, B_RING = 53, B_WO = 56, B_O = 57, B_CNT2 = 65,
       B_AFREE = 65, B_ORD = 69, B_QKV = 73, B_CNT4 = 74, B_EMPTY = 74, B_AFREE0 = 79, B_DONE = 80, B_CNT8 = 81, B_TILE = 81, B_OW = 86, B_NUM = 100 };
constexpr int OFF_TS = OFF_BAR + 1024;
constexpr int SMEM_BYTES = OFF_BAR + B_NUM * 8;
constexpr unsigned FIXED_MASK = 0xB5;
constexpr float P71 = 2361183241434822606848.0f, M71 = 4.235164736271502e-22f;

__device__ __forceinline__ uint32_t exp2_fixed(float lo, float hi, uint32_t half2) {
    uint32_t y, g, d;
    asm("cvt.pack.sat.s16.s32 %0, %1, %2;" : "=r"(y) : "r"(__float_as_uint(hi)), "r"(__float_as_uint(lo)));
    asm("lop3.b32 %0, %1, 0x007F007F, %2, 0xEA;" : "=r"(g) : "r"(y), "r"(half2));
    asm("fma.rn.bf16x2 %0, %1, %2, %3;" : "=r"(d) : "r"(y), "r"(g), "r"(y & 0xFF80FF80u));
    return d;
}
__device__ __forceinline__ uint32_t k_tile_addr(uint32_t base, int tile) {
    const int c = tile >> 2;
    return base + ((tile & 2) ? 98304 + c * 4096 : (2 * c + 1) * 4096) + (tile & 1) * 2048;
}
__host__ __device__ constexpr int stage_of(int t, int j) { return t == 0 ? j + (j >> 1) : (t == 1 && j < 4) ? 3 * j + 2 : 8 * t + j; }
__host__ __device__ constexpr uint32_t slots_of(int t) { uint32_t v = 0; for (int j = 0; j < 8; j++) v |= (uint32_t)(stage_of(t, j) % NRING) << (4 * j); return v; }
__host__ __device__ constexpr uint64_t first16() { uint64_t v = 0; for (int i = 0; i < 16; i++) v |= (uint64_t)i << (4 * stage_of(i >> 3, i & 7)); return v; }
constexpr uint32_t POS_STD = 0x76543210u, POS_LAST = 0x37521640u;

__global__ void __cluster_dims__(2, 1, 1) __launch_bounds__(640, 1)
mega_kernel(const __nv_bfloat16* __restrict__ x, const __nv_bfloat16* __restrict__ wqkv, const __nv_bfloat16* __restrict__ w1,
            const __nv_bfloat16* __restrict__ w3, __nv_bfloat16* __restrict__ out,
            const __grid_constant__ CUtensorMap mx, const __grid_constant__ CUtensorMap mqkv, const __grid_constant__ CUtensorMap mw1,
            const __grid_constant__ CUtensorMap mw3, const __grid_constant__ CUtensorMap mw2, const __grid_constant__ CUtensorMap mwo,
            uint32_t half2) {
    extern __shared__ __align__(1024) uint8_t smem_raw[];
    const uint32_t sb = __shfl_sync(0xffffffffu, smem_u32(smem_raw), 0);
    if ((sb & 0xFFFFFF) != SMEM_BASE) __trap();
    const uint32_t bars = sb + OFF_BAR, ring = sb + OFF_RING;
    const int tid = threadIdx.x, lane = tid & 31, g = lane >> 2, t4 = lane & 3;
    const int warp = __shfl_sync(0xffffffffu, tid >> 5, 0), wg = warp >> 2, wq = warp & 3;
    const int rank = blockIdx.x & 1, cl = blockIdx.x >> 1;
    const int grp = cl < 4 ? 4 + cl : cl < 36 ? (cl - 4) >> 3 : 4 + (cl - 36) / 7;
    const int rot = cl < 4 ? 7 : cl < 36 ? (cl - 4) & 7 : (cl - 36) % 7;
    const int mblk = rot * 2 + rank;
    const int nq = grp < 4 ? 2 : 1;
    const int qt0 = grp < 4 ? 2 * grp : 4 + grp;
    const int gu0 = (grp < 4 ? 3 * grp : 4 * grp - 4) - nq;
    const int head = blockIdx.x >> 2, qb = blockIdx.x & 3;

    if (elect_one()) {
#pragma unroll
        for (int i = 0; i < 5; i++) { const int b = warp * 5 + i; mbar_init(bars + 8 * b, b < B_CNT2 ? 1 : b < B_CNT4 ? 2 : b < B_CNT8 ? 4 : 8); }
        if (warp == 0) {
            fence_async_smem();
#pragma unroll
            for (int j = 0; j < 2; j++) {
                tma2d(sb + j * 16384, &mx, j * 64, mblk * 128, bars + 8 * (B_FULL + j));
                tma2d(ring + j * 16384, &mqkv, qt0 * 128, j * 64, bars + 8 * (B_FULL + j));
                tma2d(ring + j * 16384 + 8192, &mqkv, qt0 * 128 + 64, j * 64, bars + 8 * (B_FULL + j));
            }
        }
        if (warp < 8) {
#pragma unroll
            for (int i = 0; i < 5; i++) mbar_expect(bars + 8 * (warp * 5 + i), warp * 5 + i < 8 ? 32768 : 16384);
        }
        if (warp == 16) asm volatile("prefetch.tensormap [%0];" :: "l"(rank ? &mw3 : &mw1) : "memory");
        asm volatile("fence.mbarrier_init.release.cluster;" ::: "memory");
    }
    const uint32_t tag = __ldcg(g_epoch + blockIdx.x) + 1;
    __syncthreads();
    if (tid == 512) TSTAMP(26);
    asm volatile("barrier.cluster.arrive.relaxed.aligned;" ::: "memory");

    if (wg < 4) {
        const int pair = wg >> 1, half = wg & 1;
        if (pair == 1) {
            const int row = mblk * 128 + grp * 16 + (warp - 8) * 2 + (lane >> 4);
            uint4 v[8];
            const uint32_t* w = reinterpret_cast<const uint32_t*>(v);
            const __nv_bfloat16* src; int ld;
            if (half < nq) { src = wqkv + (qt0 + half) * 128 + rank * 64; ld = 3 * DM; }
            else           { src = (rank ? w3 : w1) + (gu0 + half) * 64; ld = FF; }
            src += (size_t)(rot * 64 + (lane >> 1)) * ld + wq * 16 + (lane & 1) * 8;
#pragma unroll
            for (int j = 0; j < 4; j++) v[4 + j] = __ldg(reinterpret_cast<const uint4*>(src + (size_t)j * 16 * ld));
#pragma unroll
            for (int j = 0; j < 4; j++) v[j] = __ldg(reinterpret_cast<const uint4*>(x + (size_t)row * DM) + j * 16 + (lane & 15));
            float c[8];
#pragma unroll
            for (int e = 0; e < 4; e++) {
                c[2 * e] = (bf_lo(w[16 + e]) + bf_lo(w[20 + e])) + (bf_lo(w[24 + e]) + bf_lo(w[28 + e]));
                c[2 * e + 1] = (bf_hi(w[16 + e]) + bf_hi(w[20 + e])) + (bf_hi(w[24 + e]) + bf_hi(w[28 + e]));
            }
#pragma unroll
            for (int n = 4; n > 0; n >>= 1) {
                const bool up = lane & (4 * n);
#pragma unroll
                for (int e = 0; e < n; e++) c[e] = (up ? c[e + n] : c[e]) + __shfl_xor_sync(0xffffffffu, up ? c[e] : c[e + n], 4 * n);
            }
            c[0] += __shfl_xor_sync(0xffffffffu, c[0], 2);
            if (!(lane & 2)) st_tagged(reinterpret_cast<unsigned long long*>(g_cs) + ((grp * 5 + half) * 8 + rot) * 128 + rank * 64 + wq * 16 + (lane & 1) * 8 + g, __float_as_uint(c[0]), tag);
            float s0 = 0.f, v0 = 0.f;
#pragma unroll
            for (int j = 0; j < 16; j++) s0 += bf_lo(w[j]) + bf_hi(w[j]);
#pragma unroll
            for (int d = 1; d < 16; d <<= 1) s0 += __shfl_xor_sync(0xffffffffu, s0, d);
            const float mean = s0 * (1.0f / DM);
#pragma unroll
            for (int j = 0; j < 16; j++) { const float a = bf_lo(w[j]) - mean, b = bf_hi(w[j]) - mean; v0 += fmaf(a, a, b * b); }
#pragma unroll
            for (int d = 1; d < 16; d <<= 1) v0 += __shfl_xor_sync(0xffffffffu, v0, d);
            if ((lane & 15) == 0) st_tagged(reinterpret_cast<unsigned long long*>(g_rs) + row, pack_bf16(mean, sqrtf(bf_round(bf_round(v0 * (1.0f / DM)) + 1e-5f))), tag);
        }
        asm volatile("barrier.cluster.wait.aligned;" ::: "memory");

        uint32_t q[4], qn[6];
        {
            float acc[64];
            const int rowblk = mblk * 2 + half, tile16 = rowblk * 4 + wq;
            const bool rel = wq < 2 && lane == 0, rel2 = wq == 2 && lane == 0;
            uint32_t empty;
            asm("mapa.shared::cluster.u32 %0, %1, %2;" : "=r"(empty) : "r"(bars + 8 * B_EMPTY), "r"(wq & 1));
#pragma unroll 1
            for (int t = pair; t < 5; t += 2) {
                const uint32_t sl = t == 0 ? slots_of(0) : t == 1 ? slots_of(1) : t == 2 ? slots_of(2) : t == 3 ? slots_of(3) : slots_of(4);
                const uint32_t po = t == 4 ? POS_LAST : POS_STD, full = bars + 8 * (B_FULL + 8 * t);
                if (tid == 0 && t == 0) TSTAMP(30);
                if (t == 1) mbar_wait(full - 64, 0);
                mbar_wait(full, 0);
                if (t >= 2) mbar_wait(bars + 8 * (B_ORD + t - 1), 0);
                if (tid == 0 && t == 0) TSTAMP(1);
#pragma unroll
                for (int j = 0; j < 8; j++) {
                    const uint64_t da = mkdesc(half * 8192, 16, 1024, 1) + ((po >> (4 * j)) & 7) * 1024;
                    const uint64_t db = mkdesc(OFF_RING, 8192, 1024, 1) + ((sl >> (4 * j)) & 7) * 1024;
                    if (wq == 3 && half == 0 && lane == 0) TS2(1, stage_of(t, j));
                    wg_fence();
#pragma unroll
                    for (int k = 0; k < 4; k++) wgmma_ss_n128(acc, da + k * 2, db + k * 128, (j | k) != 0);
                    wg_commit();
                    if (j == 7 && t < 4 && rel2) mbar_arrive(bars + 8 * (B_ORD + t));
                    if (j > 0) {
                        wg_wait<1>();
                        if (wq == 3 && half == 0 && lane == 0) TS2(2, stage_of(t, j - 1));
                        if (rel) mbar_arrive_remote(empty + ((sl >> (4 * j - 4)) & 7) * 8);
                        if ((j == 3 || j == 4 || j == 7) && t == 4 && rel2) mbar_arrive(bars + 8 * (j == 3 ? B_AFREE0 : j == 4 ? B_AFREE + 1 : B_AFREE + 2));
                    }
                    if (j < 7) {
                        if (t == 1) mbar_wait(full - 64 + 8 * (j + 1), 0);
                        mbar_wait(full + 8 * (j + 1), 0);
                    }
                }
                if (t >= 3) {
                    mbar_wait(bars + 8 * B_QKV, 0);
                    const uint4* pq = g_q + (head * 128 + (qb * 8 + wg) * 4 + wq) * 32 + lane;
                    const uint4 v = __ldcg(pq), u = __ldcg(pq + 512);
                    qn[0] = v.x; qn[1] = v.y; qn[2] = v.z; qn[3] = v.w; q[0] = u.x; q[1] = u.y; q[2] = u.z; q[3] = u.w;
                }
                wg_wait<0>();
                if (rel) mbar_arrive_remote(empty + (sl >> 28) * 8);
                if (t >= 3 && rel2) mbar_arrive(bars + 8 * (t == 4 ? B_AFREE + 3 : B_AFREE0));
                pin<64>(acc);
                if (wq == 0 && half == 0 && lane == 0) TSTAMP(2 + 2 * t);
                mbar_wait(bars + 8 * (B_STATS + (t >= 2)), 0);
                uint32_t rs0, rs1;
                asm volatile("ld.shared.b32 %0, [%1];" : "=r"(rs0) : "r"(sb + OFF_RS + (half * 64 + wq * 16 + g) * 4));
                asm volatile("ld.shared.b32 %0, [%1];" : "=r"(rs1) : "r"(sb + OFF_RS + (half * 64 + wq * 16 + g + 8) * 4));
                const float m0 = bf_lo(rs0), m1 = bf_lo(rs1);
                float d0 = bf_hi(rs0), d1 = bf_hi(rs1);
#pragma unroll
                for (int j = 0; j < 16; j++) {
                    float c0, c1;
                    asm volatile("ld.shared.v2.f32 {%0,%1}, [%2];" : "=f"(c0), "=f"(c1) : "r"(sb + OFF_CS + (t * 128 + j * 8 + t4 * 2) * 4));
                    acc[4 * j] = fmaf(-m0, c0, acc[4 * j]); acc[4 * j + 1] = fmaf(-m0, c1, acc[4 * j + 1]);
                    acc[4 * j + 2] = fmaf(-m1, c0, acc[4 * j + 2]); acc[4 * j + 3] = fmaf(-m1, c1, acc[4 * j + 3]);
                }
                float r0 = __frcp_rn(d0), r1 = __frcp_rn(d1);
                if (t < nq) {
                    const int qt = qt0 + t, h0 = (qt & 3) * 8;
                    if (qt < 4) {
                        r0 *= 0.25f * 1.4426950408889634f * M71; r1 *= 0.25f * 1.4426950408889634f * M71;
                    } else if (qt < 8) {
                        r0 *= ((FIXED_MASK >> (2 * wq)) & 1) ? M71 : P71; r1 *= ((FIXED_MASK >> (2 * wq + 1)) & 1) ? M71 : P71;
                    }
                    uint32_t* p; int s8, sh;
                    if (qt < 8) { p = reinterpret_cast<uint32_t*>(g_k + h0 * 4096) + tile16 * 128 + lane; s8 = 64; sh = 32; }
                    else        { p = reinterpret_cast<uint32_t*>(g_v + h0 * 4096) + tile16 * 64 + lane;  s8 = 32; sh = 8192; }
#pragma unroll
                    for (int hh = 0; hh < 8; hh++) {
                        const float* a = acc + hh * 8;
                        const uint32_t e0 = pack_bf16(a[0] * r0, a[1] * r0), e1 = pack_bf16(a[2] * r1, a[3] * r1);
                        const uint32_t e2 = pack_bf16(a[4] * r0, a[5] * r0), e3 = pack_bf16(a[6] * r1, a[7] * r1);
                        if (qt < 4) g_q[((h0 + hh) * 128 + tile16) * 32 + lane] = make_uint4(e0, e1, e2, e3);
                        else { uint32_t* pp = p + hh * 16384; pp[0] = e0; pp[s8] = e1; pp[sh] = e2; pp[sh + s8] = e3; }
                    }
                } else {
                    uint32_t* p = reinterpret_cast<uint32_t*>(g_h + (rowblk * 28 + gu0 + t) * 512) + wq * 512 + lane;
                    r0 *= -1.4426950408889634f; r1 *= -1.4426950408889634f; d0 *= d0; d1 *= d1;
#pragma unroll
                    for (int j = 0; j < 8; j++) {
                        const float* a = acc + j * 4; const float* b = a + 32;
                        p[j * 32] = pack_bf16(a[0] * b[0] * rcpf(fmaf(ex2f(a[0] * r0), d0, d0)), a[1] * b[1] * rcpf(fmaf(ex2f(a[1] * r0), d0, d0)));
                        p[256 + j * 32] = pack_bf16(a[2] * b[2] * rcpf(fmaf(ex2f(a[2] * r1), d1, d1)), a[3] * b[3] * rcpf(fmaf(ex2f(a[3] * r1), d1, d1)));
                    }
                }
                __syncwarp();
                if (elect_one()) mbar_arrive(bars + 8 * (B_TILE + t));
                if (wq == 0 && half == 0 && lane == 0) TSTAMP(3 + 2 * t);
            }
        }
        const uint64_t db2 = mkdesc(OFF_B2, 128, 256, 0);
        float s[32];
        auto ref_point = [&](int ntile, uint32_t& b0, uint32_t& b1) {
            float m0 = -INFINITY, m1 = -INFINITY, f0 = -INFINITY, f1 = -INFINITY;
#pragma unroll 1
            for (int t = 0; t < ntile; t++) {
                wg_fence();
                wgmma_rs_n64_zero(s, q, mkdesc(k_tile_addr(0, t), 128, 256, 0));
                wg_commit();
                wg_wait<0>();
                pin<32>(s);
#pragma unroll
                for (int i = 0; i < 8; i++) {
                    if ((FIXED_MASK >> i) & 1) { f0 = fmaxf(f0, fmaxf(s[4 * i], s[4 * i + 1])); f1 = fmaxf(f1, fmaxf(s[4 * i + 2], s[4 * i + 3])); }
                    else                       { m0 = fmaxf(m0, fmaxf(s[4 * i], s[4 * i + 1])); m1 = fmaxf(m1, fmaxf(s[4 * i + 2], s[4 * i + 3])); }
                }
            }
            m0 = fmaxf(m0, f0 * P71 * P71); m1 = fmaxf(m1, f1 * P71 * P71);
            m0 = fmaxf(m0, __shfl_xor_sync(0xffffffffu, m0, 1)); m1 = fmaxf(m1, __shfl_xor_sync(0xffffffffu, m1, 1));
            m0 = fmaxf(m0, __shfl_xor_sync(0xffffffffu, m0, 2)); m1 = fmaxf(m1, __shfl_xor_sync(0xffffffffu, m1, 2));
#pragma unroll
            for (int r = 0; r < 2; r++) {
                const float m = -rintf(r ? m1 : m0), mh = bf_round(m), mm = bf_round(m - mh), ml = m - mh - mm;
                const float lo = t4 == 0 ? mh : t4 == 1 ? ml : t4 == 2 ? 1.f : 0.f, hi = t4 == 0 ? mm : t4 == 1 ? 1.f : 0.f;
                (r ? b1 : b0) = pack_bf16(lo * M71, hi * M71);
            }
        };
        uint32_t q2[4];
        int redo = 1;
        mbar_wait(bars + 8 * B_KV, 0);
#pragma unroll 1
        for (int round = -1; round < 2;) {
            if (redo) ref_point(redo, q2[0], q2[1]);
            if (round < 0) {
#pragma unroll
                for (int i = 0; i < 4; i++) { const uint32_t tq = q[i]; q[i] = qn[i]; qn[i] = tq; }
                qn[4] = q2[0]; qn[5] = q2[1];
                q2[2] = __shfl_sync(0xffffffffu, q2[0], 3); q2[3] = __shfl_sync(0xffffffffu, q2[1], 3);
                round = 0;
                continue;
            }
            float o[12]; uint32_t p[16];
#pragma unroll
            for (int i = 0; i < 12; i++) o[i] = 0.f;
            pin<12>(o); pin<4>(q2);
            if (wq == 0 && half == 0 && lane == 0) TSTAMP(12 + 4 * round + pair);
            uint64_t dk0 = mkdesc(4096, 128, 256, 0), dk1 = mkdesc(98304, 128, 256, 0), dv = mkdesc(0, 128, 65536, 0);
#pragma unroll 1
            for (int c = 0; c < 8; c++, dk0 += 512, dk1 += 256, dv += 512 - (256ull << 32)) {
                if (round == 0) mbar_wait(bars + 8 * (B_KV + c), 0);
#pragma unroll
                for (int t = 0; t < 4; t++) {
                    wg_fence();
                    wgmma_rs_n64_zero(s, q, (t & 2 ? dk1 : dk0) + (t & 1) * 128);
                    wgmma_rs_n64_acc(s, q2, db2);
                    wg_commit();
                    wg_wait<0>();
                    pin<32>(s); pin<16>(p);
#pragma unroll
                    for (int i = 0; i < 16; i++) {
                        if ((FIXED_MASK >> (i >> 1)) & 1) p[i] = exp2_fixed(s[2 * i], s[2 * i + 1], half2);
                        else                              p[i] = pack_bf16(ex2f(s[2 * i]), ex2f(s[2 * i + 1]));
                    }
                    wg_fence();
#pragma unroll
                    for (int k = 0; k < 4; k++) wgmma_rs_n24_acc(o, p + 4 * k, dv + (t * 4 + k) * 16);
                    wg_commit();
                }
            }
            wg_wait<0>();
            pin<12>(o);
            if (redo != 32) {
                float chk = (o[8] + o[10]) * 256.f;
#pragma unroll
                for (int i = 0; i < 8; i++) chk += fabsf(o[i]);
                uint32_t bad;
                asm volatile("{\n.reg .pred p, q;\nsetp.geu.f32 q, %1, 0f7F800000;\nbar.red.or.pred p, %2, 128, q;\nselp.u32 %0, 1, 0, p;\n}" : "=r"(bad) : "f"(chk), "r"(1 + wg) : "memory");
                if (__any_sync(0xffffffffu, bad)) { redo = 32; continue; }
            }
            const int rowblk = qb * 8 + round * 4 + wg;
            const float r0 = rcpf(o[8]), r1 = rcpf(o[10]);
            uint32_t* po = reinterpret_cast<uint32_t*>(g_o + (rowblk * 8 + (head >> 2)) * 512) + wq * 512 + (head & 3) * 64 + lane;
            po[0] = pack_bf16(o[0] * r0, o[1] * r0); po[256] = pack_bf16(o[2] * r1, o[3] * r1);
            po[32] = pack_bf16(o[4] * r0, o[5] * r0); po[288] = pack_bf16(o[6] * r1, o[7] * r1);
            if (round == 0) {
                __syncwarp();
                if (elect_one()) mbar_arrive(bars + 8 * (B_OW + pair));
            } else {
                bar_sync(1 + wg, 128);
                if (wq == 0 && elect_one()) { mbar_arrive(bars + 8 * B_DONE); signal_cnt(C_O + rowblk); }
            }
#pragma unroll
            for (int i = 0; i < 4; i++) q[i] = qn[i];
            q2[0] = qn[4]; q2[1] = qn[5];
            redo = 0;
            if (wq == 0 && half == 0 && lane == 0) TSTAMP(14 + 4 * round + pair);
            round++;
        }
    } else {
        asm volatile("barrier.cluster.wait.aligned;" ::: "memory");
        if (tid == 512) TSTAMP(27);
        if (wq == 0) {
            const CUtensorMap* mgu = rank ? &mw3 : &mw1;
            const CUtensorMap* m1 = nq == 2 ? &mqkv : mgu;
            const int col0 = qt0 * 128 + rank * 64, col1 = nq == 2 ? col0 + 128 : (gu0 + 1) * 64;
            uint64_t order = first16() >> 8;
            uint32_t slot = 2, ph = 1;
#pragma unroll 1
            for (int n = 2; n < 40; n++) {
                const int id = n < 16 ? (int)order & 15 : n, j = id & 7;
                const int kc = (n < 32 ? j : (POS_LAST >> (4 * j)) & 7) * 64;
                const CUtensorMap* m = id < 8 ? &mqkv : id < 16 ? m1 : mgu;
                const int col = id < 8 ? col0 : id < 16 ? col1 : (gu0 + (id >> 3)) * 64;
                const uint32_t dst = ring + slot * 16384 + rank * 8192, fb = bars + 8 * (B_FULL + id);
                order >>= 4;
                if (id < 8 && elect_one()) tma2d(sb + id * 16384, &mx, kc, mblk * 128, fb);
                mbar_wait(bars + 8 * (B_EMPTY + slot), ph);
                if (elect_one()) { TS2(0, n); tma2d_mc(dst, m, col, kc, fb); }
                if (++slot == NRING) { slot = 0; ph ^= 1; }
            }
        } else {
            auto gather = [&](int t) {
                float a[4];
                for (int n = 0;; n++) {
                    uint32_t stale = 0;
                    a[0] = a[1] = a[2] = a[3] = 0.f;
#pragma unroll
                    for (int i = 0; i < 16; i++) {
                        uint32_t u, v;
                        stale |= ld_tagged2(g_cs + (grp * 5 + t) * 512 + i * 32 + lane, tag, u, v);
                        a[(i & 1) * 2] += __uint_as_float(u); a[(i & 1) * 2 + 1] += __uint_as_float(v);
                    }
                    if (__all_sync(0xffffffffu, stale == 0)) break;
                    if (n > 2000000) __trap();
                }
                asm volatile("st.shared.v2.f32 [%0], {%1,%2};" :: "r"(sb + OFF_CS + t * 512 + lane * 8), "f"(a[0]), "f"(a[1]) : "memory");
                asm volatile("st.shared.v2.f32 [%0], {%1,%2};" :: "r"(sb + OFF_CS + t * 512 + 256 + lane * 8), "f"(a[2]), "f"(a[3]) : "memory");
            };
            mbar_wait(bars + 8 * (B_FULL + 1), 0);
            if (wq == 3) {
                uint32_t a, b, c, d;
                for (int n = 0;; n++) {
                    const uint32_t stale = ld_tagged2(g_rs + mblk * 64 + lane * 2, tag, a, b) | ld_tagged2(g_rs + mblk * 64 + lane * 2 + 1, tag, c, d);
                    if (__all_sync(0xffffffffu, stale == 0)) break;
                    if (n > 2000000) __trap();
                }
                asm volatile("st.shared.v4.b32 [%0], {%1,%2,%3,%4};" :: "r"(sb + OFF_RS + lane * 16), "r"(a), "r"(b), "r"(c), "r"(d) : "memory");
            }
#pragma unroll 1
            for (int pass = 0; pass < 2; pass++) {
                const int t = pass ? wq + 1 : wq - 1;
                if (pass || wq < 3) gather(t);
                bar_sync(6, 96);
                if (wq == 1 && elect_one()) { mbar_arrive(bars + 8 * (B_STATS + pass)); TSTAMP(pass ? 31 : 28); }
                if (pass) break;
                const __nv_bfloat16* src = (rank ? w3 : w1) + (gu0 + wq + 1) * 64 + (size_t)(rot * 64 + (lane >> 3)) * FF + (lane & 7) * 8;
                uint4 v[16];
                const uint32_t* w = reinterpret_cast<const uint32_t*>(v);
#pragma unroll
                for (int j = 0; j < 16; j++) v[j] = __ldg(reinterpret_cast<const uint4*>(src + (size_t)j * 4 * FF));
                float c[8];
#pragma unroll
                for (int e = 0; e < 4; e++) {
                    float a = 0.f, b = 0.f;
#pragma unroll
                    for (int j = 0; j < 16; j++) { a += bf_lo(w[4 * j + e]); b += bf_hi(w[4 * j + e]); }
                    c[2 * e] = a; c[2 * e + 1] = b;
                }
#pragma unroll
                for (int n = 4; n > 1; n >>= 1) {
                    const bool up = lane & (4 * n);
#pragma unroll
                    for (int e = 0; e < n; e++) c[e] = (up ? c[e + n] : c[e]) + __shfl_xor_sync(0xffffffffu, up ? c[e] : c[e + n], 4 * n);
                }
                unsigned long long* dst = reinterpret_cast<unsigned long long*>(g_cs) + ((grp * 5 + wq + 1) * 8 + rot) * 128 + rank * 64 + (lane & 7) * 8 + (lane >> 3) * 2;
                st_tagged(dst, __float_as_uint(c[0]), tag); st_tagged(dst + 1, __float_as_uint(c[1]), tag);
            }
        }
        if (wq == 3) {
            if (lane == 0) g_epoch[blockIdx.x] = tag;
#pragma unroll 1
            for (int i = lane; i < 256; i += 32) asm volatile("st.shared.v4.b32 [%0], {%1,%1,%1,%1};" :: "r"(sb + OFF_ONES + i * 16), "r"(0x3F803F80u) : "memory");
#pragma unroll 1
            for (int i = lane; i < 128; i += 32) {
                const bool fx = (FIXED_MASK >> (i >> 4)) & 1;
                uint32_t a = fx ? pack_bf16(M71, M71) : pack_bf16(P71, P71);
                uint32_t b = fx ? pack_bf16(M71, 47.0f * M71) : pack_bf16(P71, -79.5f * P71);
                uint32_t c = fx ? 0u : pack_bf16(0.08214f * P71, 0.f);
                if (i & 8) a = b = c = 0;
                asm volatile("st.shared.v4.b32 [%0], {%1,%2,%3,%4};" :: "r"(sb + OFF_B2 + i * 16), "r"(a), "r"(b), "r"(c), "r"(0) : "memory");
            }
            fence_async_smem();
            __syncwarp();
            if (elect_one()) mbar_arrive(bars + 8 * B_QKV);
        } else if (wq == 1) {
#pragma unroll 1
            for (int i = 0; i < 3; i++) wait_cnt(C_QKV + i * 4 + (head >> 3), 16 * tag, 100);
            if (elect_one()) { mbar_arrive(bars + 8 * B_QKV); TSTAMP(29); }
            fence_async_all();
            const uint8_t* gk = reinterpret_cast<const uint8_t*>(g_k + head * 4096);
            const uint8_t* gv = reinterpret_cast<const uint8_t*>(g_v + head * 4096);
#pragma unroll 1
            for (int c = 0; c < 8; c++) {
                if (!(c & 1)) mbar_wait(bars + 8 * (c ? B_AFREE + (c >> 1) : B_AFREE0), 0);
                if (elect_one()) {
                    const uint32_t b = bars + 8 * (B_KV + c);
                    mbar_expect(b, 16384);
                    bulk_load(sb + (2 * c + 1) * 4096, gk + c * 8192, 4096, b);
                    bulk_load(sb + 2 * c * 4096, gv + c * 4096, 4096, b);
                    bulk_load(sb + 65536 + c * 4096, gv + 32768 + c * 4096, 4096, b);
                    bulk_load(sb + 98304 + c * 4096, gk + c * 8192 + 4096, 4096, b);
                }
            }
        } else if (wq == 2) {
#pragma unroll 1
            for (int t = 0; t < 5; t++) {
                mbar_wait(bars + 8 * (B_TILE + t), 0);
                if (elect_one()) signal_cnt(t < nq ? C_QKV + qt0 + t : C_H + mblk);
            }
        }
        bar_sync(5, 128);
        const int cb = blockIdx.x & 7, pr = blockIdx.x >> 3;
        const int rb0 = (pr >> 2) * 8 + (pr & 3);
        uint32_t gate[2][16];
        {
            float dn[64];
            auto load_stage = [&](int kb, int st) {
                const uint32_t b = bars + 8 * (B_RING + st), dst = ring + st * 24576;
                mbar_expect(b, 24576);
                bulk_load(dst, g_h + (rb0 * 28 + kb) * 512, 8192, b);
                bulk_load(dst + 8192, g_h + ((rb0 + 4) * 28 + kb) * 512, 8192, b);
                tma2d(dst + 16384, &mw2, cb * 64, kb * 64, b);
            };
            if (wq == 0) {
                wait_cnt(C_H + (rb0 >> 1), 28 * tag, 200);
                wait_cnt(C_H + (rb0 >> 1) + 2, 28 * tag, 200);
                if (elect_one()) { TSTAMP(20); fence_async_all(); load_stage(0, 0); load_stage(1, 1); }
            }
            int st = 0; uint32_t ph = 0;
#pragma unroll 1
            for (int kb = 0; kb < 28; kb++) {
                mbar_wait(bars + 8 * (B_RING + st), ph);
                const uint64_t da = mkdesc(OFF_RING + st * 24576, 128, 1024, 0), db = mkdesc(OFF_RING + st * 24576 + 16384, 8192, 1024, 1);
                wg_fence();
#pragma unroll
                for (int k = 0; k < 4; k++) { wgmma_ss_n64(dn, da + k * 16, db + k * 128, (kb | k) != 0); wgmma_ss_n64(dn + 32, da + 512 + k * 16, db + k * 128, (kb | k) != 0); }
                wg_commit();
                wg_wait<1>();
                if (wq == 0 && kb < 26 && elect_one()) load_stage(kb + 2, st == 0 ? 2 : st - 1);
                if (++st == 3) { st = 0; ph ^= 1; }
            }
            wg_wait<0>();
            pin<64>(dn);
#pragma unroll
            for (int i = 0; i < 32; i++) gate[i >> 4][i & 15] = pack_bf16(siluf(dn[2 * i]), siluf(dn[2 * i + 1]));
        }
        float acc[32];
        if (tid == 512) TSTAMP(21);
        const uint32_t bar_wo = bars + 8 * B_WO;
        if (wq == 0 && elect_one()) {
            mbar_expect(bar_wo, 65536);
#pragma unroll 1
            for (int i = 0; i < 8; i++) tma2d(ring + i * 8192, &mwo, cb * 64, i * 64, bar_wo);
        }
        if (wq >= 2) {
            mbar_wait(bars + 8 * (B_OW + wq - 2), 0);
            if (elect_one()) {
                signal_cnt(C_O + qb * 8 + 2 * wq - 4);
                asm volatile("red.relaxed.gpu.global.add.u32 [%0], 1;" :: "l"(g_cnt + (C_O + qb * 8 + 2 * wq - 3) * 8) : "memory");
            }
        }
#pragma unroll
        for (int tl = 0; tl < 2; tl++) {
            const int rb = rb0 + 4 * tl;
            uint32_t xr[16];
            const uint32_t* px = reinterpret_cast<const uint32_t*>(x + (size_t)(rb * 64 + wq * 16 + g) * DM + cb * 64) + t4;
#pragma unroll
            for (int j = 0; j < 8; j++) { xr[2 * j] = __ldg(px + j * 4); xr[2 * j + 1] = __ldg(px + 8 * DM / 2 + j * 4); }
            if (wq == 0) {
                if (tl == 1) mbar_wait(bars + 8 * B_DONE, 0);
                wait_cnt(C_O + rb, 32 * tag, tl ? 20 : 200);
                if (elect_one()) {
                    fence_async_all();
                    TSTAMP(22 + 2 * tl);
#pragma unroll 1
                    for (int i = 0; i < (tl ? 8 : 2); i++) {
                        mbar_expect(bars + 8 * (B_O + i), 8192);
                        bulk_load((tl ? sb : ring + 65536) + i * 8192, g_o + (rb * 8 + i) * 512, 8192, bars + 8 * (B_O + i));
                    }
                }
            }
            if (tl == 0) mbar_wait(bar_wo, 0);
#pragma unroll 1
            for (int kb = 0; kb < 8; kb++) {
                mbar_wait(bars + 8 * (B_O + kb), tl);
                const uint32_t a = tl == 0 ? OFF_RING + 65536 + (kb & 1) * 8192 : kb * 8192;
                const uint64_t da = mkdesc(a, 128, 1024, 0), db = mkdesc(OFF_RING + kb * 8192, 8192, 1024, 1);
                wg_fence();
#pragma unroll
                for (int k = 0; k < 4; k++) wgmma_ss_n64(acc, da + k * 16, db + k * 128, (kb | k) != 0);
                wg_commit();
                if (tl == 0) {
                    wg_wait<0>();
                    bar_sync(5, 128);
                    if (wq == 0 && kb < 6 && elect_one()) { mbar_expect(bars + 8 * (B_O + kb + 2), 8192); bulk_load(sb + a, g_o + (rb * 8 + kb + 2) * 512, 8192, bars + 8 * (B_O + kb + 2)); }
                }
            }
            wg_wait<0>();
            pin<32>(acc);
            uint32_t* po = reinterpret_cast<uint32_t*>(out + (size_t)(rb * 64 + wq * 16 + g) * DM + cb * 64) + t4;
#pragma unroll
            for (int i = 0; i < 16; i++) {
                const uint32_t r = pack_bf16(fmaf(acc[2 * i], bf_lo(gate[tl][i]), bf_lo(xr[i])), fmaf(acc[2 * i + 1], bf_hi(gate[tl][i]), bf_hi(xr[i])));
                po[(i & 1) * (8 * DM / 2) + (i >> 1) * 4] = r;
            }
            if (tid == 512) TSTAMP(23 + 2 * tl);
        }
    }
}

typedef CUresult (*EncodeFn)(CUtensorMap*, CUtensorMapDataType, cuuint32_t, void*, const cuuint64_t*, const cuuint64_t*, const cuuint32_t*,
                             const cuuint32_t*, CUtensorMapInterleave, CUtensorMapSwizzle, CUtensorMapL2promotion, CUtensorMapFloatOOBfill);

void make_map(EncodeFn fn, CUtensorMap* m, const void* p, int rows, int cols, int box_rows) {
    cuuint64_t dims[2] = {(cuuint64_t)cols, (cuuint64_t)rows};
    cuuint64_t strides[1] = {(cuuint64_t)cols * 2};
    cuuint32_t box[2] = {64, (cuuint32_t)box_rows};
    cuuint32_t es[2] = {1, 1};
    fn(m, CU_TENSOR_MAP_DATA_TYPE_BFLOAT16, 2, const_cast<void*>(p), dims, strides, box, es, CU_TENSOR_MAP_INTERLEAVE_NONE,
       CU_TENSOR_MAP_SWIZZLE_128B, CU_TENSOR_MAP_L2_PROMOTION_L2_128B, CU_TENSOR_MAP_FLOAT_OOB_FILL_NONE);
}

}

extern "C" void kernel_launch(void* const* d_in, const int* in_sizes, int n_in, void* d_out, int out_size) {
    const __nv_bfloat16* x = (const __nv_bfloat16*)d_in[0];
    static EncodeFn fn = nullptr;
    if (!fn) {
        cudaDriverEntryPointQueryResult qr;
        cudaGetDriverEntryPoint("cuTensorMapEncodeTiled", (void**)&fn, cudaEnableDefault, &qr);
        cudaFuncSetAttribute(mega_kernel, cudaFuncAttributeMaxDynamicSharedMemorySize, SMEM_BYTES);
    }
    CUtensorMap mx, mqkv, mw1, mw3, mw2, mwo;
    make_map(fn, &mx, d_in[0], SEQ, DM, 128);
    make_map(fn, &mqkv, d_in[1], DM, 3 * DM, 64);
    make_map(fn, &mwo, d_in[2], DM, DM, 64);
    make_map(fn, &mw1, d_in[4], DM, FF, 64);
    make_map(fn, &mw3, d_in[5], DM, FF, 64);
    make_map(fn, &mw2, d_in[6], FF, DM, 64);
    mega_kernel<<<128, 640, SMEM_BYTES, cudaStreamPerThread>>>(x, (const __nv_bfloat16*)d_in[1], (const __nv_bfloat16*)d_in[4], (const __nv_bfloat16*)d_in[5],
                                                               (__nv_bfloat16*)d_out, mx, mqkv, mw1, mw3, mw2, mwo, 0x3F003F00u);
}
```

```cpp
#include <cuda_runtime.h>
#include <cuda_bf16.h>
#include <cuda.h>
#include <stdint.h>

namespace {

constexpr int SEQ = 2048, DM = 512, FF = 1792;

__device__ uint4 g_q[32 * 128 * 32];
__device__ uint4 g_k[32 * 4096];
__device__ uint4 g_v[32 * 4096];
__device__ uint4 g_h[32 * 28 * 512];
__device__ uint4 g_o[32 * 8 * 512];
__device__ ulonglong2 g_cs[40 * 8 * 64];
__device__ ulonglong2 g_rs[SEQ / 2];
constexpr int C_QKV = 0, C_H = 12, C_O = 28, C_NUM = 60;
__device__ unsigned g_cnt[C_NUM * 8];
__device__ unsigned g_epoch[128];
#define TSTAMP(i)
#define TS2(k, i)

__device__ __forceinline__ uint32_t smem_u32(const void* p) { return (uint32_t)__cvta_generic_to_shared(p); }
__device__ __forceinline__ void mbar_init(uint32_t a, int c) { asm volatile("mbarrier.init.shared::cta.b64 [%0], %1;" :: "r"(a), "r"(c)); }
__device__ __forceinline__ void mbar_expect(uint32_t a, int b) { asm volatile("mbarrier.arrive.expect_tx.shared::cta.b64 _, [%0], %1;" :: "r"(a), "r"(b) : "memory"); }
__device__ __forceinline__ void mbar_arrive(uint32_t a) { asm volatile("mbarrier.arrive.shared::cta.b64 _, [%0];" :: "r"(a) : "memory"); }
__device__ __forceinline__ void mbar_arrive_remote(uint32_t a) { asm volatile("mbarrier.arrive.shared::cluster.b64 _, [%0];" :: "r"(a) : "memory"); }
__device__ __forceinline__ bool mbar_try(uint32_t a, uint32_t ph) {
    uint32_t ok;
    asm volatile("{\n.reg .pred p;\nmbarrier.try_wait.parity.shared::cta.b64 p, [%1], %2;\nselp.u32 %0, 1, 0, p;\n}" : "=r"(ok) : "r"(a), "r"(ph) : "memory");
    return ok;
}
__device__ __forceinline__ void mbar_wait(uint32_t a, uint32_t ph) {
    int n = 1 << 22;
#pragma unroll 1
    do { n = __all_sync(0xffffffffu, mbar_try(a, ph)) ? 0 : n - 1; } while (n > 0);
}
__device__ __forceinline__ bool elect_one() {
    uint32_t p;
    asm volatile("{\n.reg .pred P;\nelect.sync _|P, 0xffffffff;\nselp.u32 %0, 1, 0, P;\n}" : "=r"(p));
    return p;
}
__device__ __forceinline__ void signal_cnt(int c) {
    asm volatile("fence.acq_rel.gpu;\nred.relaxed.gpu.global.add.u32 [%0], 1;" :: "l"(g_cnt + c * 8) : "memory");
}
__device__ __forceinline__ void wait_cnt(int c, unsigned target, int ns) {
#pragma unroll 1
    for (int n = 0; n < 2000000; n++) {
        unsigned v;
        asm volatile("ld.acquire.gpu.global.u32 %0, [%1];" : "=r"(v) : "l"(g_cnt + c * 8) : "memory");
        if (__all_sync(0xffffffffu, (int)(v - target) >= 0)) break;
        __nanosleep(ns);
    }
}
__device__ __forceinline__ void st_tagged(void* p, uint32_t v, uint32_t tag) {
    asm volatile("st.relaxed.gpu.global.b64 [%0], %1;" :: "l"(p), "l"((unsigned long long)tag << 32 | v) : "memory");
}
__device__ __forceinline__ uint32_t ld_tagged2(const ulonglong2* p, uint32_t tag, uint32_t& a, uint32_t& b) {
    unsigned long long u, v;
    asm volatile("ld.relaxed.gpu.global.v2.b64 {%0,%1}, [%2];" : "=l"(u), "=l"(v) : "l"(p) : "memory");
    a = (uint32_t)u; b = (uint32_t)v;
    return ((uint32_t)(u >> 32) ^ tag) | ((uint32_t)(v >> 32) ^ tag);
}
__device__ __forceinline__ void tma2d(uint32_t dst, const CUtensorMap* m, int c0, int c1, uint32_t bar) {
    asm volatile("cp.async.bulk.tensor.2d.shared::cluster.global.mbarrier::complete_tx::bytes [%0], [%1, {%3, %4}], [%2];"
                 :: "r"(dst), "l"(m), "r"(bar), "r"(c0), "r"(c1) : "memory");
}
__device__ __forceinline__ void tma2d_mc(uint32_t dst, const CUtensorMap* m, int c0, int c1, uint32_t bar) {
    asm volatile("cp.async.bulk.tensor.2d.shared::cluster.global.mbarrier::complete_tx::bytes.multicast::cluster [%0], [%1, {%3, %4}], [%2], %5;"
                 :: "r"(dst), "l"(m), "r"(bar), "r"(c0), "r"(c1), "h"((uint16_t)3) : "memory");
}
__device__ __forceinline__ void bulk_load(uint32_t dst, const void* src, int bytes, uint32_t bar) {
    asm volatile("cp.async.bulk.shared::cluster.global.mbarrier::complete_tx::bytes [%0], [%1], %2, [%3];"
                 :: "r"(dst), "l"(src), "r"(bytes), "r"(bar) : "memory");
}
__device__ __forceinline__ void bar_sync(int id, int n) { asm volatile("bar.sync %0, %1;" :: "r"(id), "r"(n) : "memory"); }
__device__ __forceinline__ void fence_async_smem() { asm volatile("fence.proxy.async.shared::cta;" ::: "memory"); }
__device__ __forceinline__ void fence_async_all() { asm volatile("fence.proxy.async;" ::: "memory"); }
__device__ __forceinline__ void wg_fence() { asm volatile("wgmma.fence.sync.aligned;" ::: "memory"); }
__device__ __forceinline__ void wg_commit() { asm volatile("wgmma.commit_group.sync.aligned;" ::: "memory"); }
template <int N> __device__ __forceinline__ void wg_wait() { asm volatile("wgmma.wait_group.sync.aligned %0;" :: "n"(N) : "memory"); }
template <int N> __device__ __forceinline__ void pin(float* d) {
#pragma unroll
    for (int i = 0; i < N; i++) asm volatile("" : "+f"(d[i]) :: "memory");
}
template <int N> __device__ __forceinline__ void pin(uint32_t* d) {
#pragma unroll
    for (int i = 0; i < N; i++) asm volatile("" : "+r"(d[i]) :: "memory");
}
constexpr uint32_t SMEM_BASE = 1024;
__device__ __forceinline__ uint64_t mkdesc(uint32_t off, uint32_t lbo, uint32_t sbo, uint32_t swz) {
    return (uint64_t)((SMEM_BASE + off) >> 4) | ((uint64_t)(lbo >> 4) << 16) | ((uint64_t)(sbo >> 4) << 32) | ((uint64_t)swz << 62);
}
__device__ __forceinline__ float ex2f(float x) { float y; asm("ex2.approx.ftz.f32 %0, %1;" : "=f"(y) : "f"(x)); return y; }
__device__ __forceinline__ float rcpf(float x) { float y; asm("rcp.approx.ftz.f32 %0, %1;" : "=f"(y) : "f"(x)); return y; }
__device__ __forceinline__ uint32_t pack_bf16(float lo, float hi) { uint32_t r; asm("cvt.rn.bf16x2.f32 %0, %1, %2;" : "=r"(r) : "f"(hi), "f"(lo)); return r; }
__device__ __forceinline__ float bf_lo(uint32_t v) { return __uint_as_float(v << 16); }
__device__ __forceinline__ float bf_hi(uint32_t v) { return __uint_as_float(v & 0xFFFF0000u); }
__device__ __forceinline__ float bf_round(float x) { return __bfloat162float(__float2bfloat16_rn(x)); }
__device__ __forceinline__ float siluf(float g) { return g * rcpf(1.0f + ex2f(g * -1.4426950408889634f)); }

__device__ __forceinline__ void wgmma_ss_n256(float* d, uint64_t da, uint64_t db, int acc) {
    asm volatile("{\n.reg .pred p;\nsetp.ne.b32 p, %130, 0;\nwgmma.mma_async.sync.aligned.m64n256k16.f32.bf16.bf16 {"
        "%0,%1,%2,%3,%4,%5,%6,%7,%8,%9,%10,%11,%12,%13,%14,%15,%16,%17,%18,%19,%20,%21,%22,%23,%24,%25,%26,%27,%28,%29,%30,%31,%32,%33,%34,%35,%36,%37,%38,%39,"
        "%40,%41,%42,%43,%44,%45,%46,%47,%48,%49,%50,%51,%52,%53,%54,%55,%56,%57,%58,%59,%60,%61,%62,%63,%64,%65,%66,%67,%68,%69,%70,%71,%72,%73,%74,%75,%76,"
        "%77,%78,%79,%80,%81,%82,%83,%84,%85,%86,%87,%88,%89,%90,%91,%92,%93,%94,%95,%96,%97,%98,%99,%100,%101,%102,%103,%104,%105,%106,%107,%108,%109,%110,"
        "%111,%112,%113,%114,%115,%116,%117,%118,%119,%120,%121,%122,%123,%124,%125,%126,%127"
        "}, %128, %129, p, 1, 1, 0, 1;\n}\n"
        : "+f"(d[0]),"+f"(d[1]),"+f"(d[2]),"+f"(d[3]),"+f"(d[4]),"+f"(d[5]),"+f"(d[6]),"+f"(d[7]),"+f"(d[8]),"+f"(d[9]),"+f"(d[10]),"+f"(d[11]),"+f"(d[12]),
          "+f"(d[13]),"+f"(d[14]),"+f"(d[15]),"+f"(d[16]),"+f"(d[17]),"+f"(d[18]),"+f"(d[19]),"+f"(d[20]),"+f"(d[21]),"+f"(d[22]),"+f"(d[23]),"+f"(d[24]),
          "+f"(d[25]),"+f"(d[26]),"+f"(d[27]),"+f"(d[28]),"+f"(d[29]),"+f"(d[30]),"+f"(d[31]),"+f"(d[32]),"+f"(d[33]),"+f"(d[34]),"+f"(d[35]),"+f"(d[36]),
          "+f"(d[37]),"+f"(d[38]),"+f"(d[39]),"+f"(d[40]),"+f"(d[41]),"+f"(d[42]),"+f"(d[43]),"+f"(d[44]),"+f"(d[45]),"+f"(d[46]),"+f"(d[47]),"+f"(d[48]),
          "+f"(d[49]),"+f"(d[50]),"+f"(d[51]),"+f"(d[52]),"+f"(d[53]),"+f"(d[54]),"+f"(d[55]),"+f"(d[56]),"+f"(d[57]),"+f"(d[58]),"+f"(d[59]),"+f"(d[60]),
          "+f"(d[61]),"+f"(d[62]),"+f"(d[63]),"+f"(d[64]),"+f"(d[65]),"+f"(d[66]),"+f"(d[67]),"+f"(d[68]),"+f"(d[69]),"+f"(d[70]),"+f"(d[71]),"+f"(d[72]),
          "+f"(d[73]),"+f"(d[74]),"+f"(d[75]),"+f"(d[76]),"+f"(d[77]),"+f"(d[78]),"+f"(d[79]),"+f"(d[80]),"+f"(d[81]),"+f"(d[82]),"+f"(d[83]),"+f"(d[84]),
          "+f"(d[85]),"+f"(d[86]),"+f"(d[87]),"+f"(d[88]),"+f"(d[89]),"+f"(d[90]),"+f"(d[91]),"+f"(d[92]),"+f"(d[93]),"+f"(d[94]),"+f"(d[95]),"+f"(d[96]),
          "+f"(d[97]),"+f"(d[98]),"+f"(d[99]),"+f"(d[100]),"+f"(d[101]),"+f"(d[102]),"+f"(d[103]),"+f"(d[104]),"+f"(d[105]),"+f"(d[106]),"+f"(d[107]),
          "+f"(d[108]),"+f"(d[109]),"+f"(d[110]),"+f"(d[111]),"+f"(d[112]),"+f"(d[113]),"+f"(d[114]),"+f"(d[115]),"+f"(d[116]),"+f"(d[117]),"+f"(d[118]),
          "+f"(d[119]),"+f"(d[120]),"+f"(d[121]),"+f"(d[122]),"+f"(d[123]),"+f"(d[124]),"+f"(d[125]),"+f"(d[126]),"+f"(d[127])
        : "l"(da), "l"(db), "r"(acc));
}
__device__ __forceinline__ void wgmma_ss_n128(float* d, uint64_t da, uint64_t db, int acc) {
    asm volatile("{\n.reg .pred p;\nsetp.ne.b32 p, %66, 0;\nwgmma.mma_async.sync.aligned.m64n128k16.f32.bf16.bf16 {"
        "%0,%1,%2,%3,%4,%5,%6,%7,%8,%9,%10,%11,%12,%13,%14,%15,%16,%17,%18,%19,%20,%21,%22,%23,%24,%25,%26,%27,%28,%29,%30,%31,%32,%33,%34,%35,%36,%37,%38,%39,"
        "%40,%41,%42,%43,%44,%45,%46,%47,%48,%49,%50,%51,%52,%53,%54,%55,%56,%57,%58,%59,%60,%61,%62,%63"
        "}, %64, %65, p, 1, 1, 0, 1;\n}\n"
        : "+f"(d[0]),"+f"(d[1]),"+f"(d[2]),"+f"(d[3]),"+f"(d[4]),"+f"(d[5]),"+f"(d[6]),"+f"(d[7]),"+f"(d[8]),"+f"(d[9]),"+f"(d[10]),"+f"(d[11]),"+f"(d[12]),
          "+f"(d[13]),"+f"(d[14]),"+f"(d[15]),"+f"(d[16]),"+f"(d[17]),"+f"(d[18]),"+f"(d[19]),"+f"(d[20]),"+f"(d[21]),"+f"(d[22]),"+f"(d[23]),"+f"(d[24]),
          "+f"(d[25]),"+f"(d[26]),"+f"(d[27]),"+f"(d[28]),"+f"(d[29]),"+f"(d[30]),"+f"(d[31]),"+f"(d[32]),"+f"(d[33]),"+f"(d[34]),"+f"(d[35]),"+f"(d[36]),
          "+f"(d[37]),"+f"(d[38]),"+f"(d[39]),"+f"(d[40]),"+f"(d[41]),"+f"(d[42]),"+f"(d[43]),"+f"(d[44]),"+f"(d[45]),"+f"(d[46]),"+f"(d[47]),"+f"(d[48]),
          "+f"(d[49]),"+f"(d[50]),"+f"(d[51]),"+f"(d[52]),"+f"(d[53]),"+f"(d[54]),"+f"(d[55]),"+f"(d[56]),"+f"(d[57]),"+f"(d[58]),"+f"(d[59]),"+f"(d[60]),
          "+f"(d[61]),"+f"(d[62]),"+f"(d[63])
        : "l"(da), "l"(db), "r"(acc));
}
__device__ __forceinline__ void wgmma_ss_n64(float* d, uint64_t da, uint64_t db, int acc) {
    asm volatile("{\n.reg .pred p;\nsetp.ne.b32 p, %34, 0;\nwgmma.mma_async.sync.aligned.m64n64k16.f32.bf16.bf16 {"
        "%0,%1,%2,%3,%4,%5,%6,%7,%8,%9,%10,%11,%12,%13,%14,%15,%16,%17,%18,%19,%20,%21,%22,%23,%24,%25,%26,%27,%28,%29,%30,%31"
        "}, %32, %33, p, 1, 1, 0, 1;\n}\n"
        : "+f"(d[0]),"+f"(d[1]),"+f"(d[2]),"+f"(d[3]),"+f"(d[4]),"+f"(d[5]),"+f"(d[6]),"+f"(d[7]),"+f"(d[8]),"+f"(d[9]),"+f"(d[10]),"+f"(d[11]),"+f"(d[12]),
          "+f"(d[13]),"+f"(d[14]),"+f"(d[15]),"+f"(d[16]),"+f"(d[17]),"+f"(d[18]),"+f"(d[19]),"+f"(d[20]),"+f"(d[21]),"+f"(d[22]),"+f"(d[23]),"+f"(d[24]),
          "+f"(d[25]),"+f"(d[26]),"+f"(d[27]),"+f"(d[28]),"+f"(d[29]),"+f"(d[30]),"+f"(d[31])
        : "l"(da), "l"(db), "r"(acc));
}
__device__ __forceinline__ void wgmma_rs_n64_zero(float* d, const uint32_t* a, uint64_t db) {
    asm volatile("wgmma.mma_async.sync.aligned.m64n64k16.f32.bf16.bf16 {"
        "%0,%1,%2,%3,%4,%5,%6,%7,%8,%9,%10,%11,%12,%13,%14,%15,%16,%17,%18,%19,%20,%21,%22,%23,%24,%25,%26,%27,%28,%29,%30,%31"
        "}, {%32,%33,%34,%35}, %36, 0, 1, 1, 0;\n"
        : "=f"(d[0]),"=f"(d[1]),"=f"(d[2]),"=f"(d[3]),"=f"(d[4]),"=f"(d[5]),"=f"(d[6]),"=f"(d[7]),"=f"(d[8]),"=f"(d[9]),"=f"(d[10]),"=f"(d[11]),"=f"(d[12]),
          "=f"(d[13]),"=f"(d[14]),"=f"(d[15]),"=f"(d[16]),"=f"(d[17]),"=f"(d[18]),"=f"(d[19]),"=f"(d[20]),"=f"(d[21]),"=f"(d[22]),"=f"(d[23]),"=f"(d[24]),
          "=f"(d[25]),"=f"(d[26]),"=f"(d[27]),"=f"(d[28]),"=f"(d[29]),"=f"(d[30]),"=f"(d[31])
        : "r"(a[0]), "r"(a[1]), "r"(a[2]), "r"(a[3]), "l"(db));
}
__device__ __forceinline__ void wgmma_rs_n64_acc(float* d, const uint32_t* a, uint64_t db) {
    asm volatile("wgmma.mma_async.sync.aligned.m64n64k16.f32.bf16.bf16 {"
        "%0,%1,%2,%3,%4,%5,%6,%7,%8,%9,%10,%11,%12,%13,%14,%15,%16,%17,%18,%19,%20,%21,%22,%23,%24,%25,%26,%27,%28,%29,%30,%31"
        "}, {%32,%33,%34,%35}, %36, 1, 1, 1, 0;\n"
        : "+f"(d[0]),"+f"(d[1]),"+f"(d[2]),"+f"(d[3]),"+f"(d[4]),"+f"(d[5]),"+f"(d[6]),"+f"(d[7]),"+f"(d[8]),"+f"(d[9]),"+f"(d[10]),"+f"(d[11]),"+f"(d[12]),
          "+f"(d[13]),"+f"(d[14]),"+f"(d[15]),"+f"(d[16]),"+f"(d[17]),"+f"(d[18]),"+f"(d[19]),"+f"(d[20]),"+f"(d[21]),"+f"(d[22]),"+f"(d[23]),"+f"(d[24]),
          "+f"(d[25]),"+f"(d[26]),"+f"(d[27]),"+f"(d[28]),"+f"(d[29]),"+f"(d[30]),"+f"(d[31])
        : "r"(a[0]), "r"(a[1]), "r"(a[2]), "r"(a[3]), "l"(db));
}
__device__ __forceinline__ void wgmma_rs_n24_acc(float* d, const uint32_t* a, uint64_t db) {
    asm volatile("wgmma.mma_async.sync.aligned.m64n24k16.f32.bf16.bf16 {"
        "%0,%1,%2,%3,%4,%5,%6,%7,%8,%9,%10,%11"
        "}, {%12,%13,%14,%15}, %16, 1, 1, 1, 1;\n"
        : "+f"(d[0]),"+f"(d[1]),"+f"(d[2]),"+f"(d[3]),"+f"(d[4]),"+f"(d[5]),"+f"(d[6]),"+f"(d[7]),"+f"(d[8]),"+f"(d[9]),"+f"(d[10]),"+f"(d[11])
        : "r"(a[0]), "r"(a[1]), "r"(a[2]), "r"(a[3]), "l"(db));
}
__device__ __forceinline__ void wgmma_rs_n24_zero(float* d, const uint32_t* a, uint64_t db) {
    asm volatile("wgmma.mma_async.sync.aligned.m64n24k16.f32.bf16.bf16 {"
        "%0,%1,%2,%3,%4,%5,%6,%7,%8,%9,%10,%11"
        "}, {%12,%13,%14,%15}, %16, 0, 1, 1, 1;\n"
        : "=f"(d[0]),"=f"(d[1]),"=f"(d[2]),"=f"(d[3]),"=f"(d[4]),"=f"(d[5]),"=f"(d[6]),"=f"(d[7]),"=f"(d[8]),"=f"(d[9]),"=f"(d[10]),"=f"(d[11])
        : "r"(a[0]), "r"(a[1]), "r"(a[2]), "r"(a[3]), "l"(db));
}

constexpr int OFF_ONES = 131072;
constexpr int OFF_RING = OFF_ONES + 4096;
constexpr int NRING = 5;
constexpr int OFF_B2 = OFF_RING + NRING * 16384;
constexpr int OFF_CS = OFF_B2 + 2048;
constexpr int OFF_RS = OFF_CS + 2560;
constexpr int OFF_BAR = OFF_RS + 1024;
enum { B_FULL = 0, B_STATS = 40, B_KV = 45, B_RING = 53, B_WO = 56, B_O = 57, B_CNT2 = 65,
       B_AFREE = 65, B_ORD = 69, B_QKV = 74, B_CNT4 = 75, B_EMPTY = 75, B_AFREE0 = 80, B_DONE = 81, B_CNT8 = 82, B_TILE = 82, B_OW = 87, B_NUM = 100 };
constexpr int OFF_TS = OFF_BAR + 1024;
constexpr int SMEM_BYTES = OFF_BAR + B_NUM * 8;
constexpr unsigned FIXED_MASK = 0xB5;
constexpr float P71 = 2361183241434822606848.0f, M71 = 4.235164736271502e-22f;

__device__ __forceinline__ uint32_t exp2_fixed(float lo, float hi, uint32_t half2) {
    uint32_t y, g, d;
    asm("cvt.pack.sat.s16.s32 %0, %1, %2;" : "=r"(y) : "r"(__float_as_uint(hi)), "r"(__float_as_uint(lo)));
    asm("lop3.b32 %0, %1, 0x007F007F, %2, 0xEA;" : "=r"(g) : "r"(y), "r"(half2));
    asm("fma.rn.bf16x2 %0, %1, %2, %3;" : "=r"(d) : "r"(y), "r"(g), "r"(y & 0xFF80FF80u));
    return d;
}
__device__ __forceinline__ uint32_t k_tile_addr(uint32_t base, int tile) {
    const int c = tile >> 2;
    return base + ((tile & 2) ? 98304 + c * 4096 : (2 * c + 1) * 4096) + (tile & 1) * 2048;
}
constexpr uint32_t POS_STD = 0x76543210u, POS_LAST = 0xB75A9640u;

__global__ void __cluster_dims__(2, 1, 1) __launch_bounds__(640, 1)
mega_kernel(const __nv_bfloat16* __restrict__ x, const __nv_bfloat16* __restrict__ wqkv, const __nv_bfloat16* __restrict__ w1,
            const __nv_bfloat16* __restrict__ w3, __nv_bfloat16* __restrict__ out,
            const __grid_constant__ CUtensorMap mx, const __grid_constant__ CUtensorMap mqkv, const __grid_constant__ CUtensorMap mw1,
            const __grid_constant__ CUtensorMap mw3, const __grid_constant__ CUtensorMap mw2, const __grid_constant__ CUtensorMap mwo,
            uint32_t half2) {
    extern __shared__ __align__(1024) uint8_t smem_raw[];
    const uint32_t sb = __shfl_sync(0xffffffffu, smem_u32(smem_raw), 0);
    if ((sb & 0xFFFFFF) != SMEM_BASE) __trap();
    const uint32_t bars = sb + OFF_BAR, ring = sb + OFF_RING;
    const int tid = threadIdx.x, lane = tid & 31, g = lane >> 2, t4 = lane & 3;
    const int warp = __shfl_sync(0xffffffffu, tid >> 5, 0), wg = warp >> 2, wq = warp & 3;
    const int rank = blockIdx.x & 1, cl = blockIdx.x >> 1;
    const int grp = cl < 4 ? 4 + cl : cl < 36 ? (cl - 4) >> 3 : 4 + (cl - 36) / 7;
    const int rot = cl < 4 ? 7 : cl < 36 ? (cl - 4) & 7 : (cl - 36) % 7;
    const int mblk = rot * 2 + rank;
    const int nq = grp < 4 ? 2 : 1;
    const int qt0 = grp < 4 ? 2 * grp : 4 + grp;
    const int gu0 = (grp < 4 ? 3 * grp : 4 * grp - 4) - nq;
    const int head = blockIdx.x >> 2, qb = blockIdx.x & 3;

    if (elect_one()) {
#pragma unroll
        for (int i = 0; i < 5; i++) { const int b = warp * 5 + i; mbar_init(bars + 8 * b, b < B_CNT2 ? 1 : b < B_CNT4 ? 2 : b < B_CNT8 ? 4 : 8); }
        if (warp == 0) {
            fence_async_smem();
#pragma unroll
            for (int j = 0; j < 2; j++) {
                tma2d(sb + j * 16384, &mx, j * 64, mblk * 128, bars + 8 * (B_FULL + j));
                tma2d(ring + j * 16384, &mqkv, qt0 * 128, j * 64, bars + 8 * (B_FULL + j));
                tma2d(ring + j * 16384 + 8192, &mqkv, qt0 * 128 + 64, j * 64, bars + 8 * (B_FULL + j));
            }
        }
        if (warp < 8) {
#pragma unroll
            for (int i = 0; i < 5; i++) mbar_expect(bars + 8 * (warp * 5 + i), warp * 5 + i < 8 ? 32768 : 16384);
        }
        if (warp == 16) asm volatile("prefetch.tensormap [%0];" :: "l"(rank ? &mw3 : &mw1) : "memory");
        asm volatile("fence.mbarrier_init.release.cluster;" ::: "memory");
    }
    const uint32_t tag = __ldcg(g_epoch + blockIdx.x) + 1;
    __syncthreads();
    if (tid == 512) TSTAMP(26);
    asm volatile("barrier.cluster.arrive.relaxed.aligned;" ::: "memory");

    if (wg < 4) {
        const int pair = wg >> 1, half = wg & 1;
        if (pair == 1) {
            const int row = mblk * 128 + grp * 16 + (warp - 8) * 2 + (lane >> 4);
            uint4 v[8];
            const uint32_t* w = reinterpret_cast<const uint32_t*>(v);
            const __nv_bfloat16* src; int ld;
            if (half < nq) { src = wqkv + (qt0 + half) * 128 + rank * 64; ld = 3 * DM; }
            else           { src = (rank ? w3 : w1) + (gu0 + half) * 64; ld = FF; }
            src += (size_t)(rot * 64 + (lane >> 1)) * ld + wq * 16 + (lane & 1) * 8;
#pragma unroll
            for (int j = 0; j < 4; j++) v[4 + j] = __ldg(reinterpret_cast<const uint4*>(src + (size_t)j * 16 * ld));
#pragma unroll
            for (int j = 0; j < 4; j++) v[j] = __ldg(reinterpret_cast<const uint4*>(x + (size_t)row * DM) + j * 16 + (lane & 15));
            float c[8];
#pragma unroll
            for (int e = 0; e < 4; e++) {
                c[2 * e] = (bf_lo(w[16 + e]) + bf_lo(w[20 + e])) + (bf_lo(w[24 + e]) + bf_lo(w[28 + e]));
                c[2 * e + 1] = (bf_hi(w[16 + e]) + bf_hi(w[20 + e])) + (bf_hi(w[24 + e]) + bf_hi(w[28 + e]));
            }
#pragma unroll
            for (int n = 4; n > 0; n >>= 1) {
                const bool up = lane & (4 * n);
#pragma unroll
                for (int e = 0; e < n; e++) c[e] = (up ? c[e + n] : c[e]) + __shfl_xor_sync(0xffffffffu, up ? c[e] : c[e + n], 4 * n);
            }
            c[0] += __shfl_xor_sync(0xffffffffu, c[0], 2);
            if (!(lane & 2)) st_tagged(reinterpret_cast<unsigned long long*>(g_cs) + ((grp * 5 + half) * 8 + rot) * 128 + rank * 64 + wq * 16 + (lane & 1) * 8 + g, __float_as_uint(c[0]), tag);
            float s0 = 0.f, v0 = 0.f;
#pragma unroll
            for (int j = 0; j < 16; j++) s0 += bf_lo(w[j]) + bf_hi(w[j]);
#pragma unroll
            for (int d = 1; d < 16; d <<= 1) s0 += __shfl_xor_sync(0xffffffffu, s0, d);
            const float mean = s0 * (1.0f / DM);
#pragma unroll
            for (int j = 0; j < 16; j++) { const float a = bf_lo(w[j]) - mean, b = bf_hi(w[j]) - mean; v0 += fmaf(a, a, b * b); }
#pragma unroll
            for (int d = 1; d < 16; d <<= 1) v0 += __shfl_xor_sync(0xffffffffu, v0, d);
            if ((lane & 15) == 0) st_tagged(reinterpret_cast<unsigned long long*>(g_rs) + row, pack_bf16(mean, sqrtf(bf_round(bf_round(v0 * (1.0f / DM)) + 1e-5f))), tag);
        }
        asm volatile("barrier.cluster.wait.aligned;" ::: "memory");

        uint32_t q[4], qn[6];
        {
            float acc[64];
            const int rowblk = mblk * 2 + half, tile16 = rowblk * 4 + wq;
            const bool rel = wq < 2 && lane == 0, rel2 = wq == 2 && lane == 0;
            uint32_t empty;
            asm("mapa.shared::cluster.u32 %0, %1, %2;" : "=r"(empty) : "r"(bars + 8 * B_EMPTY), "r"(wq & 1));
#pragma unroll 1
            for (int t = pair; t < 5; t += 2) {
                uint32_t po = t == 4 ? POS_LAST : POS_STD, full = bars + 8 * (B_FULL + 8 * t), slot = (0x24130u >> (4 * t)) & 7, prev = 0;
                if (tid == 0 && t == 0) TSTAMP(30);
                if (t > 0) mbar_wait(bars + 8 * (B_ORD + t - 1), 0);
#pragma unroll 1
                for (int j = 0; j < 8; j++) {
                    const uint64_t da = mkdesc(half * 8192, 16, 1024, 1) + (po & 7) * 1024, db = mkdesc(OFF_RING, 8192, 1024, 1) + slot * 1024;
                    mbar_wait(full, 0);
                    if (wq == 3 && half == 0 && lane == 0) TS2(1, t * 8 + j);
                    wg_fence();
#pragma unroll
                    for (int k = 0; k < 4; k++) wgmma_ss_n128(acc, da + k * 2, db + k * 128, (j | k) != 0);
                    wg_commit();
                    if (j == 7 && rel2) mbar_arrive(bars + 8 * (B_ORD + t));
                    wg_wait<1>();
                    if (wq == 3 && half == 0 && lane == 0) TS2(2, t * 8 + j);
                    if (j > 0 && rel) mbar_arrive_remote(empty + prev * 8);
                    if ((po & 8) && rel2) mbar_arrive(bars + 8 * (j == 3 ? B_AFREE0 : B_AFREE + (j >> 1) - 1));
                    prev = slot; slot = slot == NRING - 1 ? 0 : slot + 1; po >>= 4; full += 8;
                }
                if (t >= 3) {
                    mbar_wait(bars + 8 * B_QKV, 0);
                    const uint4* pq = g_q + (head * 128 + (qb * 8 + wg) * 4 + wq) * 32 + lane;
                    const uint4 v = __ldcg(pq), u = __ldcg(pq + 512);
                    qn[0] = v.x; qn[1] = v.y; qn[2] = v.z; qn[3] = v.w; q[0] = u.x; q[1] = u.y; q[2] = u.z; q[3] = u.w;
                }
                wg_wait<0>();
                if (rel) mbar_arrive_remote(empty + prev * 8);
                if (t >= 3 && rel2) mbar_arrive(bars + 8 * (t == 4 ? B_AFREE + 3 : B_AFREE0));
                pin<64>(acc);
                if (wq == 0 && half == 0 && lane == 0) TSTAMP(2 + 2 * t);
                mbar_wait(bars + 8 * (B_STATS + (t >= 2)), 0);
                uint32_t rs0, rs1;
                asm volatile("ld.shared.b32 %0, [%1];" : "=r"(rs0) : "r"(sb + OFF_RS + (half * 64 + wq * 16 + g) * 4));
                asm volatile("ld.shared.b32 %0, [%1];" : "=r"(rs1) : "r"(sb + OFF_RS + (half * 64 + wq * 16 + g + 8) * 4));
                const float m0 = bf_lo(rs0), m1 = bf_lo(rs1);
                float d0 = bf_hi(rs0), d1 = bf_hi(rs1);
#pragma unroll
                for (int j = 0; j < 16; j++) {
                    float c0, c1;
                    asm volatile("ld.shared.v2.f32 {%0,%1}, [%2];" : "=f"(c0), "=f"(c1) : "r"(sb + OFF_CS + (t * 128 + j * 8 + t4 * 2) * 4));
                    acc[4 * j] = fmaf(-m0, c0, acc[4 * j]); acc[4 * j + 1] = fmaf(-m0, c1, acc[4 * j + 1]);
                    acc[4 * j + 2] = fmaf(-m1, c0, acc[4 * j + 2]); acc[4 * j + 3] = fmaf(-m1, c1, acc[4 * j + 3]);
                }
                float r0 = __frcp_rn(d0), r1 = __frcp_rn(d1);
                if (t < nq) {
                    const int qt = qt0 + t, h0 = (qt & 3) * 8;
                    if (qt < 4) {
                        r0 *= 0.25f * 1.4426950408889634f * M71; r1 *= 0.25f * 1.4426950408889634f * M71;
                    } else if (qt < 8) {
                        r0 *= ((FIXED_MASK >> (2 * wq)) & 1) ? M71 : P71; r1 *= ((FIXED_MASK >> (2 * wq + 1)) & 1) ? M71 : P71;
                    }
                    uint32_t* p; int s8, sh;
                    if (qt < 8) { p = reinterpret_cast<uint32_t*>(g_k + h0 * 4096) + tile16 * 128 + lane; s8 = 64; sh = 32; }
                    else        { p = reinterpret_cast<uint32_t*>(g_v + h0 * 4096) + tile16 * 64 + lane;  s8 = 32; sh = 8192; }
#pragma unroll
                    for (int hh = 0; hh < 8; hh++) {
                        const float* a = acc + hh * 8;
                        const uint32_t e0 = pack_bf16(a[0] * r0, a[1] * r0), e1 = pack_bf16(a[2] * r1, a[3] * r1);
                        const uint32_t e2 = pack_bf16(a[4] * r0, a[5] * r0), e3 = pack_bf16(a[6] * r1, a[7] * r1);
                        if (qt < 4) g_q[((h0 + hh) * 128 + tile16) * 32 + lane] = make_uint4(e0, e1, e2, e3);
                        else { uint32_t* pp = p + hh * 16384; pp[0] = e0; pp[s8] = e1; pp[sh] = e2; pp[sh + s8] = e3; }
                    }
                } else {
                    uint32_t* p = reinterpret_cast<uint32_t*>(g_h + (rowblk * 28 + gu0 + t) * 512) + wq * 512 + lane;
                    r0 *= -1.4426950408889634f; r1 *= -1.4426950408889634f; d0 *= d0; d1 *= d1;
#pragma unroll
                    for (int j = 0; j < 8; j++) {
                        const float* a = acc + j * 4; const float* b = a + 32;
                        p[j * 32] = pack_bf16(a[0] * b[0] * rcpf(fmaf(ex2f(a[0] * r0), d0, d0)), a[1] * b[1] * rcpf(fmaf(ex2f(a[1] * r0), d0, d0)));
                        p[256 + j * 32] = pack_bf16(a[2] * b[2] * rcpf(fmaf(ex2f(a[2] * r1), d1, d1)), a[3] * b[3] * rcpf(fmaf(ex2f(a[3] * r1), d1, d1)));
                    }
                }
                __syncwarp();
                if (elect_one()) mbar_arrive(bars + 8 * (B_TILE + t));
                if (wq == 0 && half == 0 && lane == 0) TSTAMP(3 + 2 * t);
            }
        }
        const uint64_t db2 = mkdesc(OFF_B2, 128, 256, 0);
        float s[32];
        auto ref_point = [&](int ntile, uint32_t& b0, uint32_t& b1) {
            float m0 = -INFINITY, m1 = -INFINITY, f0 = -INFINITY, f1 = -INFINITY;
#pragma unroll 1
            for (int t = 0; t < ntile; t++) {
                wg_fence();
                wgmma_rs_n64_zero(s, q, mkdesc(k_tile_addr(0, t), 128, 256, 0));
                wg_commit();
                wg_wait<0>();
                pin<32>(s);
#pragma unroll
                for (int i = 0; i < 8; i++) {
                    if ((FIXED_MASK >> i) & 1) { f0 = fmaxf(f0, fmaxf(s[4 * i], s[4 * i + 1])); f1 = fmaxf(f1, fmaxf(s[4 * i + 2], s[4 * i + 3])); }
                    else                       { m0 = fmaxf(m0, fmaxf(s[4 * i], s[4 * i + 1])); m1 = fmaxf(m1, fmaxf(s[4 * i + 2], s[4 * i + 3])); }
                }
            }
            m0 = fmaxf(m0, f0 * P71 * P71); m1 = fmaxf(m1, f1 * P71 * P71);
            m0 = fmaxf(m0, __shfl_xor_sync(0xffffffffu, m0, 1)); m1 = fmaxf(m1, __shfl_xor_sync(0xffffffffu, m1, 1));
            m0 = fmaxf(m0, __shfl_xor_sync(0xffffffffu, m0, 2)); m1 = fmaxf(m1, __shfl_xor_sync(0xffffffffu, m1, 2));
#pragma unroll
            for (int r = 0; r < 2; r++) {
                const float m = -rintf(r ? m1 : m0), mh = bf_round(m), mm = bf_round(m - mh), ml = m - mh - mm;
                const float lo = t4 == 0 ? mh : t4 == 1 ? ml : t4 == 2 ? 1.f : 0.f, hi = t4 == 0 ? mm : t4 == 1 ? 1.f : 0.f;
                (r ? b1 : b0) = pack_bf16(lo * M71, hi * M71);
            }
        };
        uint32_t q2[4];
        int redo = 1;
        mbar_wait(bars + 8 * B_KV, 0);
#pragma unroll 1
        for (int round = -1; round < 2;) {
            if (redo) ref_point(redo, q2[0], q2[1]);
            if (round < 0) {
#pragma unroll
                for (int i = 0; i < 4; i++) { const uint32_t tq = q[i]; q[i] = qn[i]; qn[i] = tq; }
                qn[4] = q2[0]; qn[5] = q2[1];
                q2[2] = __shfl_sync(0xffffffffu, q2[0], 3); q2[3] = __shfl_sync(0xffffffffu, q2[1], 3);
                round = 0;
                continue;
            }
            float o[12]; uint32_t p[16];
#pragma unroll
            for (int i = 0; i < 12; i++) o[i] = 0.f;
            pin<12>(o); pin<4>(q2);
            if (wq == 0 && half == 0 && lane == 0) TSTAMP(12 + 4 * round + pair);
            uint64_t dk0 = mkdesc(4096, 128, 256, 0), dk1 = mkdesc(98304, 128, 256, 0), dv = mkdesc(0, 128, 65536, 0);
#pragma unroll 1
            for (int c = 0; c < 8; c++, dk0 += 512, dk1 += 256, dv += 512 - (256ull << 32)) {
                if (round == 0) mbar_wait(bars + 8 * (B_KV + c), 0);
#pragma unroll
                for (int t = 0; t < 4; t++) {
                    wg_fence();
                    wgmma_rs_n64_zero(s, q, (t & 2 ? dk1 : dk0) + (t & 1) * 128);
                    wgmma_rs_n64_acc(s, q2, db2);
                    wg_commit();
                    wg_wait<0>();
                    pin<32>(s); pin<16>(p);
#pragma unroll
                    for (int i = 0; i < 16; i++) {
                        if ((FIXED_MASK >> (i >> 1)) & 1) p[i] = exp2_fixed(s[2 * i], s[2 * i + 1], half2);
                        else                              p[i] = pack_bf16(ex2f(s[2 * i]), ex2f(s[2 * i + 1]));
                    }
                    wg_fence();
#pragma unroll
                    for (int k = 0; k < 4; k++) wgmma_rs_n24_acc(o, p + 4 * k, dv + (t * 4 + k) * 16);
                    wg_commit();
                }
            }
            wg_wait<0>();
            pin<12>(o);
            if (redo != 32) {
                float chk = (o[8] + o[10]) * 256.f;
#pragma unroll
                for (int i = 0; i < 8; i++) chk += fabsf(o[i]);
                uint32_t bad;
                asm volatile("{\n.reg .pred p, q;\nsetp.geu.f32 q, %1, 0f7F800000;\nbar.red.or.pred p, %2, 128, q;\nselp.u32 %0, 1, 0, p;\n}" : "=r"(bad) : "f"(chk), "r"(1 + wg) : "memory");
                if (__any_sync(0xffffffffu, bad)) { redo = 32; continue; }
            }
            const int rowblk = qb * 8 + round * 4 + wg;
            const float r0 = rcpf(o[8]), r1 = rcpf(o[10]);
            uint32_t* po = reinterpret_cast<uint32_t*>(g_o + (rowblk * 8 + (head >> 2)) * 512) + wq * 512 + (head & 3) * 64 + lane;
            po[0] = pack_bf16(o[0] * r0, o[1] * r0); po[256] = pack_bf16(o[2] * r1, o[3] * r1);
            po[32] = pack_bf16(o[4] * r0, o[5] * r0); po[288] = pack_bf16(o[6] * r1, o[7] * r1);
            if (round == 0) {
                __syncwarp();
                if (elect_one()) mbar_arrive(bars + 8 * (B_OW + pair));
            } else {
                bar_sync(1 + wg, 128);
                if (wq == 0 && elect_one()) { mbar_arrive(bars + 8 * B_DONE); signal_cnt(C_O + rowblk); }
            }
#pragma unroll
            for (int i = 0; i < 4; i++) q[i] = qn[i];
            q2[0] = qn[4]; q2[1] = qn[5];
            redo = 0;
            if (wq == 0 && half == 0 && lane == 0) TSTAMP(14 + 4 * round + pair);
            round++;
        }
    } else {
        asm volatile("barrier.cluster.wait.aligned;" ::: "memory");
        if (tid == 512) TSTAMP(27);
        if (wq == 0) {
            uint32_t slot = 2, ph = 1;
#pragma unroll 1
            for (int n = 2; n < 40; n++) {
                const int t = n >> 3, j = n & 7;
                const int kc = (n < 32 ? j : (POS_LAST >> (4 * j)) & 7) * 64;
                const CUtensorMap* m = t < nq ? &mqkv : rank ? &mw3 : &mw1;
                const int col = t < nq ? (qt0 + t) * 128 + rank * 64 : (gu0 + t) * 64;
                const uint32_t dst = ring + slot * 16384 + rank * 8192, fb = bars + 8 * (B_FULL + n);
                if (n < 8 && elect_one()) tma2d(sb + n * 16384, &mx, kc, mblk * 128, fb);
                mbar_wait(bars + 8 * (B_EMPTY + slot), ph);
                if (elect_one()) { TS2(0, n); tma2d_mc(dst, m, col, kc, fb); }
                if (++slot == NRING) { slot = 0; ph ^= 1; }
            }
        } else {
            auto gather = [&](int t) {
                float a[4];
#pragma unroll 1
                for (int n = 0; n < 2000000; n++) {
                    uint32_t stale = 0;
                    a[0] = a[1] = a[2] = a[3] = 0.f;
#pragma unroll
                    for (int i = 0; i < 16; i++) {
                        uint32_t u, v;
                        stale |= ld_tagged2(g_cs + (grp * 5 + t) * 512 + i * 32 + lane, tag, u, v);
                        a[(i & 1) * 2] += __uint_as_float(u); a[(i & 1) * 2 + 1] += __uint_as_float(v);
                    }
                    if (__all_sync(0xffffffffu, stale == 0)) break;
                }
                asm volatile("st.shared.v2.f32 [%0], {%1,%2};" :: "r"(sb + OFF_CS + t * 512 + lane * 8), "f"(a[0]), "f"(a[1]) : "memory");
                asm volatile("st.shared.v2.f32 [%0], {%1,%2};" :: "r"(sb + OFF_CS + t * 512 + 256 + lane * 8), "f"(a[2]), "f"(a[3]) : "memory");
            };
            mbar_wait(bars + 8 * (B_FULL + 1), 0);
            if (wq == 3) {
                uint32_t a, b, c, d;
#pragma unroll 1
                for (int n = 0; n < 2000000; n++) {
                    const uint32_t stale = ld_tagged2(g_rs + mblk * 64 + lane * 2, tag, a, b) | ld_tagged2(g_rs + mblk * 64 + lane * 2 + 1, tag, c, d);
                    if (__all_sync(0xffffffffu, stale == 0)) break;
                }
                asm volatile("st.shared.v4.b32 [%0], {%1,%2,%3,%4};" :: "r"(sb + OFF_RS + lane * 16), "r"(a), "r"(b), "r"(c), "r"(d) : "memory");
            }
#pragma unroll 1
            for (int pass = 0; pass < 2; pass++) {
                const int t = pass ? wq + 1 : wq - 1;
                if (pass || wq < 3) gather(t);
                bar_sync(6, 96);
                if (wq == 1 && elect_one()) { mbar_arrive(bars + 8 * (B_STATS + pass)); TSTAMP(pass ? 31 : 28); }
                if (pass) break;
                const __nv_bfloat16* src = (rank ? w3 : w1) + (gu0 + wq + 1) * 64 + (size_t)(rot * 64 + (lane >> 3)) * FF + (lane & 7) * 8;
                uint4 v[16];
                const uint32_t* w = reinterpret_cast<const uint32_t*>(v);
#pragma unroll
                for (int j = 0; j < 16; j++) v[j] = __ldg(reinterpret_cast<const uint4*>(src + (size_t)j * 4 * FF));
                float c[8];
#pragma unroll
                for (int e = 0; e < 4; e++) {
                    float a = 0.f, b = 0.f;
#pragma unroll
                    for (int j = 0; j < 16; j++) { a += bf_lo(w[4 * j + e]); b += bf_hi(w[4 * j + e]); }
                    c[2 * e] = a; c[2 * e + 1] = b;
                }
#pragma unroll
                for (int n = 4; n > 1; n >>= 1) {
                    const bool up = lane & (4 * n);
#pragma unroll
                    for (int e = 0; e < n; e++) c[e] = (up ? c[e + n] : c[e]) + __shfl_xor_sync(0xffffffffu, up ? c[e] : c[e + n], 4 * n);
                }
                unsigned long long* dst = reinterpret_cast<unsigned long long*>(g_cs) + ((grp * 5 + wq + 1) * 8 + rot) * 128 + rank * 64 + (lane & 7) * 8 + (lane >> 3) * 2;
                st_tagged(dst, __float_as_uint(c[0]), tag); st_tagged(dst + 1, __float_as_uint(c[1]), tag);
            }
        }
        if (wq == 3) {
            if (lane == 0) g_epoch[blockIdx.x] = tag;
#pragma unroll 1
            for (int i = lane; i < 256; i += 32) asm volatile("st.shared.v4.b32 [%0], {%1,%1,%1,%1};" :: "r"(sb + OFF_ONES + i * 16), "r"(0x3F803F80u) : "memory");
#pragma unroll 1
            for (int i = lane; i < 128; i += 32) {
                const bool fx = (FIXED_MASK >> (i >> 4)) & 1;
                uint32_t a = fx ? pack_bf16(M71, M71) : pack_bf16(P71, P71);
                uint32_t b = fx ? pack_bf16(M71, 47.0f * M71) : pack_bf16(P71, -79.5f * P71);
                uint32_t c = fx ? 0u : pack_bf16(0.08214f * P71, 0.f);
                if (i & 8) a = b = c = 0;
                asm volatile("st.shared.v4.b32 [%0], {%1,%2,%3,%4};" :: "r"(sb + OFF_B2 + i * 16), "r"(a), "r"(b), "r"(c), "r"(0) : "memory");
            }
            fence_async_smem();
            __syncwarp();
            if (elect_one()) mbar_arrive(bars + 8 * B_QKV);
        } else if (wq == 1) {
#pragma unroll 1
            for (int i = 0; i < 3; i++) wait_cnt(C_QKV + i * 4 + (head >> 3), 16 * tag, 100);
            if (elect_one()) { mbar_arrive(bars + 8 * B_QKV); TSTAMP(29); }
            fence_async_all();
            const uint8_t* gk = reinterpret_cast<const uint8_t*>(g_k + head * 4096);
            const uint8_t* gv = reinterpret_cast<const uint8_t*>(g_v + head * 4096);
#pragma unroll 1
            for (int c = 0; c < 8; c++) {
                if (!(c & 1)) mbar_wait(bars + 8 * (c ? B_AFREE + (c >> 1) : B_AFREE0), 0);
                if (elect_one()) {
                    const uint32_t b = bars + 8 * (B_KV + c);
                    mbar_expect(b, 16384);
                    bulk_load(sb + (2 * c + 1) * 4096, gk + c * 8192, 4096, b);
                    bulk_load(sb + 2 * c * 4096, gv + c * 4096, 4096, b);
                    bulk_load(sb + 65536 + c * 4096, gv + 32768 + c * 4096, 4096, b);
                    bulk_load(sb + 98304 + c * 4096, gk + c * 8192 + 4096, 4096, b);
                }
            }
        } else if (wq == 2) {
#pragma unroll 1
            for (int t = 0; t < 5; t++) {
                mbar_wait(bars + 8 * (B_TILE + t), 0);
                if (elect_one()) signal_cnt(t < nq ? C_QKV + qt0 + t : C_H + mblk);
            }
        }
        bar_sync(5, 128);
        const int cb = blockIdx.x & 7, pr = blockIdx.x >> 3;
        const int rb0 = (pr >> 2) * 8 + (pr & 3);
        uint32_t gate[2][16];
        {
            float dn[64];
            auto load_stage = [&](int kb, int st) {
                const uint32_t b = bars + 8 * (B_RING + st), dst = ring + st * 24576;
                mbar_expect(b, 24576);
                bulk_load(dst, g_h + (rb0 * 28 + kb) * 512, 8192, b);
                bulk_load(dst + 8192, g_h + ((rb0 + 4) * 28 + kb) * 512, 8192, b);
                tma2d(dst + 16384, &mw2, cb * 64, kb * 64, b);
            };
            if (wq == 0) {
                wait_cnt(C_H + (rb0 >> 1), 28 * tag, 200);
                wait_cnt(C_H + (rb0 >> 1) + 2, 28 * tag, 200);
                if (elect_one()) { TSTAMP(20); fence_async_all(); load_stage(0, 0); load_stage(1, 1); }
            }
            int st = 0; uint32_t ph = 0;
#pragma unroll 1
            for (int kb = 0; kb < 28; kb++) {
                mbar_wait(bars + 8 * (B_RING + st), ph);
                const uint64_t da = mkdesc(OFF_RING + st * 24576, 128, 1024, 0), db = mkdesc(OFF_RING + st * 24576 + 16384, 8192, 1024, 1);
                wg_fence();
#pragma unroll
                for (int k = 0; k < 4; k++) { wgmma_ss_n64(dn, da + k * 16, db + k * 128, (kb | k) != 0); wgmma_ss_n64(dn + 32, da + 512 + k * 16, db + k * 128, (kb | k) != 0); }
                wg_commit();
                wg_wait<1>();
                if (wq == 0 && kb < 26 && elect_one()) load_stage(kb + 2, st == 0 ? 2 : st - 1);
                if (++st == 3) { st = 0; ph ^= 1; }
            }
            wg_wait<0>();
            pin<64>(dn);
#pragma unroll
            for (int i = 0; i < 32; i++) gate[i >> 4][i & 15] = pack_bf16(siluf(dn[2 * i]), siluf(dn[2 * i + 1]));
        }
        float acc[32];
        if (tid == 512) TSTAMP(21);
        const uint32_t bar_wo = bars + 8 * B_WO;
        if (wq == 0 && elect_one()) {
            mbar_expect(bar_wo, 65536);
#pragma unroll 1
            for (int i = 0; i < 8; i++) tma2d(ring + i * 8192, &mwo, cb * 64, i * 64, bar_wo);
        }
        if (wq >= 2) {
            mbar_wait(bars + 8 * (B_OW + wq - 2), 0);
            if (elect_one()) {
                signal_cnt(C_O + qb * 8 + 2 * wq - 4);
                asm volatile("red.relaxed.gpu.global.add.u32 [%0], 1;" :: "l"(g_cnt + (C_O + qb * 8 + 2 * wq - 3) * 8) : "memory");
            }
        }
#pragma unroll 1
        for (int tl = 0; tl < 2; tl++) {
            const int rb = rb0 + 4 * tl;
            uint32_t xr[16];
            const uint32_t* px = reinterpret_cast<const uint32_t*>(x + (size_t)(rb * 64 + wq * 16 + g) * DM + cb * 64) + t4;
#pragma unroll
            for (int j = 0; j < 8; j++) { xr[2 * j] = __ldg(px + j * 4); xr[2 * j + 1] = __ldg(px + 8 * DM / 2 + j * 4); }
            if (wq == 0) {
                if (tl == 1) mbar_wait(bars + 8 * B_DONE, 0);
                wait_cnt(C_O + rb, 32 * tag, tl ? 20 : 200);
                if (elect_one()) {
                    fence_async_all();
                    TSTAMP(22 + 2 * tl);
#pragma unroll 1
                    for (int i = 0; i < (tl ? 8 : 2); i++) {
                        mbar_expect(bars + 8 * (B_O + i), 8192);
                        bulk_load((tl ? sb : ring + 65536) + i * 8192, g_o + (rb * 8 + i) * 512, 8192, bars + 8 * (B_O + i));
                    }
                }
            }
            if (tl == 0) mbar_wait(bar_wo, 0);
#pragma unroll 1
            for (int kb = 0; kb < 8; kb++) {
                mbar_wait(bars + 8 * (B_O + kb), tl);
                const uint32_t a = tl == 0 ? OFF_RING + 65536 + (kb & 1) * 8192 : kb * 8192;
                const uint64_t da = mkdesc(a, 128, 1024, 0), db = mkdesc(OFF_RING + kb * 8192, 8192, 1024, 1);
                wg_fence();
#pragma unroll
                for (int k = 0; k < 4; k++) wgmma_ss_n64(acc, da + k * 16, db + k * 128, (kb | k) != 0);
                wg_commit();
                if (tl == 0) {
                    wg_wait<0>();
                    bar_sync(5, 128);
                    if (wq == 0 && kb < 6 && elect_one()) { mbar_expect(bars + 8 * (B_O + kb + 2), 8192); bulk_load(sb + a, g_o + (rb * 8 + kb + 2) * 512, 8192, bars + 8 * (B_O + kb + 2)); }
                }
            }
            wg_wait<0>();
            pin<32>(acc);
            uint32_t* po = reinterpret_cast<uint32_t*>(out + (size_t)(rb * 64 + wq * 16 + g) * DM + cb * 64) + t4;
#pragma unroll
            for (int i = 0; i < 16; i++) {
                const uint32_t r = pack_bf16(fmaf(acc[2 * i], bf_lo(gate[0][i]), bf_lo(xr[i])), fmaf(acc[2 * i + 1], bf_hi(gate[0][i]), bf_hi(xr[i])));
                po[(i & 1) * (8 * DM / 2) + (i >> 1) * 4] = r;
                gate[0][i] = gate[1][i];
            }
            if (tid == 512) TSTAMP(23 + 2 * tl);
        }
    }
}

typedef CUresult (*EncodeFn)(CUtensorMap*, CUtensorMapDataType, cuuint32_t, void*, const cuuint64_t*, const cuuint64_t*, const cuuint32_t*,
                             const cuuint32_t*, CUtensorMapInterleave, CUtensorMapSwizzle, CUtensorMapL2promotion, CUtensorMapFloatOOBfill);

void make_map(EncodeFn fn, CUtensorMap* m, const void* p, int rows, int cols, int box_rows) {
    cuuint64_t dims[2] = {(cuuint64_t)cols, (cuuint64_t)rows};
    cuuint64_t strides[1] = {(cuuint64_t)cols * 2};
    cuuint32_t box[2] = {64, (cuuint32_t)box_rows};
    cuuint32_t es[2] = {1, 1};
    fn(m, CU_TENSOR_MAP_DATA_TYPE_BFLOAT16, 2, const_cast<void*>(p), dims, strides, box, es, CU_TENSOR_MAP_INTERLEAVE_NONE,
       CU_TENSOR_MAP_SWIZZLE_128B, CU_TENSOR_MAP_L2_PROMOTION_L2_128B, CU_TENSOR_MAP_FLOAT_OOB_FILL_NONE);
}

}

extern "C" void kernel_launch(void* const* d_in, const int* in_sizes, int n_in, void* d_out, int out_size) {
    const __nv_bfloat16* x = (const __nv_bfloat16*)d_in[0];
    static EncodeFn fn = nullptr;
    if (!fn) {
        cudaDriverEntryPointQueryResult qr;
        cudaGetDriverEntryPoint("cuTensorMapEncodeTiled", (void**)&fn, cudaEnableDefault, &qr);
        cudaFuncSetAttribute(mega_kernel, cudaFuncAttributeMaxDynamicSharedMemorySize, SMEM_BYTES);
    }
    CUtensorMap mx, mqkv, mw1, mw3, mw2, mwo;
    make_map(fn, &mx, d_in[0], SEQ, DM, 128);
    make_map(fn, &mqkv, d_in[1], DM, 3 * DM, 64);
    make_map(fn, &mwo, d_in[2], DM, DM, 64);
    make_map(fn, &mw1, d_in[4], DM, FF, 64);
    make_map(fn, &mw3, d_in[5], DM, FF, 64);
    make_map(fn, &mw2, d_in[6], FF, DM, 64);
    mega_kernel<<<128, 640, SMEM_BYTES, cudaStreamPerThread>>>(x, (const __nv_bfloat16*)d_in[1], (const __nv_bfloat16*)d_in[4], (const __nv_bfloat16*)d_in[5],
                                                               (__nv_bfloat16*)d_out, mx, mqkv, mw1, mw3, mw2, mwo, 0x3F003F00u);
}
```

```cpp
#include <cuda_runtime.h>
#include <cuda_bf16.h>
#include <cuda.h>
#include <stdint.h>

namespace {

constexpr int SEQ = 2048, DM = 512, FF = 1792;

__device__ uint4 g_q[32 * 128 * 32];
__device__ uint4 g_k[32 * 4096];
__device__ uint4 g_v[32 * 4096];
__device__ uint4 g_h[32 * 28 * 512];
__device__ uint4 g_o[32 * 8 * 512];
__device__ ulonglong2 g_cs[40 * 8 * 64];
__device__ ulonglong2 g_rs[SEQ / 2];
constexpr int C_QKV = 0, C_H = 12, C_O = 28, C_NUM = 60;
__device__ unsigned g_cnt[C_NUM * 8];
__device__ unsigned g_epoch[128];
#define TSTAMP(i)
#define TS2(k, i)

__device__ __forceinline__ uint32_t smem_u32(const void* p) { return (uint32_t)__cvta_generic_to_shared(p); }
__device__ __forceinline__ void mbar_init(uint32_t a, int c) { asm volatile("mbarrier.init.shared::cta.b64 [%0], %1;" :: "r"(a), "r"(c)); }
__device__ __forceinline__ void mbar_expect(uint32_t a, int b) { asm volatile("mbarrier.arrive.expect_tx.shared::cta.b64 _, [%0], %1;" :: "r"(a), "r"(b) : "memory"); }
__device__ __forceinline__ void mbar_arrive(uint32_t a) { asm volatile("mbarrier.arrive.shared::cta.b64 _, [%0];" :: "r"(a) : "memory"); }
__device__ __forceinline__ void mbar_arrive_remote(uint32_t a) { asm volatile("mbarrier.arrive.shared::cluster.b64 _, [%0];" :: "r"(a) : "memory"); }
__device__ __forceinline__ bool mbar_try(uint32_t a, uint32_t ph) {
    uint32_t ok;
    asm volatile("{\n.reg .pred p;\nmbarrier.try_wait.parity.shared::cta.b64 p, [%1], %2;\nselp.u32 %0, 1, 0, p;\n}" : "=r"(ok) : "r"(a), "r"(ph) : "memory");
    return ok;
}
__device__ __forceinline__ void mbar_wait(uint32_t a, uint32_t ph) {
    int n = 1 << 22;
#pragma unroll 1
    do { n = __all_sync(0xffffffffu, mbar_try(a, ph)) ? 0 : n - 1; } while (n > 0);
}
__device__ __forceinline__ bool elect_one() {
    uint32_t p;
    asm volatile("{\n.reg .pred P;\nelect.sync _|P, 0xffffffff;\nselp.u32 %0, 1, 0, P;\n}" : "=r"(p));
    return p;
}
__device__ __forceinline__ void signal_cnt(int c) {
    asm volatile("fence.release.gpu;\nred.relaxed.gpu.global.add.u32 [%0], 1;" :: "l"(g_cnt + c * 8) : "memory");
}
__device__ __forceinline__ void wait_cnt(int c, unsigned target, int ns) {
#pragma unroll 1
    for (int n = 0; n < 2000000; n++) {
        unsigned v;
        asm volatile("ld.relaxed.gpu.global.u32 %0, [%1];" : "=r"(v) : "l"(g_cnt + c * 8) : "memory");
        if (__all_sync(0xffffffffu, (int)(v - target) >= 0)) break;
        __nanosleep(ns);
    }
}
__device__ __forceinline__ void st_tagged(void* p, uint32_t v, uint32_t tag) {
    asm volatile("st.relaxed.gpu.global.b64 [%0], %1;" :: "l"(p), "l"((unsigned long long)tag << 32 | v) : "memory");
}
__device__ __forceinline__ uint32_t ld_tagged2(const ulonglong2* p, uint32_t tag, uint32_t& a, uint32_t& b) {
    unsigned long long u, v;
    asm volatile("ld.relaxed.gpu.global.v2.b64 {%0,%1}, [%2];" : "=l"(u), "=l"(v) : "l"(p) : "memory");
    a = (uint32_t)u; b = (uint32_t)v;
    return ((uint32_t)(u >> 32) ^ tag) | ((uint32_t)(v >> 32) ^ tag);
}
__device__ __forceinline__ void tma2d(uint32_t dst, const CUtensorMap* m, int c0, int c1, uint32_t bar) {
    asm volatile("cp.async.bulk.tensor.2d.shared::cluster.global.mbarrier::complete_tx::bytes [%0], [%1, {%3, %4}], [%2];"
                 :: "r"(dst), "l"(m), "r"(bar), "r"(c0), "r"(c1) : "memory");
}
__device__ __forceinline__ void tma2d_mc(uint32_t dst, const CUtensorMap* m, int c0, int c1, uint32_t bar) {
    asm volatile("cp.async.bulk.tensor.2d.shared::cluster.global.mbarrier::complete_tx::bytes.multicast::cluster [%0], [%1, {%3, %4}], [%2], %5;"
                 :: "r"(dst), "l"(m), "r"(bar), "r"(c0), "r"(c1), "h"((uint16_t)3) : "memory");
}
__device__ __forceinline__ void bulk_load(uint32_t dst, const void* src, int bytes, uint32_t bar) {
    asm volatile("cp.async.bulk.shared::cluster.global.mbarrier::complete_tx::bytes [%0], [%1], %2, [%3];"
                 :: "r"(dst), "l"(src), "r"(bytes), "r"(bar) : "memory");
}
__device__ __forceinline__ void bar_sync(int id, int n) { asm volatile("bar.sync %0, %1;" :: "r"(id), "r"(n) : "memory"); }
__device__ __forceinline__ void fence_async_smem() { asm volatile("fence.proxy.async.shared::cta;" ::: "memory"); }
__device__ __forceinline__ void fence_async_all() { asm volatile("fence.acquire.gpu;\nfence.proxy.async.global;" ::: "memory"); }
__device__ __forceinline__ void wg_fence() { asm volatile("wgmma.fence.sync.aligned;" ::: "memory"); }
__device__ __forceinline__ void wg_commit() { asm volatile("wgmma.commit_group.sync.aligned;" ::: "memory"); }
template <int N> __device__ __forceinline__ void wg_wait() { asm volatile("wgmma.wait_group.sync.aligned %0;" :: "n"(N) : "memory"); }
template <int N> __device__ __forceinline__ void pin(float* d) {
#pragma unroll
    for (int i = 0; i < N; i++) asm volatile("" : "+f"(d[i]) :: "memory");
}
template <int N> __device__ __forceinline__ void pin(uint32_t* d) {
#pragma unroll
    for (int i = 0; i < N; i++) asm volatile("" : "+r"(d[i]) :: "memory");
}
constexpr uint32_t SMEM_BASE = 1024;
__device__ __forceinline__ uint64_t mkdesc(uint32_t off, uint32_t lbo, uint32_t sbo, uint32_t swz) {
    return (uint64_t)((SMEM_BASE + off) >> 4) | ((uint64_t)(lbo >> 4) << 16) | ((uint64_t)(sbo >> 4) << 32) | ((uint64_t)swz << 62);
}
__device__ __forceinline__ float ex2f(float x) { float y; asm("ex2.approx.ftz.f32 %0, %1;" : "=f"(y) : "f"(x)); return y; }
__device__ __forceinline__ float rcpf(float x) { float y; asm("rcp.approx.ftz.f32 %0, %1;" : "=f"(y) : "f"(x)); return y; }
__device__ __forceinline__ uint32_t pack_bf16(float lo, float hi) { uint32_t r; asm("cvt.rn.bf16x2.f32 %0, %1, %2;" : "=r"(r) : "f"(hi), "f"(lo)); return r; }
__device__ __forceinline__ float bf_lo(uint32_t v) { return __uint_as_float(v << 16); }
__device__ __forceinline__ float bf_hi(uint32_t v) { return __uint_as_float(v & 0xFFFF0000u); }
__device__ __forceinline__ float bf_round(float x) { return __bfloat162float(__float2bfloat16_rn(x)); }
__device__ __forceinline__ float siluf(float g) { return g * rcpf(1.0f + ex2f(g * -1.4426950408889634f)); }

__device__ __forceinline__ void wgmma_ss_n256(float* d, uint64_t da, uint64_t db, int acc) {
    asm volatile("{\n.reg .pred p;\nsetp.ne.b32 p, %130, 0;\nwgmma.mma_async.sync.aligned.m64n256k16.f32.bf16.bf16 {"
        "%0,%1,%2,%3,%4,%5,%6,%7,%8,%9,%10,%11,%12,%13,%14,%15,%16,%17,%18,%19,%20,%21,%22,%23,%24,%25,%26,%27,%28,%29,%30,%31,%32,%33,%34,%35,%36,%37,%38,%39,"
        "%40,%41,%42,%43,%44,%45,%46,%47,%48,%49,%50,%51,%52,%53,%54,%55,%56,%57,%58,%59,%60,%61,%62,%63,%64,%65,%66,%67,%68,%69,%70,%71,%72,%73,%74,%75,%76,"
        "%77,%78,%79,%80,%81,%82,%83,%84,%85,%86,%87,%88,%89,%90,%91,%92,%93,%94,%95,%96,%97,%98,%99,%100,%101,%102,%103,%104,%105,%106,%107,%108,%109,%110,"
        "%111,%112,%113,%114,%115,%116,%117,%118,%119,%120,%121,%122,%123,%124,%125,%126,%127"
        "}, %128, %129, p, 1, 1, 0, 1;\n}\n"
        : "+f"(d[0]),"+f"(d[1]),"+f"(d[2]),"+f"(d[3]),"+f"(d[4]),"+f"(d[5]),"+f"(d[6]),"+f"(d[7]),"+f"(d[8]),"+f"(d[9]),"+f"(d[10]),"+f"(d[11]),"+f"(d[12]),
          "+f"(d[13]),"+f"(d[14]),"+f"(d[15]),"+f"(d[16]),"+f"(d[17]),"+f"(d[18]),"+f"(d[19]),"+f"(d[20]),"+f"(d[21]),"+f"(d[22]),"+f"(d[23]),"+f"(d[24]),
          "+f"(d[25]),"+f"(d[26]),"+f"(d[27]),"+f"(d[28]),"+f"(d[29]),"+f"(d[30]),"+f"(d[31]),"+f"(d[32]),"+f"(d[33]),"+f"(d[34]),"+f"(d[35]),"+f"(d[36]),
          "+f"(d[37]),"+f"(d[38]),"+f"(d[39]),"+f"(d[40]),"+f"(d[41]),"+f"(d[42]),"+f"(d[43]),"+f"(d[44]),"+f"(d[45]),"+f"(d[46]),"+f"(d[47]),"+f"(d[48]),
          "+f"(d[49]),"+f"(d[50]),"+f"(d[51]),"+f"(d[52]),"+f"(d[53]),"+f"(d[54]),"+f"(d[55]),"+f"(d[56]),"+f"(d[57]),"+f"(d[58]),"+f"(d[59]),"+f"(d[60]),
          "+f"(d[61]),"+f"(d[62]),"+f"(d[63]),"+f"(d[64]),"+f"(d[65]),"+f"(d[66]),"+f"(d[67]),"+f"(d[68]),"+f"(d[69]),"+f"(d[70]),"+f"(d[71]),"+f"(d[72]),
          "+f"(d[73]),"+f"(d[74]),"+f"(d[75]),"+f"(d[76]),"+f"(d[77]),"+f"(d[78]),"+f"(d[79]),"+f"(d[80]),"+f"(d[81]),"+f"(d[82]),"+f"(d[83]),"+f"(d[84]),
          "+f"(d[85]),"+f"(d[86]),"+f"(d[87]),"+f"(d[88]),"+f"(d[89]),"+f"(d[90]),"+f"(d[91]),"+f"(d[92]),"+f"(d[93]),"+f"(d[94]),"+f"(d[95]),"+f"(d[96]),
          "+f"(d[97]),"+f"(d[98]),"+f"(d[99]),"+f"(d[100]),"+f"(d[101]),"+f"(d[102]),"+f"(d[103]),"+f"(d[104]),"+f"(d[105]),"+f"(d[106]),"+f"(d[107]),
          "+f"(d[108]),"+f"(d[109]),"+f"(d[110]),"+f"(d[111]),"+f"(d[112]),"+f"(d[113]),"+f"(d[114]),"+f"(d[115]),"+f"(d[116]),"+f"(d[117]),"+f"(d[118]),
          "+f"(d[119]),"+f"(d[120]),"+f"(d[121]),"+f"(d[122]),"+f"(d[123]),"+f"(d[124]),"+f"(d[125]),"+f"(d[126]),"+f"(d[127])
        : "l"(da), "l"(db), "r"(acc));
}
__device__ __forceinline__ void wgmma_ss_n128(float* d, uint64_t da, uint64_t db, int acc) {
    asm volatile("{\n.reg .pred p;\nsetp.ne.b32 p, %66, 0;\nwgmma.mma_async.sync.aligned.m64n128k16.f32.bf16.bf16 {"
        "%0,%1,%2,%3,%4,%5,%6,%7,%8,%9,%10,%11,%12,%13,%14,%15,%16,%17,%18,%19,%20,%21,%22,%23,%24,%25,%26,%27,%28,%29,%30,%31,%32,%33,%34,%35,%36,%37,%38,%39,"
        "%40,%41,%42,%43,%44,%45,%46,%47,%48,%49,%50,%51,%52,%53,%54,%55,%56,%57,%58,%59,%60,%61,%62,%63"
        "}, %64, %65, p, 1, 1, 0, 1;\n}\n"
        : "+f"(d[0]),"+f"(d[1]),"+f"(d[2]),"+f"(d[3]),"+f"(d[4]),"+f"(d[5]),"+f"(d[6]),"+f"(d[7]),"+f"(d[8]),"+f"(d[9]),"+f"(d[10]),"+f"(d[11]),"+f"(d[12]),
          "+f"(d[13]),"+f"(d[14]),"+f"(d[15]),"+f"(d[16]),"+f"(d[17]),"+f"(d[18]),"+f"(d[19]),"+f"(d[20]),"+f"(d[21]),"+f"(d[22]),"+f"(d[23]),"+f"(d[24]),
          "+f"(d[25]),"+f"(d[26]),"+f"(d[27]),"+f"(d[28]),"+f"(d[29]),"+f"(d[30]),"+f"(d[31]),"+f"(d[32]),"+f"(d[33]),"+f"(d[34]),"+f"(d[35]),"+f"(d[36]),
          "+f"(d[37]),"+f"(d[38]),"+f"(d[39]),"+f"(d[40]),"+f"(d[41]),"+f"(d[42]),"+f"(d[43]),"+f"(d[44]),"+f"(d[45]),"+f"(d[46]),"+f"(d[47]),"+f"(d[48]),
          "+f"(d[49]),"+f"(d[50]),"+f"(d[51]),"+f"(d[52]),"+f"(d[53]),"+f"(d[54]),"+f"(d[55]),"+f"(d[56]),"+f"(d[57]),"+f"(d[58]),"+f"(d[59]),"+f"(d[60]),
          "+f"(d[61]),"+f"(d[62]),"+f"(d[63])
        : "l"(da), "l"(db), "r"(acc));
}
__device__ __forceinline__ void wgmma_ss_n64(float* d, uint64_t da, uint64_t db, int acc) {
    asm volatile("{\n.reg .pred p;\nsetp.ne.b32 p, %34, 0;\nwgmma.mma_async.sync.aligned.m64n64k16.f32.bf16.bf16 {"
        "%0,%1,%2,%3,%4,%5,%6,%7,%8,%9,%10,%11,%12,%13,%14,%15,%16,%17,%18,%19,%20,%21,%22,%23,%24,%25,%26,%27,%28,%29,%30,%31"
        "}, %32, %33, p, 1, 1, 0, 1;\n}\n"
        : "+f"(d[0]),"+f"(d[1]),"+f"(d[2]),"+f"(d[3]),"+f"(d[4]),"+f"(d[5]),"+f"(d[6]),"+f"(d[7]),"+f"(d[8]),"+f"(d[9]),"+f"(d[10]),"+f"(d[11]),"+f"(d[12]),
          "+f"(d[13]),"+f"(d[14]),"+f"(d[15]),"+f"(d[16]),"+f"(d[17]),"+f"(d[18]),"+f"(d[19]),"+f"(d[20]),"+f"(d[21]),"+f"(d[22]),"+f"(d[23]),"+f"(d[24]),
          "+f"(d[25]),"+f"(d[26]),"+f"(d[27]),"+f"(d[28]),"+f"(d[29]),"+f"(d[30]),"+f"(d[31])
        : "l"(da), "l"(db), "r"(acc));
}
__device__ __forceinline__ void wgmma_rs_n64_zero(float* d, const uint32_t* a, uint64_t db) {
    asm volatile("wgmma.mma_async.sync.aligned.m64n64k16.f32.bf16.bf16 {"
        "%0,%1,%2,%3,%4,%5,%6,%7,%8,%9,%10,%11,%12,%13,%14,%15,%16,%17,%18,%19,%20,%21,%22,%23,%24,%25,%26,%27,%28,%29,%30,%31"
        "}, {%32,%33,%34,%35}, %36, 0, 1, 1, 0;\n"
        : "=f"(d[0]),"=f"(d[1]),"=f"(d[2]),"=f"(d[3]),"=f"(d[4]),"=f"(d[5]),"=f"(d[6]),"=f"(d[7]),"=f"(d[8]),"=f"(d[9]),"=f"(d[10]),"=f"(d[11]),"=f"(d[12]),
          "=f"(d[13]),"=f"(d[14]),"=f"(d[15]),"=f"(d[16]),"=f"(d[17]),"=f"(d[18]),"=f"(d[19]),"=f"(d[20]),"=f"(d[21]),"=f"(d[22]),"=f"(d[23]),"=f"(d[24]),
          "=f"(d[25]),"=f"(d[26]),"=f"(d[27]),"=f"(d[28]),"=f"(d[29]),"=f"(d[30]),"=f"(d[31])
        : "r"(a[0]), "r"(a[1]), "r"(a[2]), "r"(a[3]), "l"(db));
}
__device__ __forceinline__ void wgmma_rs_n64_acc(float* d, const uint32_t* a, uint64_t db) {
    asm volatile("wgmma.mma_async.sync.aligned.m64n64k16.f32.bf16.bf16 {"
        "%0,%1,%2,%3,%4,%5,%6,%7,%8,%9,%10,%11,%12,%13,%14,%15,%16,%17,%18,%19,%20,%21,%22,%23,%24,%25,%26,%27,%28,%29,%30,%31"
        "}, {%32,%33,%34,%35}, %36, 1, 1, 1, 0;\n"
        : "+f"(d[0]),"+f"(d[1]),"+f"(d[2]),"+f"(d[3]),"+f"(d[4]),"+f"(d[5]),"+f"(d[6]),"+f"(d[7]),"+f"(d[8]),"+f"(d[9]),"+f"(d[10]),"+f"(d[11]),"+f"(d[12]),
          "+f"(d[13]),"+f"(d[14]),"+f"(d[15]),"+f"(d[16]),"+f"(d[17]),"+f"(d[18]),"+f"(d[19]),"+f"(d[20]),"+f"(d[21]),"+f"(d[22]),"+f"(d[23]),"+f"(d[24]),
          "+f"(d[25]),"+f"(d[26]),"+f"(d[27]),"+f"(d[28]),"+f"(d[29]),"+f"(d[30]),"+f"(d[31])
        : "r"(a[0]), "r"(a[1]), "r"(a[2]), "r"(a[3]), "l"(db));
}
__device__ __forceinline__ void wgmma_rs_n24_acc(float* d, const uint32_t* a, uint64_t db) {
    asm volatile("wgmma.mma_async.sync.aligned.m64n24k16.f32.bf16.bf16 {"
        "%0,%1,%2,%3,%4,%5,%6,%7,%8,%9,%10,%11"
        "}, {%12,%13,%14,%15}, %16, 1, 1, 1, 1;\n"
        : "+f"(d[0]),"+f"(d[1]),"+f"(d[2]),"+f"(d[3]),"+f"(d[4]),"+f"(d[5]),"+f"(d[6]),"+f"(d[7]),"+f"(d[8]),"+f"(d[9]),"+f"(d[10]),"+f"(d[11])
        : "r"(a[0]), "r"(a[1]), "r"(a[2]), "r"(a[3]), "l"(db));
}
__device__ __forceinline__ void wgmma_rs_n24_zero(float* d, const uint32_t* a, uint64_t db) {
    asm volatile("wgmma.mma_async.sync.aligned.m64n24k16.f32.bf16.bf16 {"
        "%0,%1,%2,%3,%4,%5,%6,%7,%8,%9,%10,%11"
        "}, {%12,%13,%14,%15}, %16, 0, 1, 1, 1;\n"
        : "=f"(d[0]),"=f"(d[1]),"=f"(d[2]),"=f"(d[3]),"=f"(d[4]),"=f"(d[5]),"=f"(d[6]),"=f"(d[7]),"=f"(d[8]),"=f"(d[9]),"=f"(d[10]),"=f"(d[11])
        : "r"(a[0]), "r"(a[1]), "r"(a[2]), "r"(a[3]), "l"(db));
}

constexpr int OFF_ONES = 131072;
constexpr int OFF_RING = OFF_ONES + 4096;
constexpr int NRING = 5;
constexpr int OFF_B2 = OFF_RING + NRING * 16384;
constexpr int OFF_CS = OFF_B2 + 2048;
constexpr int OFF_RS = OFF_CS + 2560;
constexpr int OFF_BAR = OFF_RS + 1024;
enum { B_FULL = 0, B_STATS = 40, B_KV = 45, B_RING = 53, B_WO = 56, B_O = 57, B_CNT2 = 65,
       B_AFREE = 65, B_ORD = 69, B_QKV = 74, B_CNT4 = 75, B_EMPTY = 75, B_AFREE0 = 80, B_DONE = 81, B_CNT8 = 82, B_TILE = 82, B_OW = 87, B_NUM = 100 };
constexpr int OFF_TS = OFF_BAR + 1024;
constexpr int SMEM_BYTES = OFF_BAR + B_NUM * 8;
constexpr unsigned FIXED_MASK = 0xB5;
constexpr float P71 = 2361183241434822606848.0f, M71 = 4.235164736271502e-22f;

__device__ __forceinline__ uint32_t exp2_fixed(float lo, float hi, uint32_t half2) {
    uint32_t y, g, d;
    asm("cvt.pack.sat.s16.s32 %0, %1, %2;" : "=r"(y) : "r"(__float_as_uint(hi)), "r"(__float_as_uint(lo)));
    asm("lop3.b32 %0, %1, 0x007F007F, %2, 0xEA;" : "=r"(g) : "r"(y), "r"(half2));
    asm("fma.rn.bf16x2 %0, %1, %2, %3;" : "=r"(d) : "r"(y), "r"(g), "r"(y & 0xFF80FF80u));
    return d;
}
__device__ __forceinline__ uint32_t k_tile_addr(uint32_t base, int tile) {
    const int c = tile >> 2;
    return base + ((tile & 2) ? 98304 + c * 4096 : (2 * c + 1) * 4096) + (tile & 1) * 2048;
}
constexpr uint32_t POS_STD = 0x76543210u, POS_LAST = 0xB75A9640u;

__global__ void __cluster_dims__(2, 1, 1) __launch_bounds__(640, 1)
mega_kernel(const __nv_bfloat16* __restrict__ x, const __nv_bfloat16* __restrict__ wqkv, const __nv_bfloat16* __restrict__ w1,
            const __nv_bfloat16* __restrict__ w3, __nv_bfloat16* __restrict__ out,
            const __grid_constant__ CUtensorMap mx, const __grid_constant__ CUtensorMap mqkv, const __grid_constant__ CUtensorMap mw1,
            const __grid_constant__ CUtensorMap mw3, const __grid_constant__ CUtensorMap mw2, const __grid_constant__ CUtensorMap mwo,
            uint32_t half2) {
    extern __shared__ __align__(1024) uint8_t smem_raw[];
    const uint32_t sb = __shfl_sync(0xffffffffu, smem_u32(smem_raw), 0);
    if ((sb & 0xFFFFFF) != SMEM_BASE) __trap();
    const uint32_t bars = sb + OFF_BAR, ring = sb + OFF_RING;
    const int tid = threadIdx.x, lane = tid & 31, g = lane >> 2, t4 = lane & 3;
    const int warp = __shfl_sync(0xffffffffu, tid >> 5, 0), wg = warp >> 2, wq = warp & 3;
    const int rank = blockIdx.x & 1, cl = blockIdx.x >> 1;
    const int grp = cl < 4 ? 4 + cl : cl < 36 ? (cl - 4) >> 3 : 4 + (cl - 36) / 7;
    const int rot = cl < 4 ? 7 : cl < 36 ? (cl - 4) & 7 : (cl - 36) % 7;
    const int mblk = rot * 2 + rank;
    const int nq = grp < 4 ? 2 : 1;
    const int qt0 = grp < 4 ? 2 * grp : 4 + grp;
    const int gu0 = (grp < 4 ? 3 * grp : 4 * grp - 4) - nq;
    const int head = blockIdx.x >> 2, qb = blockIdx.x & 3;

    if (elect_one()) {
#pragma unroll
        for (int i = 0; i < 5; i++) { const int b = warp * 5 + i; mbar_init(bars + 8 * b, b < B_CNT2 ? 1 : b < B_CNT4 ? 2 : b < B_CNT8 ? 4 : 8); }
        if (warp == 0) {
            fence_async_smem();
#pragma unroll
            for (int j = 0; j < 2; j++) {
                tma2d(sb + j * 16384, &mx, j * 64, mblk * 128, bars + 8 * (B_FULL + j));
                tma2d(ring + j * 16384, &mqkv, qt0 * 128, j * 64, bars + 8 * (B_FULL + j));
                tma2d(ring + j * 16384 + 8192, &mqkv, qt0 * 128 + 64, j * 64, bars + 8 * (B_FULL + j));
            }
        }
        if (warp < 8) {
#pragma unroll
            for (int i = 0; i < 5; i++) mbar_expect(bars + 8 * (warp * 5 + i), warp * 5 + i < 8 ? 32768 : 16384);
        }
        if (warp == 16) asm volatile("prefetch.tensormap [%0];" :: "l"(rank ? &mw3 : &mw1) : "memory");
        asm volatile("fence.mbarrier_init.release.cluster;" ::: "memory");
    }
    const uint32_t tag = __ldcg(g_epoch + blockIdx.x) + 1;
    __syncthreads();
    if (tid == 512) TSTAMP(26);
    asm volatile("barrier.cluster.arrive.relaxed.aligned;" ::: "memory");

    if (wg < 4) {
        const int pair = wg >> 1, half = wg & 1;
        if (pair == 1) {
            const int row = mblk * 128 + grp * 16 + (warp - 8) * 2 + (lane >> 4);
            uint4 v[8];
            const uint32_t* w = reinterpret_cast<const uint32_t*>(v);
            const __nv_bfloat16* src; int ld;
            if (half < nq) { src = wqkv + (qt0 + half) * 128 + rank * 64; ld = 3 * DM; }
            else           { src = (rank ? w3 : w1) + (gu0 + half) * 64; ld = FF; }
            src += (size_t)(rot * 64 + (lane >> 1)) * ld + wq * 16 + (lane & 1) * 8;
#pragma unroll
            for (int j = 0; j < 4; j++) v[4 + j] = __ldg(reinterpret_cast<const uint4*>(src + (size_t)j * 16 * ld));
#pragma unroll
            for (int j = 0; j < 4; j++) v[j] = __ldg(reinterpret_cast<const uint4*>(x + (size_t)row * DM) + j * 16 + (lane & 15));
            float c[8];
#pragma unroll
            for (int e = 0; e < 4; e++) {
                c[2 * e] = (bf_lo(w[16 + e]) + bf_lo(w[20 + e])) + (bf_lo(w[24 + e]) + bf_lo(w[28 + e]));
                c[2 * e + 1] = (bf_hi(w[16 + e]) + bf_hi(w[20 + e])) + (bf_hi(w[24 + e]) + bf_hi(w[28 + e]));
            }
#pragma unroll
            for (int n = 4; n > 0; n >>= 1) {
                const bool up = lane & (4 * n);
#pragma unroll
                for (int e = 0; e < n; e++) c[e] = (up ? c[e + n] : c[e]) + __shfl_xor_sync(0xffffffffu, up ? c[e] : c[e + n], 4 * n);
            }
            c[0] += __shfl_xor_sync(0xffffffffu, c[0], 2);
            if (!(lane & 2)) st_tagged(reinterpret_cast<unsigned long long*>(g_cs) + ((grp * 5 + half) * 8 + rot) * 128 + rank * 64 + wq * 16 + (lane & 1) * 8 + g, __float_as_uint(c[0]), tag);
            float s0 = 0.f, v0 = 0.f;
#pragma unroll
            for (int j = 0; j < 16; j++) s0 += bf_lo(w[j]) + bf_hi(w[j]);
#pragma unroll
            for (int d = 1; d < 16; d <<= 1) s0 += __shfl_xor_sync(0xffffffffu, s0, d);
            const float mean = s0 * (1.0f / DM);
#pragma unroll
            for (int j = 0; j < 16; j++) { const float a = bf_lo(w[j]) - mean, b = bf_hi(w[j]) - mean; v0 += fmaf(a, a, b * b); }
#pragma unroll
            for (int d = 1; d < 16; d <<= 1) v0 += __shfl_xor_sync(0xffffffffu, v0, d);
            if ((lane & 15) == 0) st_tagged(reinterpret_cast<unsigned long long*>(g_rs) + row, pack_bf16(mean, sqrtf(bf_round(bf_round(v0 * (1.0f / DM)) + 1e-5f))), tag);
        }

        uint32_t q[4], qn[6];
        {
            float acc[64];
            const int rowblk = mblk * 2 + half, tile16 = rowblk * 4 + wq;
            const bool rel = wq < 2 && lane == 0, rel2 = wq == 2 && lane == 0;
            uint32_t empty;
            asm("mapa.shared::cluster.u32 %0, %1, %2;" : "=r"(empty) : "r"(bars + 8 * B_EMPTY), "r"(wq & 1));
#pragma unroll 1
            for (int t = pair; t < 5; t += 2) {
                uint32_t po = t == 4 ? POS_LAST : POS_STD, full = bars + 8 * (B_FULL + 8 * t), slot = (0x24130u >> (4 * t)) & 7, prev = 0;
                if (tid == 0 && t == 0) TSTAMP(30);
                if (t > 0) mbar_wait(bars + 8 * (B_ORD + t - 1), 0);
#pragma unroll 1
                for (int j = 0; j < 8; j++) {
                    const uint64_t da = mkdesc(half * 8192, 16, 1024, 1) + (po & 7) * 1024, db = mkdesc(OFF_RING, 8192, 1024, 1) + slot * 1024;
                    mbar_wait(full, 0);
                    if (wq == 3 && half == 0 && lane == 0) TS2(1, t * 8 + j);
                    wg_fence();
#pragma unroll
                    for (int k = 0; k < 4; k++) wgmma_ss_n128(acc, da + k * 2, db + k * 128, (j | k) != 0);
                    wg_commit();
                    if (j == 7 && rel2) mbar_arrive(bars + 8 * (B_ORD + t));
                    wg_wait<1>();
                    if (wq == 3 && half == 0 && lane == 0) TS2(2, t * 8 + j);
                    if (t == 0 && j == 1) mbar_wait(full + 8, 0);
                    if (j > 0 && rel) mbar_arrive_remote(empty + prev * 8);
                    if ((po & 8) && rel2) mbar_arrive(bars + 8 * (j == 3 ? B_AFREE0 : B_AFREE + (j >> 1) - 1));
                    prev = slot; slot = slot == NRING - 1 ? 0 : slot + 1; po >>= 4; full += 8;
                }
                if (t >= 3) {
                    mbar_wait(bars + 8 * B_QKV, 0);
                    const uint4* pq = g_q + (head * 128 + (qb * 8 + wg) * 4 + wq) * 32 + lane;
                    const uint4 v = __ldcg(pq), u = __ldcg(pq + 512);
                    qn[0] = v.x; qn[1] = v.y; qn[2] = v.z; qn[3] = v.w; q[0] = u.x; q[1] = u.y; q[2] = u.z; q[3] = u.w;
                }
                wg_wait<0>();
                if (rel) mbar_arrive_remote(empty + prev * 8);
                if (t >= 3 && rel2) mbar_arrive(bars + 8 * (t == 4 ? B_AFREE + 3 : B_AFREE0));
                pin<64>(acc);
                if (wq == 0 && half == 0 && lane == 0) TSTAMP(2 + 2 * t);
                mbar_wait(bars + 8 * (B_STATS + (t >= 2)), 0);
                uint32_t rs0, rs1;
                asm volatile("ld.shared.b32 %0, [%1];" : "=r"(rs0) : "r"(sb + OFF_RS + (half * 64 + wq * 16 + g) * 4));
                asm volatile("ld.shared.b32 %0, [%1];" : "=r"(rs1) : "r"(sb + OFF_RS + (half * 64 + wq * 16 + g + 8) * 4));
                const float m0 = bf_lo(rs0), m1 = bf_lo(rs1);
                float d0 = bf_hi(rs0), d1 = bf_hi(rs1);
#pragma unroll
                for (int j = 0; j < 16; j++) {
                    float c0, c1;
                    asm volatile("ld.shared.v2.f32 {%0,%1}, [%2];" : "=f"(c0), "=f"(c1) : "r"(sb + OFF_CS + (t * 128 + j * 8 + t4 * 2) * 4));
                    acc[4 * j] = fmaf(-m0, c0, acc[4 * j]); acc[4 * j + 1] = fmaf(-m0, c1, acc[4 * j + 1]);
                    acc[4 * j + 2] = fmaf(-m1, c0, acc[4 * j + 2]); acc[4 * j + 3] = fmaf(-m1, c1, acc[4 * j + 3]);
                }
                float r0 = __frcp_rn(d0), r1 = __frcp_rn(d1);
                if (t < nq) {
                    const int qt = qt0 + t, h0 = (qt & 3) * 8;
                    if (qt < 4) {
                        r0 *= 0.25f * 1.4426950408889634f * M71; r1 *= 0.25f * 1.4426950408889634f * M71;
                    } else if (qt < 8) {
                        r0 *= ((FIXED_MASK >> (2 * wq)) & 1) ? M71 : P71; r1 *= ((FIXED_MASK >> (2 * wq + 1)) & 1) ? M71 : P71;
                    }
                    uint32_t* p; int s8, sh;
                    if (qt < 8) { p = reinterpret_cast<uint32_t*>(g_k + h0 * 4096) + tile16 * 128 + lane; s8 = 64; sh = 32; }
                    else        { p = reinterpret_cast<uint32_t*>(g_v + h0 * 4096) + tile16 * 64 + lane;  s8 = 32; sh = 8192; }
#pragma unroll
                    for (int hh = 0; hh < 8; hh++) {
                        const float* a = acc + hh * 8;
                        const uint32_t e0 = pack_bf16(a[0] * r0, a[1] * r0), e1 = pack_bf16(a[2] * r1, a[3] * r1);
                        const uint32_t e2 = pack_bf16(a[4] * r0, a[5] * r0), e3 = pack_bf16(a[6] * r1, a[7] * r1);
                        if (qt < 4) g_q[((h0 + hh) * 128 + tile16) * 32 + lane] = make_uint4(e0, e1, e2, e3);
                        else { uint32_t* pp = p + hh * 16384; pp[0] = e0; pp[s8] = e1; pp[sh] = e2; pp[sh + s8] = e3; }
                    }
                } else {
                    uint32_t* p = reinterpret_cast<uint32_t*>(g_h + (rowblk * 28 + gu0 + t) * 512) + wq * 512 + lane;
                    r0 *= -1.4426950408889634f; r1 *= -1.4426950408889634f; d0 *= d0; d1 *= d1;
#pragma unroll
                    for (int j = 0; j < 8; j++) {
                        const float* a = acc + j * 4; const float* b = a + 32;
                        p[j * 32] = pack_bf16(a[0] * b[0] * rcpf(fmaf(ex2f(a[0] * r0), d0, d0)), a[1] * b[1] * rcpf(fmaf(ex2f(a[1] * r0), d0, d0)));
                        p[256 + j * 32] = pack_bf16(a[2] * b[2] * rcpf(fmaf(ex2f(a[2] * r1), d1, d1)), a[3] * b[3] * rcpf(fmaf(ex2f(a[3] * r1), d1, d1)));
                    }
                }
                __syncwarp();
                if (elect_one()) mbar_arrive(bars + 8 * (B_TILE + t));
                if (wq == 0 && half == 0 && lane == 0) TSTAMP(3 + 2 * t);
            }
        }
        const uint64_t db2 = mkdesc(OFF_B2, 128, 256, 0);
        float s[32];
        auto ref_point = [&](int ntile, uint32_t& b0, uint32_t& b1) {
            float m0 = -INFINITY, m1 = -INFINITY, f0 = -INFINITY, f1 = -INFINITY;
#pragma unroll 1
            for (int t = 0; t < ntile; t++) {
                wg_fence();
                wgmma_rs_n64_zero(s, q, mkdesc(k_tile_addr(0, t), 128, 256, 0));
                wg_commit();
                wg_wait<0>();
                pin<32>(s);
#pragma unroll
                for (int i = 0; i < 8; i++) {
                    if ((FIXED_MASK >> i) & 1) { f0 = fmaxf(f0, fmaxf(s[4 * i], s[4 * i + 1])); f1 = fmaxf(f1, fmaxf(s[4 * i + 2], s[4 * i + 3])); }
                    else                       { m0 = fmaxf(m0, fmaxf(s[4 * i], s[4 * i + 1])); m1 = fmaxf(m1, fmaxf(s[4 * i + 2], s[4 * i + 3])); }
                }
            }
            m0 = fmaxf(m0, f0 * P71 * P71); m1 = fmaxf(m1, f1 * P71 * P71);
            m0 = fmaxf(m0, __shfl_xor_sync(0xffffffffu, m0, 1)); m1 = fmaxf(m1, __shfl_xor_sync(0xffffffffu, m1, 1));
            m0 = fmaxf(m0, __shfl_xor_sync(0xffffffffu, m0, 2)); m1 = fmaxf(m1, __shfl_xor_sync(0xffffffffu, m1, 2));
#pragma unroll
            for (int r = 0; r < 2; r++) {
                const float m = -rintf(r ? m1 : m0), mh = bf_round(m), mm = bf_round(m - mh), ml = m - mh - mm;
                const float lo = t4 == 0 ? mh : t4 == 1 ? ml : t4 == 2 ? 1.f : 0.f, hi = t4 == 0 ? mm : t4 == 1 ? 1.f : 0.f;
                (r ? b1 : b0) = pack_bf16(lo * M71, hi * M71);
            }
        };
        uint32_t q2[4];
        int redo = 1;
        mbar_wait(bars + 8 * B_KV, 0);
#pragma unroll 1
        for (int round = -1; round < 2;) {
            if (redo) ref_point(redo, q2[0], q2[1]);
            if (round < 0) {
#pragma unroll
                for (int i = 0; i < 4; i++) { const uint32_t tq = q[i]; q[i] = qn[i]; qn[i] = tq; }
                qn[4] = q2[0]; qn[5] = q2[1];
                q2[2] = __shfl_sync(0xffffffffu, q2[0], 3); q2[3] = __shfl_sync(0xffffffffu, q2[1], 3);
                round = 0;
                continue;
            }
            float o[12]; uint32_t p[16];
#pragma unroll
            for (int i = 0; i < 12; i++) o[i] = 0.f;
            pin<12>(o); pin<4>(q2);
            if (wq == 0 && half == 0 && lane == 0) TSTAMP(12 + 4 * round + pair);
            uint64_t dk0 = mkdesc(4096, 128, 256, 0), dk1 = mkdesc(98304, 128, 256, 0), dv = mkdesc(0, 128, 65536, 0);
#pragma unroll 1
            for (int c = 0; c < 8; c++, dk0 += 512, dk1 += 256, dv += 512 - (256ull << 32)) {
                if (round == 0) mbar_wait(bars + 8 * (B_KV + c), 0);
#pragma unroll
                for (int t = 0; t < 4; t++) {
                    wg_fence();
                    wgmma_rs_n64_zero(s, q, (t & 2 ? dk1 : dk0) + (t & 1) * 128);
                    wgmma_rs_n64_acc(s, q2, db2);
                    wg_commit();
                    wg_wait<0>();
                    pin<32>(s); pin<16>(p);
#pragma unroll
                    for (int i = 0; i < 16; i++) {
                        if ((FIXED_MASK >> (i >> 1)) & 1) p[i] = exp2_fixed(s[2 * i], s[2 * i + 1], half2);
                        else                              p[i] = pack_bf16(ex2f(s[2 * i]), ex2f(s[2 * i + 1]));
                    }
                    wg_fence();
#pragma unroll
                    for (int k = 0; k < 4; k++) wgmma_rs_n24_acc(o, p + 4 * k, dv + (t * 4 + k) * 16);
                    wg_commit();
                }
            }
            wg_wait<0>();
            pin<12>(o);
            if (redo != 32) {
                float chk = (o[8] + o[10]) * 256.f;
#pragma unroll
                for (int i = 0; i < 8; i++) chk += fabsf(o[i]);
                uint32_t bad;
                asm volatile("{\n.reg .pred p, q;\nsetp.geu.f32 q, %1, 0f7F800000;\nbar.red.or.pred p, %2, 128, q;\nselp.u32 %0, 1, 0, p;\n}" : "=r"(bad) : "f"(chk), "r"(1 + wg) : "memory");
                if (__any_sync(0xffffffffu, bad)) { redo = 32; continue; }
            }
            const int rowblk = qb * 8 + round * 4 + wg;
            const float r0 = rcpf(o[8]), r1 = rcpf(o[10]);
            uint32_t* po = reinterpret_cast<uint32_t*>(g_o + (rowblk * 8 + (head >> 2)) * 512) + wq * 512 + (head & 3) * 64 + lane;
            po[0] = pack_bf16(o[0] * r0, o[1] * r0); po[256] = pack_bf16(o[2] * r1, o[3] * r1);
            po[32] = pack_bf16(o[4] * r0, o[5] * r0); po[288] = pack_bf16(o[6] * r1, o[7] * r1);
            if (round == 0) {
                __syncwarp();
                if (elect_one()) mbar_arrive(bars + 8 * (B_OW + pair));
            } else {
                bar_sync(1 + wg, 128);
                if (wq == 0 && elect_one()) { mbar_arrive(bars + 8 * B_DONE); signal_cnt(C_O + rowblk); }
            }
#pragma unroll
            for (int i = 0; i < 4; i++) q[i] = qn[i];
            q2[0] = qn[4]; q2[1] = qn[5];
            redo = 0;
            if (wq == 0 && half == 0 && lane == 0) TSTAMP(14 + 4 * round + pair);
            round++;
        }
    } else {
        if (wq == 0) {
            asm volatile("barrier.cluster.wait.aligned;" ::: "memory");
            if (tid == 512) TSTAMP(27);
            uint32_t slot = 2, ph = 1;
#pragma unroll 1
            for (int n = 2; n < 40; n++) {
                const int t = n >> 3, j = n & 7;
                const int kc = (n < 32 ? j : (POS_LAST >> (4 * j)) & 7) * 64;
                const CUtensorMap* m = t < nq ? &mqkv : rank ? &mw3 : &mw1;
                const int col = t < nq ? (qt0 + t) * 128 + rank * 64 : (gu0 + t) * 64;
                const uint32_t dst = ring + slot * 16384 + rank * 8192, fb = bars + 8 * (B_FULL + n);
                if (n < 8 && elect_one()) tma2d(sb + n * 16384, &mx, kc, mblk * 128, fb);
                mbar_wait(bars + 8 * (B_EMPTY + slot), ph);
                if (elect_one()) { TS2(0, n); tma2d_mc(dst, m, col, kc, fb); }
                if (++slot == NRING) { slot = 0; ph ^= 1; }
            }
        } else {
            auto gather = [&](int t) {
                float a[4];
#pragma unroll 1
                for (int n = 0; n < 2000000; n++) {
                    uint32_t stale = 0;
                    a[0] = a[1] = a[2] = a[3] = 0.f;
#pragma unroll
                    for (int i = 0; i < 16; i++) {
                        uint32_t u, v;
                        stale |= ld_tagged2(g_cs + (grp * 5 + t) * 512 + i * 32 + lane, tag, u, v);
                        a[(i & 1) * 2] += __uint_as_float(u); a[(i & 1) * 2 + 1] += __uint_as_float(v);
                    }
                    if (__all_sync(0xffffffffu, stale == 0)) break;
                }
                asm volatile("st.shared.v2.f32 [%0], {%1,%2};" :: "r"(sb + OFF_CS + t * 512 + lane * 8), "f"(a[0]), "f"(a[1]) : "memory");
                asm volatile("st.shared.v2.f32 [%0], {%1,%2};" :: "r"(sb + OFF_CS + t * 512 + 256 + lane * 8), "f"(a[2]), "f"(a[3]) : "memory");
            };
            mbar_wait(bars + 8 * (B_FULL + 1), 0);
            if (wq == 3) {
                uint32_t a, b, c, d;
#pragma unroll 1
                for (int n = 0; n < 2000000; n++) {
                    const uint32_t stale = ld_tagged2(g_rs + mblk * 64 + lane * 2, tag, a, b) | ld_tagged2(g_rs + mblk * 64 + lane * 2 + 1, tag, c, d);
                    if (__all_sync(0xffffffffu, stale == 0)) break;
                }
                asm volatile("st.shared.v4.b32 [%0], {%1,%2,%3,%4};" :: "r"(sb + OFF_RS + lane * 16), "r"(a), "r"(b), "r"(c), "r"(d) : "memory");
            }
#pragma unroll 1
            for (int pass = 0; pass < 2; pass++) {
                const int t = pass ? wq + 1 : wq - 1;
                if (pass || wq < 3) gather(t);
                bar_sync(6, 96);
                if (wq == 1 && elect_one()) { mbar_arrive(bars + 8 * (B_STATS + pass)); TSTAMP(pass ? 31 : 28); }
                if (pass) break;
                const __nv_bfloat16* src = (rank ? w3 : w1) + (gu0 + wq + 1) * 64 + (size_t)(rot * 64 + (lane >> 3)) * FF + (lane & 7) * 8;
                uint4 v[16];
                const uint32_t* w = reinterpret_cast<const uint32_t*>(v);
#pragma unroll
                for (int j = 0; j < 16; j++) v[j] = __ldg(reinterpret_cast<const uint4*>(src + (size_t)j * 4 * FF));
                float c[8];
#pragma unroll
                for (int e = 0; e < 4; e++) {
                    float a = 0.f, b = 0.f;
#pragma unroll
                    for (int j = 0; j < 16; j++) { a += bf_lo(w[4 * j + e]); b += bf_hi(w[4 * j + e]); }
                    c[2 * e] = a; c[2 * e + 1] = b;
                }
#pragma unroll
                for (int n = 4; n > 1; n >>= 1) {
                    const bool up = lane & (4 * n);
#pragma unroll
                    for (int e = 0; e < n; e++) c[e] = (up ? c[e + n] : c[e]) + __shfl_xor_sync(0xffffffffu, up ? c[e] : c[e + n], 4 * n);
                }
                unsigned long long* dst = reinterpret_cast<unsigned long long*>(g_cs) + ((grp * 5 + wq + 1) * 8 + rot) * 128 + rank * 64 + (lane & 7) * 8 + (lane >> 3) * 2;
                st_tagged(dst, __float_as_uint(c[0]), tag); st_tagged(dst + 1, __float_as_uint(c[1]), tag);
            }
        }
        if (wq == 3) {
            if (lane == 0) g_epoch[blockIdx.x] = tag;
#pragma unroll 1
            for (int i = lane; i < 256; i += 32) asm volatile("st.shared.v4.b32 [%0], {%1,%1,%1,%1};" :: "r"(sb + OFF_ONES + i * 16), "r"(0x3F803F80u) : "memory");
#pragma unroll 1
            for (int i = lane; i < 128; i += 32) {
                const bool fx = (FIXED_MASK >> (i >> 4)) & 1;
                uint32_t a = fx ? pack_bf16(M71, M71) : pack_bf16(P71, P71);
                uint32_t b = fx ? pack_bf16(M71, 47.0f * M71) : pack_bf16(P71, -79.5f * P71);
                uint32_t c = fx ? 0u : pack_bf16(0.08214f * P71, 0.f);
                if (i & 8) a = b = c = 0;
                asm volatile("st.shared.v4.b32 [%0], {%1,%2,%3,%4};" :: "r"(sb + OFF_B2 + i * 16), "r"(a), "r"(b), "r"(c), "r"(0) : "memory");
            }
            fence_async_smem();
            __syncwarp();
            if (elect_one()) mbar_arrive(bars + 8 * B_QKV);
        } else if (wq == 1) {
#pragma unroll 1
            for (int i = 0; i < 3; i++) wait_cnt(C_QKV + i * 4 + (head >> 3), 16 * tag, 100);
            fence_async_all();
            if (elect_one()) { mbar_arrive(bars + 8 * B_QKV); TSTAMP(29); }
            const uint8_t* gk = reinterpret_cast<const uint8_t*>(g_k + head * 4096);
            const uint8_t* gv = reinterpret_cast<const uint8_t*>(g_v + head * 4096);
#pragma unroll 1
            for (int c = 0; c < 8; c++) {
                if (!(c & 1)) mbar_wait(bars + 8 * (c ? B_AFREE + (c >> 1) : B_AFREE0), 0);
                if (elect_one()) {
                    const uint32_t b = bars + 8 * (B_KV + c);
                    mbar_expect(b, 16384);
                    bulk_load(sb + (2 * c + 1) * 4096, gk + c * 8192, 4096, b);
                    bulk_load(sb + 2 * c * 4096, gv + c * 4096, 4096, b);
                    bulk_load(sb + 65536 + c * 4096, gv + 32768 + c * 4096, 4096, b);
                    bulk_load(sb + 98304 + c * 4096, gk + c * 8192 + 4096, 4096, b);
                }
            }
        } else if (wq == 2) {
#pragma unroll 1
            for (int t = 0; t < 5; t++) {
                mbar_wait(bars + 8 * (B_TILE + t), 0);
                if (elect_one()) signal_cnt(t < nq ? C_QKV + qt0 + t : C_H + mblk);
            }
        }
        bar_sync(5, 128);
        const int cb = blockIdx.x & 7, pr = blockIdx.x >> 3;
        const int rb0 = (pr >> 2) * 8 + (pr & 3);
        uint32_t gate[2][16];
        {
            float dn[64];
            auto load_stage = [&](int kb, int st) {
                const uint32_t b = bars + 8 * (B_RING + st), dst = ring + st * 24576;
                mbar_expect(b, 24576);
                bulk_load(dst, g_h + (rb0 * 28 + kb) * 512, 8192, b);
                bulk_load(dst + 8192, g_h + ((rb0 + 4) * 28 + kb) * 512, 8192, b);
                tma2d(dst + 16384, &mw2, cb * 64, kb * 64, b);
            };
            if (wq == 0) {
                wait_cnt(C_H + (rb0 >> 1), 28 * tag, 200);
                wait_cnt(C_H + (rb0 >> 1) + 2, 28 * tag, 200);
                if (elect_one()) { TSTAMP(20); fence_async_all(); load_stage(0, 0); load_stage(1, 1); }
            }
            int st = 0; uint32_t ph = 0;
#pragma unroll 1
            for (int kb = 0; kb < 28; kb++) {
                mbar_wait(bars + 8 * (B_RING + st), ph);
                const uint64_t da = mkdesc(OFF_RING + st * 24576, 128, 1024, 0), db = mkdesc(OFF_RING + st * 24576 + 16384, 8192, 1024, 1);
                wg_fence();
#pragma unroll
                for (int k = 0; k < 4; k++) { wgmma_ss_n64(dn, da + k * 16, db + k * 128, (kb | k) != 0); wgmma_ss_n64(dn + 32, da + 512 + k * 16, db + k * 128, (kb | k) != 0); }
                wg_commit();
                wg_wait<1>();
                if (wq == 0 && kb < 26 && elect_one()) load_stage(kb + 2, st == 0 ? 2 : st - 1);
                if (++st == 3) { st = 0; ph ^= 1; }
            }
            wg_wait<0>();
            pin<64>(dn);
#pragma unroll
            for (int i = 0; i < 32; i++) gate[i >> 4][i & 15] = pack_bf16(siluf(dn[2 * i]), siluf(dn[2 * i + 1]));
        }
        float acc[32];
        if (tid == 512) TSTAMP(21);
        const uint32_t bar_wo = bars + 8 * B_WO;
        if (wq == 0 && elect_one()) {
            mbar_expect(bar_wo, 65536);
#pragma unroll 1
            for (int i = 0; i < 8; i++) tma2d(ring + i * 8192, &mwo, cb * 64, i * 64, bar_wo);
        }
        if (wq >= 2) {
            mbar_wait(bars + 8 * (B_OW + wq - 2), 0);
            if (elect_one()) {
                signal_cnt(C_O + qb * 8 + 2 * wq - 4);
                asm volatile("red.relaxed.gpu.global.add.u32 [%0], 1;" :: "l"(g_cnt + (C_O + qb * 8 + 2 * wq - 3) * 8) : "memory");
            }
        }
#pragma unroll 1
        for (int tl = 0; tl < 2; tl++) {
            const int rb = rb0 + 4 * tl;
            uint32_t xr[16];
            const uint32_t* px = reinterpret_cast<const uint32_t*>(x + (size_t)(rb * 64 + wq * 16 + g) * DM + cb * 64) + t4;
#pragma unroll
            for (int j = 0; j < 8; j++) { xr[2 * j] = __ldg(px + j * 4); xr[2 * j + 1] = __ldg(px + 8 * DM / 2 + j * 4); }
            if (wq == 0) {
                if (tl == 1) mbar_wait(bars + 8 * B_DONE, 0);
                wait_cnt(C_O + rb, 32 * tag, tl ? 20 : 200);
                if (elect_one()) {
                    fence_async_all();
                    TSTAMP(22 + 2 * tl);
#pragma unroll 1
                    for (int i = 0; i < (tl ? 8 : 2); i++) {
                        mbar_expect(bars + 8 * (B_O + i), 8192);
                        bulk_load((tl ? sb : ring + 65536) + i * 8192, g_o + (rb * 8 + i) * 512, 8192, bars + 8 * (B_O + i));
                    }
                }
            }
            if (tl == 0) mbar_wait(bar_wo, 0);
#pragma unroll 1
            for (int kb = 0; kb < 8; kb++) {
                mbar_wait(bars + 8 * (B_O + kb), tl);
                const uint32_t a = tl == 0 ? OFF_RING + 65536 + (kb & 1) * 8192 : kb * 8192;
                const uint64_t da = mkdesc(a, 128, 1024, 0), db = mkdesc(OFF_RING + kb * 8192, 8192, 1024, 1);
                wg_fence();
#pragma unroll
                for (int k = 0; k < 4; k++) wgmma_ss_n64(acc, da + k * 16, db + k * 128, (kb | k) != 0);
                wg_commit();
                if (tl == 0) {
                    wg_wait<0>();
                    bar_sync(5, 128);
                    if (wq == 0 && kb < 6 && elect_one()) { mbar_expect(bars + 8 * (B_O + kb + 2), 8192); bulk_load(sb + a, g_o + (rb * 8 + kb + 2) * 512, 8192, bars + 8 * (B_O + kb + 2)); }
                }
            }
            wg_wait<0>();
            pin<32>(acc);
            uint32_t* po = reinterpret_cast<uint32_t*>(out + (size_t)(rb * 64 + wq * 16 + g) * DM + cb * 64) + t4;
#pragma unroll
            for (int i = 0; i < 16; i++) {
                const uint32_t r = pack_bf16(fmaf(acc[2 * i], bf_lo(gate[0][i]), bf_lo(xr[i])), fmaf(acc[2 * i + 1], bf_hi(gate[0][i]), bf_hi(xr[i])));
                po[(i & 1) * (8 * DM / 2) + (i >> 1) * 4] = r;
                gate[0][i] = gate[1][i];
            }
            if (tid == 512) TSTAMP(23 + 2 * tl);
        }
    }
}

typedef CUresult (*EncodeFn)(CUtensorMap*, CUtensorMapDataType, cuuint32_t, void*, const cuuint64_t*, const cuuint64_t*, const cuuint32_t*,
                             const cuuint32_t*, CUtensorMapInterleave, CUtensorMapSwizzle, CUtensorMapL2promotion, CUtensorMapFloatOOBfill);

void make_map(EncodeFn fn, CUtensorMap* m, const void* p, int rows, int cols, int box_rows) {
    cuuint64_t dims[2] = {(cuuint64_t)cols, (cuuint64_t)rows};
    cuuint64_t strides[1] = {(cuuint64_t)cols * 2};
    cuuint32_t box[2] = {64, (cuuint32_t)box_rows};
    cuuint32_t es[2] = {1, 1};
    fn(m, CU_TENSOR_MAP_DATA_TYPE_BFLOAT16, 2, const_cast<void*>(p), dims, strides, box, es, CU_TENSOR_MAP_INTERLEAVE_NONE,
       CU_TENSOR_MAP_SWIZZLE_128B, CU_TENSOR_MAP_L2_PROMOTION_L2_128B, CU_TENSOR_MAP_FLOAT_OOB_FILL_NONE);
}

}

extern "C" void kernel_launch(void* const* d_in, const int* in_sizes, int n_in, void* d_out, int out_size) {
    const __nv_bfloat16* x = (const __nv_bfloat16*)d_in[0];
    static EncodeFn fn = nullptr;
    if (!fn) {
        cudaDriverEntryPointQueryResult qr;
        cudaGetDriverEntryPoint("cuTensorMapEncodeTiled", (void**)&fn, cudaEnableDefault, &qr);
        cudaFuncSetAttribute(mega_kernel, cudaFuncAttributeMaxDynamicSharedMemorySize, SMEM_BYTES);
    }
    CUtensorMap mx, mqkv, mw1, mw3, mw2, mwo;
    make_map(fn, &mx, d_in[0], SEQ, DM, 128);
    make_map(fn, &mqkv, d_in[1], DM, 3 * DM, 64);
    make_map(fn, &mwo, d_in[2], DM, DM, 64);
    make_map(fn, &mw1, d_in[4], DM, FF, 64);
    make_map(fn, &mw3, d_in[5], DM, FF, 64);
    make_map(fn, &mw2, d_in[6], FF, DM, 64);
    mega_kernel<<<128, 640, SMEM_BYTES, cudaStreamPerThread>>>(x, (const __nv_bfloat16*)d_in[1], (const __nv_bfloat16*)d_in[4], (const __nv_bfloat16*)d_in[5],
                                                               (__nv_bfloat16*)d_out, mx, mqkv, mw1, mw3, mw2, mwo, 0x3F003F00u);
}
```

```cpp
#include <cuda_runtime.h>
#include <cuda_bf16.h>
#include <cuda.h>
#include <stdint.h>

namespace {

constexpr int SEQ = 2048, DM = 512, FF = 1792;

__device__ uint4 g_q[32 * 128 * 32];
__device__ uint4 g_k[32 * 4096];
__device__ uint4 g_v[32 * 4096];
__device__ uint4 g_h[32 * 28 * 512];
__device__ uint4 g_o[32 * 8 * 512];
__device__ ulonglong2 g_cs[40 * 8 * 64];
__device__ ulonglong2 g_rs[SEQ / 2];
constexpr int C_QKV = 0, C_H = 12, C_O = 28, C_NUM = 60;
__device__ unsigned g_cnt[C_NUM * 8];
__device__ unsigned g_epoch[128];
#define TSTAMP(i)
#define TS2(k, i)

__device__ __forceinline__ uint32_t smem_u32(const void* p) { return (uint32_t)__cvta_generic_to_shared(p); }
__device__ __forceinline__ void mbar_init(uint32_t a, int c) { asm volatile("mbarrier.init.shared::cta.b64 [%0], %1;" :: "r"(a), "r"(c)); }
__device__ __forceinline__ void mbar_expect(uint32_t a, int b) { asm volatile("mbarrier.arrive.expect_tx.shared::cta.b64 _, [%0], %1;" :: "r"(a), "r"(b) : "memory"); }
__device__ __forceinline__ void mbar_arrive(uint32_t a) { asm volatile("mbarrier.arrive.shared::cta.b64 _, [%0];" :: "r"(a) : "memory"); }
__device__ __forceinline__ void mbar_arrive_remote(uint32_t a) { asm volatile("mbarrier.arrive.shared::cluster.b64 _, [%0];" :: "r"(a) : "memory"); }
__device__ __forceinline__ bool mbar_try(uint32_t a, uint32_t ph) {
    uint32_t ok;
    asm volatile("{\n.reg .pred p;\nmbarrier.try_wait.parity.shared::cta.b64 p, [%1], %2;\nselp.u32 %0, 1, 0, p;\n}" : "=r"(ok) : "r"(a), "r"(ph) : "memory");
    return ok;
}
__device__ __forceinline__ void mbar_wait(uint32_t a, uint32_t ph) {
    int n = 1 << 22;
#pragma unroll 1
    do { n = __all_sync(0xffffffffu, mbar_try(a, ph)) ? 0 : n - 1; } while (n > 0);
}
__device__ __forceinline__ bool elect_one() {
    uint32_t p;
    asm volatile("{\n.reg .pred P;\nelect.sync _|P, 0xffffffff;\nselp.u32 %0, 1, 0, P;\n}" : "=r"(p));
    return p;
}
__device__ __forceinline__ void signal_cnt(int c) {
    asm volatile("fence.release.gpu;\nred.relaxed.gpu.global.add.u32 [%0], 1;" :: "l"(g_cnt + c * 8) : "memory");
}
__device__ __forceinline__ void wait_cnt(int c, unsigned target, int ns) {
#pragma unroll 1
    for (int n = 0; n < 2000000; n++) {
        unsigned v;
        asm volatile("ld.relaxed.gpu.global.u32 %0, [%1];" : "=r"(v) : "l"(g_cnt + c * 8) : "memory");
        if (__all_sync(0xffffffffu, (int)(v - target) >= 0)) break;
        __nanosleep(ns);
    }
}
__device__ __forceinline__ void st_tagged(void* p, uint32_t v, uint32_t tag) {
    asm volatile("st.relaxed.gpu.global.b64 [%0], %1;" :: "l"(p), "l"((unsigned long long)tag << 32 | v) : "memory");
}
__device__ __forceinline__ uint32_t ld_tagged2(const ulonglong2* p, uint32_t tag, uint32_t& a, uint32_t& b) {
    unsigned long long u, v;
    asm volatile("ld.relaxed.gpu.global.v2.b64 {%0,%1}, [%2];" : "=l"(u), "=l"(v) : "l"(p) : "memory");
    a = (uint32_t)u; b = (uint32_t)v;
    return ((uint32_t)(u >> 32) ^ tag) | ((uint32_t)(v >> 32) ^ tag);
}
__device__ __forceinline__ void tma2d(uint32_t dst, const CUtensorMap* m, int c0, int c1, uint32_t bar) {
    asm volatile("cp.async.bulk.tensor.2d.shared::cluster.global.mbarrier::complete_tx::bytes [%0], [%1, {%3, %4}], [%2];"
                 :: "r"(dst), "l"(m), "r"(bar), "r"(c0), "r"(c1) : "memory");
}
__device__ __forceinline__ void tma2d_mc(uint32_t dst, const CUtensorMap* m, int c0, int c1, uint32_t bar) {
    asm volatile("cp.async.bulk.tensor.2d.shared::cluster.global.mbarrier::complete_tx::bytes.multicast::cluster [%0], [%1, {%3, %4}], [%2], %5;"
                 :: "r"(dst), "l"(m), "r"(bar), "r"(c0), "r"(c1), "h"((uint16_t)3) : "memory");
}
__device__ __forceinline__ void bulk_load(uint32_t dst, const void* src, int bytes, uint32_t bar) {
    asm volatile("cp.async.bulk.shared::cluster.global.mbarrier::complete_tx::bytes [%0], [%1], %2, [%3];"
                 :: "r"(dst), "l"(src), "r"(bytes), "r"(bar) : "memory");
}
__device__ __forceinline__ void bar_sync(int id, int n) { asm volatile("bar.sync %0, %1;" :: "r"(id), "r"(n) : "memory"); }
__device__ __forceinline__ void fence_async_smem() { asm volatile("fence.proxy.async.shared::cta;" ::: "memory"); }
__device__ __forceinline__ void fence_async_all() { asm volatile("fence.acquire.gpu;\nfence.proxy.async.global;" ::: "memory"); }
__device__ __forceinline__ void wg_fence() { asm volatile("wgmma.fence.sync.aligned;" ::: "memory"); }
__device__ __forceinline__ void wg_commit() { asm volatile("wgmma.commit_group.sync.aligned;" ::: "memory"); }
template <int N> __device__ __forceinline__ void wg_wait() { asm volatile("wgmma.wait_group.sync.aligned %0;" :: "n"(N) : "memory"); }
template <int N> __device__ __forceinline__ void pin(float* d) {
#pragma unroll
    for (int i = 0; i < N; i++) asm volatile("" : "+f"(d[i]) :: "memory");
}
template <int N> __device__ __forceinline__ void pin(uint32_t* d) {
#pragma unroll
    for (int i = 0; i < N; i++) asm volatile("" : "+r"(d[i]) :: "memory");
}
constexpr uint32_t SMEM_BASE = 1024;
__device__ __forceinline__ uint64_t mkdesc(uint32_t off, uint32_t lbo, uint32_t sbo, uint32_t swz) {
    return (uint64_t)((SMEM_BASE + off) >> 4) | ((uint64_t)(lbo >> 4) << 16) | ((uint64_t)(sbo >> 4) << 32) | ((uint64_t)swz << 62);
}
__device__ __forceinline__ float ex2f(float x) { float y; asm("ex2.approx.ftz.f32 %0, %1;" : "=f"(y) : "f"(x)); return y; }
__device__ __forceinline__ float rcpf(float x) { float y; asm("rcp.approx.ftz.f32 %0, %1;" : "=f"(y) : "f"(x)); return y; }
__device__ __forceinline__ uint32_t pack_bf16(float lo, float hi) { uint32_t r; asm("cvt.rn.bf16x2.f32 %0, %1, %2;" : "=r"(r) : "f"(hi), "f"(lo)); return r; }
__device__ __forceinline__ float bf_lo(uint32_t v) { return __uint_as_float(v << 16); }
__device__ __forceinline__ float bf_hi(uint32_t v) { return __uint_as_float(v & 0xFFFF0000u); }
__device__ __forceinline__ float bf_round(float x) { return __bfloat162float(__float2bfloat16_rn(x)); }
__device__ __forceinline__ float siluf(float g) { return g * rcpf(1.0f + ex2f(g * -1.4426950408889634f)); }

__device__ __forceinline__ void wgmma_ss_n256(float* d, uint64_t da, uint64_t db, int acc) {
    asm volatile("{\n.reg .pred p;\nsetp.ne.b32 p, %130, 0;\nwgmma.mma_async.sync.aligned.m64n256k16.f32.bf16.bf16 {"
        "%0,%1,%2,%3,%4,%5,%6,%7,%8,%9,%10,%11,%12,%13,%14,%15,%16,%17,%18,%19,%20,%21,%22,%23,%24,%25,%26,%27,%28,%29,%30,%31,%32,%33,%34,%35,%36,%37,%38,%39,"
        "%40,%41,%42,%43,%44,%45,%46,%47,%48,%49,%50,%51,%52,%53,%54,%55,%56,%57,%58,%59,%60,%61,%62,%63,%64,%65,%66,%67,%68,%69,%70,%71,%72,%73,%74,%75,%76,"
        "%77,%78,%79,%80,%81,%82,%83,%84,%85,%86,%87,%88,%89,%90,%91,%92,%93,%94,%95,%96,%97,%98,%99,%100,%101,%102,%103,%104,%105,%106,%107,%108,%109,%110,"
        "%111,%112,%113,%114,%115,%116,%117,%118,%119,%120,%121,%122,%123,%124,%125,%126,%127"
        "}, %128, %129, p, 1, 1, 0, 1;\n}\n"
        : "+f"(d[0]),"+f"(d[1]),"+f"(d[2]),"+f"(d[3]),"+f"(d[4]),"+f"(d[5]),"+f"(d[6]),"+f"(d[7]),"+f"(d[8]),"+f"(d[9]),"+f"(d[10]),"+f"(d[11]),"+f"(d[12]),
          "+f"(d[13]),"+f"(d[14]),"+f"(d[15]),"+f"(d[16]),"+f"(d[17]),"+f"(d[18]),"+f"(d[19]),"+f"(d[20]),"+f"(d[21]),"+f"(d[22]),"+f"(d[23]),"+f"(d[24]),
          "+f"(d[25]),"+f"(d[26]),"+f"(d[27]),"+f"(d[28]),"+f"(d[29]),"+f"(d[30]),"+f"(d[31]),"+f"(d[32]),"+f"(d[33]),"+f"(d[34]),"+f"(d[35]),"+f"(d[36]),
          "+f"(d[37]),"+f"(d[38]),"+f"(d[39]),"+f"(d[40]),"+f"(d[41]),"+f"(d[42]),"+f"(d[43]),"+f"(d[44]),"+f"(d[45]),"+f"(d[46]),"+f"(d[47]),"+f"(d[48]),
          "+f"(d[49]),"+f"(d[50]),"+f"(d[51]),"+f"(d[52]),"+f"(d[53]),"+f"(d[54]),"+f"(d[55]),"+f"(d[56]),"+f"(d[57]),"+f"(d[58]),"+f"(d[59]),"+f"(d[60]),
          "+f"(d[61]),"+f"(d[62]),"+f"(d[63]),"+f"(d[64]),"+f"(d[65]),"+f"(d[66]),"+f"(d[67]),"+f"(d[68]),"+f"(d[69]),"+f"(d[70]),"+f"(d[71]),"+f"(d[72]),
          "+f"(d[73]),"+f"(d[74]),"+f"(d[75]),"+f"(d[76]),"+f"(d[77]),"+f"(d[78]),"+f"(d[79]),"+f"(d[80]),"+f"(d[81]),"+f"(d[82]),"+f"(d[83]),"+f"(d[84]),
          "+f"(d[85]),"+f"(d[86]),"+f"(d[87]),"+f"(d[88]),"+f"(d[89]),"+f"(d[90]),"+f"(d[91]),"+f"(d[92]),"+f"(d[93]),"+f"(d[94]),"+f"(d[95]),"+f"(d[96]),
          "+f"(d[97]),"+f"(d[98]),"+f"(d[99]),"+f"(d[100]),"+f"(d[101]),"+f"(d[102]),"+f"(d[103]),"+f"(d[104]),"+f"(d[105]),"+f"(d[106]),"+f"(d[107]),
          "+f"(d[108]),"+f"(d[109]),"+f"(d[110]),"+f"(d[111]),"+f"(d[112]),"+f"(d[113]),"+f"(d[114]),"+f"(d[115]),"+f"(d[116]),"+f"(d[117]),"+f"(d[118]),
          "+f"(d[119]),"+f"(d[120]),"+f"(d[121]),"+f"(d[122]),"+f"(d[123]),"+f"(d[124]),"+f"(d[125]),"+f"(d[126]),"+f"(d[127])
        : "l"(da), "l"(db), "r"(acc));
}
__device__ __forceinline__ void wgmma_ss_n128(float* d, uint64_t da, uint64_t db, int acc) {
    asm volatile("{\n.reg .pred p;\nsetp.ne.b32 p, %66, 0;\nwgmma.mma_async.sync.aligned.m64n128k16.f32.bf16.bf16 {"
        "%0,%1,%2,%3,%4,%5,%6,%7,%8,%9,%10,%11,%12,%13,%14,%15,%16,%17,%18,%19,%20,%21,%22,%23,%24,%25,%26,%27,%28,%29,%30,%31,%32,%33,%34,%35,%36,%37,%38,%39,"
        "%40,%41,%42,%43,%44,%45,%46,%47,%48,%49,%50,%51,%52,%53,%54,%55,%56,%57,%58,%59,%60,%61,%62,%63"
        "}, %64, %65, p, 1, 1, 0, 1;\n}\n"
        : "+f"(d[0]),"+f"(d[1]),"+f"(d[2]),"+f"(d[3]),"+f"(d[4]),"+f"(d[5]),"+f"(d[6]),"+f"(d[7]),"+f"(d[8]),"+f"(d[9]),"+f"(d[10]),"+f"(d[11]),"+f"(d[12]),
          "+f"(d[13]),"+f"(d[14]),"+f"(d[15]),"+f"(d[16]),"+f"(d[17]),"+f"(d[18]),"+f"(d[19]),"+f"(d[20]),"+f"(d[21]),"+f"(d[22]),"+f"(d[23]),"+f"(d[24]),
          "+f"(d[25]),"+f"(d[26]),"+f"(d[27]),"+f"(d[28]),"+f"(d[29]),"+f"(d[30]),"+f"(d[31]),"+f"(d[32]),"+f"(d[33]),"+f"(d[34]),"+f"(d[35]),"+f"(d[36]),
          "+f"(d[37]),"+f"(d[38]),"+f"(d[39]),"+f"(d[40]),"+f"(d[41]),"+f"(d[42]),"+f"(d[43]),"+f"(d[44]),"+f"(d[45]),"+f"(d[46]),"+f"(d[47]),"+f"(d[48]),
          "+f"(d[49]),"+f"(d[50]),"+f"(d[51]),"+f"(d[52]),"+f"(d[53]),"+f"(d[54]),"+f"(d[55]),"+f"(d[56]),"+f"(d[57]),"+f"(d[58]),"+f"(d[59]),"+f"(d[60]),
          "+f"(d[61]),"+f"(d[62]),"+f"(d[63])
        : "l"(da), "l"(db), "r"(acc));
}
__device__ __forceinline__ void wgmma_ss_n64(float* d, uint64_t da, uint64_t db, int acc) {
    asm volatile("{\n.reg .pred p;\nsetp.ne.b32 p, %34, 0;\nwgmma.mma_async.sync.aligned.m64n64k16.f32.bf16.bf16 {"
        "%0,%1,%2,%3,%4,%5,%6,%7,%8,%9,%10,%11,%12,%13,%14,%15,%16,%17,%18,%19,%20,%21,%22,%23,%24,%25,%26,%27,%28,%29,%30,%31"
        "}, %32, %33, p, 1, 1, 0, 1;\n}\n"
        : "+f"(d[0]),"+f"(d[1]),"+f"(d[2]),"+f"(d[3]),"+f"(d[4]),"+f"(d[5]),"+f"(d[6]),"+f"(d[7]),"+f"(d[8]),"+f"(d[9]),"+f"(d[10]),"+f"(d[11]),"+f"(d[12]),
          "+f"(d[13]),"+f"(d[14]),"+f"(d[15]),"+f"(d[16]),"+f"(d[17]),"+f"(d[18]),"+f"(d[19]),"+f"(d[20]),"+f"(d[21]),"+f"(d[22]),"+f"(d[23]),"+f"(d[24]),
          "+f"(d[25]),"+f"(d[26]),"+f"(d[27]),"+f"(d[28]),"+f"(d[29]),"+f"(d[30]),"+f"(d[31])
        : "l"(da), "l"(db), "r"(acc));
}
__device__ __forceinline__ void wgmma_rs_n64_zero(float* d, const uint32_t* a, uint64_t db) {
    asm volatile("wgmma.mma_async.sync.aligned.m64n64k16.f32.bf16.bf16 {"
        "%0,%1,%2,%3,%4,%5,%6,%7,%8,%9,%10,%11,%12,%13,%14,%15,%16,%17,%18,%19,%20,%21,%22,%23,%24,%25,%26,%27,%28,%29,%30,%31"
        "}, {%32,%33,%34,%35}, %36, 0, 1, 1, 0;\n"
        : "=f"(d[0]),"=f"(d[1]),"=f"(d[2]),"=f"(d[3]),"=f"(d[4]),"=f"(d[5]),"=f"(d[6]),"=f"(d[7]),"=f"(d[8]),"=f"(d[9]),"=f"(d[10]),"=f"(d[11]),"=f"(d[12]),
          "=f"(d[13]),"=f"(d[14]),"=f"(d[15]),"=f"(d[16]),"=f"(d[17]),"=f"(d[18]),"=f"(d[19]),"=f"(d[20]),"=f"(d[21]),"=f"(d[22]),"=f"(d[23]),"=f"(d[24]),
          "=f"(d[25]),"=f"(d[26]),"=f"(d[27]),"=f"(d[28]),"=f"(d[29]),"=f"(d[30]),"=f"(d[31])
        : "r"(a[0]), "r"(a[1]), "r"(a[2]), "r"(a[3]), "l"(db));
}
__device__ __forceinline__ void wgmma_rs_n64_acc(float* d, const uint32_t* a, uint64_t db) {
    asm volatile("wgmma.mma_async.sync.aligned.m64n64k16.f32.bf16.bf16 {"
        "%0,%1,%2,%3,%4,%5,%6,%7,%8,%9,%10,%11,%12,%13,%14,%15,%16,%17,%18,%19,%20,%21,%22,%23,%24,%25,%26,%27,%28,%29,%30,%31"
        "}, {%32,%33,%34,%35}, %36, 1, 1, 1, 0;\n"
        : "+f"(d[0]),"+f"(d[1]),"+f"(d[2]),"+f"(d[3]),"+f"(d[4]),"+f"(d[5]),"+f"(d[6]),"+f"(d[7]),"+f"(d[8]),"+f"(d[9]),"+f"(d[10]),"+f"(d[11]),"+f"(d[12]),
          "+f"(d[13]),"+f"(d[14]),"+f"(d[15]),"+f"(d[16]),"+f"(d[17]),"+f"(d[18]),"+f"(d[19]),"+f"(d[20]),"+f"(d[21]),"+f"(d[22]),"+f"(d[23]),"+f"(d[24]),
          "+f"(d[25]),"+f"(d[26]),"+f"(d[27]),"+f"(d[28]),"+f"(d[29]),"+f"(d[30]),"+f"(d[31])
        : "r"(a[0]), "r"(a[1]), "r"(a[2]), "r"(a[3]), "l"(db));
}
__device__ __forceinline__ void wgmma_rs_n24_acc(float* d, const uint32_t* a, uint64_t db) {
    asm volatile("wgmma.mma_async.sync.aligned.m64n24k16.f32.bf16.bf16 {"
        "%0,%1,%2,%3,%4,%5,%6,%7,%8,%9,%10,%11"
        "}, {%12,%13,%14,%15}, %16, 1, 1, 1, 1;\n"
        : "+f"(d[0]),"+f"(d[1]),"+f"(d[2]),"+f"(d[3]),"+f"(d[4]),"+f"(d[5]),"+f"(d[6]),"+f"(d[7]),"+f"(d[8]),"+f"(d[9]),"+f"(d[10]),"+f"(d[11])
        : "r"(a[0]), "r"(a[1]), "r"(a[2]), "r"(a[3]), "l"(db));
}
__device__ __forceinline__ void wgmma_rs_n24_zero(float* d, const uint32_t* a, uint64_t db) {
    asm volatile("wgmma.mma_async.sync.aligned.m64n24k16.f32.bf16.bf16 {"
        "%0,%1,%2,%3,%4,%5,%6,%7,%8,%9,%10,%11"
        "}, {%12,%13,%14,%15}, %16, 0, 1, 1, 1;\n"
        : "=f"(d[0]),"=f"(d[1]),"=f"(d[2]),"=f"(d[3]),"=f"(d[4]),"=f"(d[5]),"=f"(d[6]),"=f"(d[7]),"=f"(d[8]),"=f"(d[9]),"=f"(d[10]),"=f"(d[11])
        : "r"(a[0]), "r"(a[1]), "r"(a[2]), "r"(a[3]), "l"(db));
}

constexpr int OFF_ONES = 131072;
constexpr int OFF_RING = OFF_ONES + 4096;
constexpr int NRING = 5;
constexpr int OFF_B2 = OFF_RING + NRING * 16384;
constexpr int OFF_CS = OFF_B2 + 2048;
constexpr int OFF_RS = OFF_CS + 2560;
constexpr int OFF_BAR = OFF_RS + 1024;
enum { B_FULL = 0, B_STATS = 40, B_KV = 45, B_RING = 53, B_WO = 56, B_O = 57, B_CNT2 = 65,
       B_AFREE = 65, B_ORD = 69, B_QKV = 74, B_CNT4 = 75, B_EMPTY = 75, B_AFREE0 = 80, B_DONE = 81, B_CNT8 = 82, B_TILE = 82, B_OW = 87, B_NUM = 100 };
constexpr int OFF_TS = OFF_BAR + 1024;
constexpr int SMEM_BYTES = OFF_BAR + B_NUM * 8;
constexpr unsigned FIXED_MASK = 0xB5;
constexpr float P71 = 2361183241434822606848.0f, M71 = 4.235164736271502e-22f;

__device__ __forceinline__ uint32_t exp2_fixed(float lo, float hi, uint32_t half2) {
    uint32_t y, g, d;
    asm("cvt.pack.sat.s16.s32 %0, %1, %2;" : "=r"(y) : "r"(__float_as_uint(hi)), "r"(__float_as_uint(lo)));
    asm("lop3.b32 %0, %1, 0x007F007F, %2, 0xEA;" : "=r"(g) : "r"(y), "r"(half2));
    asm("fma.rn.bf16x2 %0, %1, %2, %3;" : "=r"(d) : "r"(y), "r"(g), "r"(y & 0xFF80FF80u));
    return d;
}
__device__ __forceinline__ uint32_t k_tile_addr(uint32_t base, int tile) {
    const int c = tile >> 2;
    return base + ((tile & 2) ? 98304 + c * 4096 : (2 * c + 1) * 4096) + (tile & 1) * 2048;
}
constexpr uint32_t POS_STD = 0x76543210u, POS_LAST = 0xB75A9640u;

__global__ void __cluster_dims__(2, 1, 1) __launch_bounds__(640, 1)
mega_kernel(const __nv_bfloat16* __restrict__ x, const __nv_bfloat16* __restrict__ wqkv, const __nv_bfloat16* __restrict__ w1,
            const __nv_bfloat16* __restrict__ w3, __nv_bfloat16* __restrict__ out,
            const __grid_constant__ CUtensorMap mx, const __grid_constant__ CUtensorMap mqkv, const __grid_constant__ CUtensorMap mw1,
            const __grid_constant__ CUtensorMap mw3, const __grid_constant__ CUtensorMap mw2, const __grid_constant__ CUtensorMap mwo,
            uint32_t half2) {
    extern __shared__ __align__(1024) uint8_t smem_raw[];
    const uint32_t sb = __shfl_sync(0xffffffffu, smem_u32(smem_raw), 0);
    if ((sb & 0xFFFFFF) != SMEM_BASE) __trap();
    const uint32_t bars = sb + OFF_BAR, ring = sb + OFF_RING;
    const int tid = threadIdx.x, lane = tid & 31, g = lane >> 2, t4 = lane & 3;
    const int warp = __shfl_sync(0xffffffffu, tid >> 5, 0), wg = warp >> 2, wq = warp & 3;
    const int rank = blockIdx.x & 1, cl = blockIdx.x >> 1;
    const int grp = cl < 4 ? 4 + cl : cl < 36 ? (cl - 4) >> 3 : 4 + (cl - 36) / 7;
    const int rot = cl < 4 ? 7 : cl < 36 ? (cl - 4) & 7 : (cl - 36) % 7;
    const int mblk = rot * 2 + rank;
    const int nq = grp < 4 ? 2 : 1;
    const int qt0 = grp < 4 ? 2 * grp : 4 + grp;
    const int gu0 = (grp < 4 ? 3 * grp : 4 * grp - 4) - nq;
    const int head = blockIdx.x >> 2, qb = blockIdx.x & 3;

    if (elect_one()) {
#pragma unroll
        for (int i = 0; i < 5; i++) { const int b = warp * 5 + i; mbar_init(bars + 8 * b, b < B_CNT2 ? 1 : b < B_CNT4 ? 2 : b < B_CNT8 ? 4 : 8); }
        if (warp == 0) {
            fence_async_smem();
#pragma unroll
            for (int j = 0; j < 2; j++) {
                tma2d(sb + j * 16384, &mx, j * 64, mblk * 128, bars + 8 * (B_FULL + j));
                tma2d(ring + j * 16384, &mqkv, qt0 * 128, j * 64, bars + 8 * (B_FULL + j));
                tma2d(ring + j * 16384 + 8192, &mqkv, qt0 * 128 + 64, j * 64, bars + 8 * (B_FULL + j));
            }
        }
        if (warp < 8) {
#pragma unroll
            for (int i = 0; i < 5; i++) mbar_expect(bars + 8 * (warp * 5 + i), warp * 5 + i < 8 ? 32768 : 16384);
        }
        if (warp == 16) asm volatile("prefetch.tensormap [%0];" :: "l"(rank ? &mw3 : &mw1) : "memory");
        asm volatile("fence.mbarrier_init.release.cluster;" ::: "memory");
    }
    const uint32_t tag = __ldcg(g_epoch + blockIdx.x) + 1;
    __syncthreads();
    if (tid == 512) TSTAMP(26);
    asm volatile("barrier.cluster.arrive.relaxed.aligned;" ::: "memory");

    if (wg < 4) {
        const int pair = wg >> 1, half = wg & 1;
        if (pair == 1) {
            const int r = grp * 16 + (warp - 8) * 2 + (lane >> 4), row = mblk * 128 + r;
            uint32_t w[16];
#pragma unroll 1
            for (int j = 0; j < 8; j++) mbar_wait(bars + 8 * (B_FULL + j), 0);
#pragma unroll
            for (int j = 0; j < 4; j++)
                asm volatile("ld.shared.v4.b32 {%0,%1,%2,%3}, [%4];" : "=r"(w[4 * j]), "=r"(w[4 * j + 1]), "=r"(w[4 * j + 2]), "=r"(w[4 * j + 3])
                             : "r"(sb + j * 32768 + (lane & 8) * 2048 + r * 128 + (lane & 7) * 16));
            float s0 = 0.f, v0 = 0.f;
#pragma unroll
            for (int j = 0; j < 16; j++) s0 += bf_lo(w[j]) + bf_hi(w[j]);
#pragma unroll
            for (int d = 1; d < 16; d <<= 1) s0 += __shfl_xor_sync(0xffffffffu, s0, d);
            const float mean = s0 * (1.0f / DM);
#pragma unroll
            for (int j = 0; j < 16; j++) { const float a = bf_lo(w[j]) - mean, b = bf_hi(w[j]) - mean; v0 += fmaf(a, a, b * b); }
#pragma unroll
            for (int d = 1; d < 16; d <<= 1) v0 += __shfl_xor_sync(0xffffffffu, v0, d);
            if ((lane & 15) == 0) st_tagged(reinterpret_cast<unsigned long long*>(g_rs) + row, pack_bf16(mean, sqrtf(bf_round(bf_round(v0 * (1.0f / DM)) + 1e-5f))), tag);
        }

        uint32_t q[4], qn[6];
        {
            float acc[64];
            const int rowblk = mblk * 2 + half, tile16 = rowblk * 4 + wq;
            const bool rel = wq < 2 && lane == 0, rel2 = wq == 2 && lane == 0;
            uint32_t empty;
            asm("mapa.shared::cluster.u32 %0, %1, %2;" : "=r"(empty) : "r"(bars + 8 * B_EMPTY), "r"(wq & 1));
#pragma unroll 1
            for (int t = pair; t < 5; t += 2) {
                uint32_t po = t == 4 ? POS_LAST : POS_STD, full = bars + 8 * (B_FULL + 8 * t), slot = (0x24130u >> (4 * t)) & 7, prev = 0;
                uint64_t da = mkdesc(half * 8192, 16, 1024, 1), db = mkdesc(OFF_RING, 8192, 1024, 1) + slot * 1024;
                if (tid == 0 && t == 0) TSTAMP(30);
                mbar_wait(full, 0);
                if (t > 0) mbar_wait(bars + 8 * (B_ORD + t - 1), 0);
#pragma unroll 1
                for (int j = 0; j < 8; j++) {
                    wg_fence();
#pragma unroll
                    for (int k = 0; k < 4; k++) wgmma_ss_n128(acc, da + k * 2, db + k * 128, (j | k) != 0);
                    wg_commit();
                    const uint32_t rel_a = empty + prev * 8, rel_b = bars + 8 * (j == 3 ? B_AFREE0 : B_AFREE + (j >> 1) - 1);
                    const bool do_a = j > 0 && rel, do_b = (po & 8) && rel2;
                    prev = slot; slot = slot == NRING - 1 ? 0 : slot + 1; po >>= 4; full += 8;
                    da = mkdesc(half * 8192, 16, 1024, 1) + (po & 7) * 1024; db = mkdesc(OFF_RING, 8192, 1024, 1) + slot * 1024;
                    if (j < 7) mbar_wait(full, 0); else if (rel2) mbar_arrive(bars + 8 * (B_ORD + t));
                    wg_wait<1>();
                    if (do_a) mbar_arrive_remote(rel_a);
                    if (do_b) mbar_arrive(rel_b);
                }
                if (t >= 3) {
                    mbar_wait(bars + 8 * B_QKV, 0);
                    const uint4* pq = g_q + (head * 128 + (qb * 8 + wg) * 4 + wq) * 32 + lane;
                    const uint4 v = __ldcg(pq), u = __ldcg(pq + 512);
                    qn[0] = v.x; qn[1] = v.y; qn[2] = v.z; qn[3] = v.w; q[0] = u.x; q[1] = u.y; q[2] = u.z; q[3] = u.w;
                }
                wg_wait<0>();
                if (rel) mbar_arrive_remote(empty + prev * 8);
                if (t >= 3 && rel2) mbar_arrive(bars + 8 * (t == 4 ? B_AFREE + 3 : B_AFREE0));
                pin<64>(acc);
                if (wq == 0 && half == 0 && lane == 0) TSTAMP(2 + 2 * t);
                mbar_wait(bars + 8 * (B_STATS + t), 0);
                uint32_t rs0, rs1;
                asm volatile("ld.shared.b32 %0, [%1];" : "=r"(rs0) : "r"(sb + OFF_RS + (half * 64 + wq * 16 + g) * 4));
                asm volatile("ld.shared.b32 %0, [%1];" : "=r"(rs1) : "r"(sb + OFF_RS + (half * 64 + wq * 16 + g + 8) * 4));
                const float m0 = bf_lo(rs0), m1 = bf_lo(rs1);
                float d0 = bf_hi(rs0), d1 = bf_hi(rs1);
#pragma unroll
                for (int j = 0; j < 16; j++) {
                    float c0, c1;
                    asm volatile("ld.shared.v2.f32 {%0,%1}, [%2];" : "=f"(c0), "=f"(c1) : "r"(sb + OFF_CS + (t * 128 + j * 8 + t4 * 2) * 4));
                    acc[4 * j] = fmaf(-m0, c0, acc[4 * j]); acc[4 * j + 1] = fmaf(-m0, c1, acc[4 * j + 1]);
                    acc[4 * j + 2] = fmaf(-m1, c0, acc[4 * j + 2]); acc[4 * j + 3] = fmaf(-m1, c1, acc[4 * j + 3]);
                }
                float r0 = __frcp_rn(d0), r1 = __frcp_rn(d1);
                if (t < nq) {
                    const int qt = qt0 + t, h0 = (qt & 3) * 8;
                    if (qt < 4) {
                        r0 *= 0.25f * 1.4426950408889634f * M71; r1 *= 0.25f * 1.4426950408889634f * M71;
                    } else if (qt < 8) {
                        r0 *= ((FIXED_MASK >> (2 * wq)) & 1) ? M71 : P71; r1 *= ((FIXED_MASK >> (2 * wq + 1)) & 1) ? M71 : P71;
                    }
                    uint32_t* p; int s8, sh;
                    if (qt < 8) { p = reinterpret_cast<uint32_t*>(g_k + h0 * 4096) + tile16 * 128 + lane; s8 = 64; sh = 32; }
                    else        { p = reinterpret_cast<uint32_t*>(g_v + h0 * 4096) + tile16 * 64 + lane;  s8 = 32; sh = 8192; }
#pragma unroll
                    for (int hh = 0; hh < 8; hh++) {
                        const float* a = acc + hh * 8;
                        const uint32_t e0 = pack_bf16(a[0] * r0, a[1] * r0), e1 = pack_bf16(a[2] * r1, a[3] * r1);
                        const uint32_t e2 = pack_bf16(a[4] * r0, a[5] * r0), e3 = pack_bf16(a[6] * r1, a[7] * r1);
                        if (qt < 4) g_q[((h0 + hh) * 128 + tile16) * 32 + lane] = make_uint4(e0, e1, e2, e3);
                        else { uint32_t* pp = p + hh * 16384; pp[0] = e0; pp[s8] = e1; pp[sh] = e2; pp[sh + s8] = e3; }
                    }
                } else {
                    uint32_t* p = reinterpret_cast<uint32_t*>(g_h + (rowblk * 28 + gu0 + t) * 512) + wq * 512 + lane;
                    r0 *= -1.4426950408889634f; r1 *= -1.4426950408889634f; d0 *= d0; d1 *= d1;
#pragma unroll
                    for (int j = 0; j < 8; j++) {
                        const float* a = acc + j * 4; const float* b = a + 32;
                        p[j * 32] = pack_bf16(a[0] * b[0] * rcpf(fmaf(ex2f(a[0] * r0), d0, d0)), a[1] * b[1] * rcpf(fmaf(ex2f(a[1] * r0), d0, d0)));
                        p[256 + j * 32] = pack_bf16(a[2] * b[2] * rcpf(fmaf(ex2f(a[2] * r1), d1, d1)), a[3] * b[3] * rcpf(fmaf(ex2f(a[3] * r1), d1, d1)));
                    }
                }
                __syncwarp();
                if (elect_one()) mbar_arrive(bars + 8 * (B_TILE + t));
                if (wq == 0 && half == 0 && lane == 0) TSTAMP(3 + 2 * t);
            }
        }
        const uint64_t db2 = mkdesc(OFF_B2, 128, 256, 0);
        float s[32];
        auto ref_point = [&](int ntile, uint32_t& b0, uint32_t& b1) {
            float m0 = -INFINITY, m1 = -INFINITY, f0 = -INFINITY, f1 = -INFINITY;
#pragma unroll 1
            for (int t = 0; t < ntile; t++) {
                wg_fence();
                wgmma_rs_n64_zero(s, q, mkdesc(k_tile_addr(0, t), 128, 256, 0));
                wg_commit();
                wg_wait<0>();
                pin<32>(s);
#pragma unroll
                for (int i = 0; i < 8; i++) {
                    if ((FIXED_MASK >> i) & 1) { f0 = fmaxf(f0, fmaxf(s[4 * i], s[4 * i + 1])); f1 = fmaxf(f1, fmaxf(s[4 * i + 2], s[4 * i + 3])); }
                    else                       { m0 = fmaxf(m0, fmaxf(s[4 * i], s[4 * i + 1])); m1 = fmaxf(m1, fmaxf(s[4 * i + 2], s[4 * i + 3])); }
                }
            }
            m0 = fmaxf(m0, f0 * P71 * P71); m1 = fmaxf(m1, f1 * P71 * P71);
            m0 = fmaxf(m0, __shfl_xor_sync(0xffffffffu, m0, 1)); m1 = fmaxf(m1, __shfl_xor_sync(0xffffffffu, m1, 1));
            m0 = fmaxf(m0, __shfl_xor_sync(0xffffffffu, m0, 2)); m1 = fmaxf(m1, __shfl_xor_sync(0xffffffffu, m1, 2));
#pragma unroll
            for (int r = 0; r < 2; r++) {
                const float m = -rintf(r ? m1 : m0), mh = bf_round(m), mm = bf_round(m - mh), ml = m - mh - mm;
                const float lo = t4 == 0 ? mh : t4 == 1 ? ml : t4 == 2 ? 1.f : 0.f, hi = t4 == 0 ? mm : t4 == 1 ? 1.f : 0.f;
                (r ? b1 : b0) = pack_bf16(lo * M71, hi * M71);
            }
        };
        uint32_t q2[4];
        int redo = 1;
        mbar_wait(bars + 8 * B_KV, 0);
#pragma unroll 1
        for (int round = -1; round < 2;) {
            if (redo) ref_point(redo, q2[0], q2[1]);
            if (round < 0) {
#pragma unroll
                for (int i = 0; i < 4; i++) { const uint32_t tq = q[i]; q[i] = qn[i]; qn[i] = tq; }
                qn[4] = q2[0]; qn[5] = q2[1];
                q2[2] = __shfl_sync(0xffffffffu, q2[0], 3); q2[3] = __shfl_sync(0xffffffffu, q2[1], 3);
                round = 0;
                continue;
            }
            float o[12]; uint32_t p[16];
#pragma unroll
            for (int i = 0; i < 12; i++) o[i] = 0.f;
            pin<12>(o); pin<4>(q2);
            if (wq == 0 && half == 0 && lane == 0) TSTAMP(12 + 4 * round + pair);
            uint64_t dk0 = mkdesc(4096, 128, 256, 0), dk1 = mkdesc(98304, 128, 256, 0), dv = mkdesc(0, 128, 65536, 0);
#pragma unroll 1
            for (int c = 0; c < 8; c++, dk0 += 512, dk1 += 256, dv += 512 - (256ull << 32)) {
                if (round == 0) mbar_wait(bars + 8 * (B_KV + c), 0);
#pragma unroll
                for (int t = 0; t < 4; t++) {
                    wg_fence();
                    wgmma_rs_n64_zero(s, q, (t & 2 ? dk1 : dk0) + (t & 1) * 128);
                    wgmma_rs_n64_acc(s, q2, db2);
                    wg_commit();
                    wg_wait<0>();
                    pin<32>(s); pin<16>(p);
#pragma unroll
                    for (int i = 0; i < 16; i++) {
                        if ((FIXED_MASK >> (i >> 1)) & 1) p[i] = exp2_fixed(s[2 * i], s[2 * i + 1], half2);
                        else                              p[i] = pack_bf16(ex2f(s[2 * i]), ex2f(s[2 * i + 1]));
                    }
                    wg_fence();
#pragma unroll
                    for (int k = 0; k < 4; k++) wgmma_rs_n24_acc(o, p + 4 * k, dv + (t * 4 + k) * 16);
                    wg_commit();
                }
            }
            wg_wait<0>();
            pin<12>(o);
            if (redo != 32) {
                float chk = (o[8] + o[10]) * 256.f;
#pragma unroll
                for (int i = 0; i < 8; i++) chk += fabsf(o[i]);
                uint32_t bad;
                asm volatile("{\n.reg .pred p, q;\nsetp.geu.f32 q, %1, 0f7F800000;\nbar.red.or.pred p, %2, 128, q;\nselp.u32 %0, 1, 0, p;\n}" : "=r"(bad) : "f"(chk), "r"(1 + wg) : "memory");
                if (__any_sync(0xffffffffu, bad)) { redo = 32; continue; }
            }
            const int rowblk = qb * 8 + round * 4 + wg;
            const float r0 = rcpf(o[8]), r1 = rcpf(o[10]);
            uint32_t* po = reinterpret_cast<uint32_t*>(g_o + (rowblk * 8 + (head >> 2)) * 512) + wq * 512 + (head & 3) * 64 + lane;
            po[0] = pack_bf16(o[0] * r0, o[1] * r0); po[256] = pack_bf16(o[2] * r1, o[3] * r1);
            po[32] = pack_bf16(o[4] * r0, o[5] * r0); po[288] = pack_bf16(o[6] * r1, o[7] * r1);
            if (round == 0) {
                __syncwarp();
                if (elect_one()) mbar_arrive(bars + 8 * (B_OW + pair));
            } else {
                bar_sync(1 + wg, 128);
                if (wq == 0 && elect_one()) { mbar_arrive(bars + 8 * B_DONE); signal_cnt(C_O + rowblk); }
            }
#pragma unroll
            for (int i = 0; i < 4; i++) q[i] = qn[i];
            q2[0] = qn[4]; q2[1] = qn[5];
            redo = 0;
            if (wq == 0 && half == 0 && lane == 0) TSTAMP(14 + 4 * round + pair);
            round++;
        }
    } else {
        if (wq == 0) {
            asm volatile("barrier.cluster.wait.aligned;" ::: "memory");
            if (tid == 512) TSTAMP(27);
            uint32_t slot = 2, ph = 1;
#pragma unroll 1
            for (int n = 2; n < 40; n++) {
                const int t = n >> 3, j = n & 7;
                const int kc = (n < 32 ? j : (POS_LAST >> (4 * j)) & 7) * 64;
                const CUtensorMap* m = t < nq ? &mqkv : rank ? &mw3 : &mw1;
                const int col = t < nq ? (qt0 + t) * 128 + rank * 64 : (gu0 + t) * 64;
                const uint32_t dst = ring + slot * 16384 + rank * 8192, fb = bars + 8 * (B_FULL + n);
                if (n < 8 && elect_one()) tma2d(sb + n * 16384, &mx, kc, mblk * 128, fb);
                mbar_wait(bars + 8 * (B_EMPTY + slot), ph);
                if (elect_one()) { TS2(0, n); tma2d_mc(dst, m, col, kc, fb); }
                if (++slot == NRING) { slot = 0; ph ^= 1; }
            }
        } else if (wq == 1) {
            mbar_wait(bars + 8 * (B_FULL + 5), 0);
#pragma unroll 1
            for (int t = 0; t < 5; t++) {
                float a[4];
#pragma unroll 1
                for (int n = 0; n < 2000000; n++) {
                    uint32_t stale = 0;
                    a[0] = a[1] = a[2] = a[3] = 0.f;
#pragma unroll
                    for (int i = 0; i < 16; i++) {
                        uint32_t u, v;
                        stale |= ld_tagged2(g_cs + (grp * 5 + t) * 512 + i * 32 + lane, tag, u, v);
                        a[(i & 1) * 2] += __uint_as_float(u); a[(i & 1) * 2 + 1] += __uint_as_float(v);
                    }
                    if (__all_sync(0xffffffffu, stale == 0)) break;
                    __nanosleep(400);
                }
                asm volatile("st.shared.v2.f32 [%0], {%1,%2};" :: "r"(sb + OFF_CS + t * 512 + lane * 8), "f"(a[0]), "f"(a[1]) : "memory");
                asm volatile("st.shared.v2.f32 [%0], {%1,%2};" :: "r"(sb + OFF_CS + t * 512 + 256 + lane * 8), "f"(a[2]), "f"(a[3]) : "memory");
                if (t == 0) {
                    uint32_t a, b, c, d;
#pragma unroll 1
                    for (int n = 0; n < 2000000; n++) {
                        const uint32_t stale = ld_tagged2(g_rs + mblk * 64 + lane * 2, tag, a, b) | ld_tagged2(g_rs + mblk * 64 + lane * 2 + 1, tag, c, d);
                        if (__all_sync(0xffffffffu, stale == 0)) break;
                    }
                    asm volatile("st.shared.v4.b32 [%0], {%1,%2,%3,%4};" :: "r"(sb + OFF_RS + lane * 16), "r"(a), "r"(b), "r"(c), "r"(d) : "memory");
                }
                __syncwarp();
                if (elect_one()) { mbar_arrive(bars + 8 * (B_STATS + t)); TSTAMP(32 + t); }
            }
        } else {
#pragma unroll 1
            for (int t = 3 - wq; t < (wq == 3 ? 5 : 2); t += t ? 1 : 2) {
                const __nv_bfloat16* src; int ld;
                if (t < nq) { src = wqkv + (qt0 + t) * 128 + rank * 64; ld = 3 * DM; }
                else        { src = (rank ? w3 : w1) + (gu0 + t) * 64; ld = FF; }
                src += (size_t)(rot * 64 + (lane >> 3)) * ld + (lane & 7) * 8;
                uint4 v[16];
                const uint32_t* w = reinterpret_cast<const uint32_t*>(v);
#pragma unroll
                for (int j = 0; j < 16; j++) v[j] = __ldg(reinterpret_cast<const uint4*>(src + (size_t)j * 4 * ld));
                float c[8];
#pragma unroll
                for (int e = 0; e < 4; e++) {
                    float a = 0.f, b = 0.f;
#pragma unroll
                    for (int j = 0; j < 16; j++) { a += bf_lo(w[4 * j + e]); b += bf_hi(w[4 * j + e]); }
                    c[2 * e] = a; c[2 * e + 1] = b;
                }
#pragma unroll
                for (int n = 4; n > 1; n >>= 1) {
                    const bool up = lane & (4 * n);
#pragma unroll
                    for (int e = 0; e < n; e++) c[e] = (up ? c[e + n] : c[e]) + __shfl_xor_sync(0xffffffffu, up ? c[e] : c[e + n], 4 * n);
                }
                unsigned long long* dst = reinterpret_cast<unsigned long long*>(g_cs) + ((grp * 5 + t) * 8 + rot) * 128 + rank * 64 + (lane & 7) * 8 + (lane >> 3) * 2;
                st_tagged(dst, __float_as_uint(c[0]), tag); st_tagged(dst + 1, __float_as_uint(c[1]), tag);
                if (lane == 0) TSTAMP(40 + t);
            }
        }
        if (wq == 3) {
            if (lane == 0) g_epoch[blockIdx.x] = tag;
#pragma unroll 1
            for (int i = lane; i < 256; i += 32) asm volatile("st.shared.v4.b32 [%0], {%1,%1,%1,%1};" :: "r"(sb + OFF_ONES + i * 16), "r"(0x3F803F80u) : "memory");
#pragma unroll 1
            for (int i = lane; i < 128; i += 32) {
                const bool fx = (FIXED_MASK >> (i >> 4)) & 1;
                uint32_t a = fx ? pack_bf16(M71, M71) : pack_bf16(P71, P71);
                uint32_t b = fx ? pack_bf16(M71, 47.0f * M71) : pack_bf16(P71, -79.5f * P71);
                uint32_t c = fx ? 0u : pack_bf16(0.08214f * P71, 0.f);
                if (i & 8) a = b = c = 0;
                asm volatile("st.shared.v4.b32 [%0], {%1,%2,%3,%4};" :: "r"(sb + OFF_B2 + i * 16), "r"(a), "r"(b), "r"(c), "r"(0) : "memory");
            }
            fence_async_smem();
            __syncwarp();
            if (elect_one()) mbar_arrive(bars + 8 * B_QKV);
        } else if (wq == 1) {
#pragma unroll 1
            for (int i = 0; i < 3; i++) wait_cnt(C_QKV + i * 4 + (head >> 3), 16 * tag, 100);
            fence_async_all();
            if (elect_one()) { mbar_arrive(bars + 8 * B_QKV); TSTAMP(29); }
            const uint8_t* gk = reinterpret_cast<const uint8_t*>(g_k + head * 4096);
            const uint8_t* gv = reinterpret_cast<const uint8_t*>(g_v + head * 4096);
#pragma unroll 1
            for (int c = 0; c < 8; c++) {
                if (!(c & 1)) mbar_wait(bars + 8 * (c ? B_AFREE + (c >> 1) : B_AFREE0), 0);
                if (elect_one()) {
                    const uint32_t b = bars + 8 * (B_KV + c);
                    mbar_expect(b, 16384);
                    bulk_load(sb + (2 * c + 1) * 4096, gk + c * 8192, 4096, b);
                    bulk_load(sb + 2 * c * 4096, gv + c * 4096, 4096, b);
                    bulk_load(sb + 65536 + c * 4096, gv + 32768 + c * 4096, 4096, b);
                    bulk_load(sb + 98304 + c * 4096, gk + c * 8192 + 4096, 4096, b);
                }
            }
        } else if (wq == 2) {
#pragma unroll 1
            for (int t = 0; t < 5; t++) {
                mbar_wait(bars + 8 * (B_TILE + t), 0);
                if (elect_one()) signal_cnt(t < nq ? C_QKV + qt0 + t : C_H + mblk);
            }
        }
        bar_sync(5, 128);
        const int cb = blockIdx.x & 7, pr = blockIdx.x >> 3;
        const int rb0 = (pr >> 2) * 8 + (pr & 3);
        uint32_t gate[2][16];
        {
            float dn[64];
            auto load_stage = [&](int kb, int st) {
                const uint32_t b = bars + 8 * (B_RING + st), dst = ring + st * 24576;
                mbar_expect(b, 24576);
                bulk_load(dst, g_h + (rb0 * 28 + kb) * 512, 8192, b);
                bulk_load(dst + 8192, g_h + ((rb0 + 4) * 28 + kb) * 512, 8192, b);
                tma2d(dst + 16384, &mw2, cb * 64, kb * 64, b);
            };
            if (wq == 0) {
                wait_cnt(C_H + (rb0 >> 1), 28 * tag, 200);
                wait_cnt(C_H + (rb0 >> 1) + 2, 28 * tag, 200);
                if (elect_one()) { TSTAMP(20); fence_async_all(); load_stage(0, 0); load_stage(1, 1); }
            }
            int st = 0; uint32_t ph = 0;
#pragma unroll 1
            for (int kb = 0; kb < 28; kb++) {
                mbar_wait(bars + 8 * (B_RING + st), ph);
                const uint64_t da = mkdesc(OFF_RING + st * 24576, 128, 1024, 0), db = mkdesc(OFF_RING + st * 24576 + 16384, 8192, 1024, 1);
                wg_fence();
#pragma unroll
                for (int k = 0; k < 4; k++) { wgmma_ss_n64(dn, da + k * 16, db + k * 128, (kb | k) != 0); wgmma_ss_n64(dn + 32, da + 512 + k * 16, db + k * 128, (kb | k) != 0); }
                wg_commit();
                wg_wait<1>();
                if (wq == 0 && kb < 26 && elect_one()) load_stage(kb + 2, st == 0 ? 2 : st - 1);
                if (++st == 3) { st = 0; ph ^= 1; }
            }
            wg_wait<0>();
            pin<64>(dn);
#pragma unroll
            for (int i = 0; i < 32; i++) gate[i >> 4][i & 15] = pack_bf16(siluf(dn[2 * i]), siluf(dn[2 * i + 1]));
        }
        float acc[32];
        if (tid == 512) TSTAMP(21);
        const uint32_t bar_wo = bars + 8 * B_WO;
        if (wq == 0 && elect_one()) {
            mbar_expect(bar_wo, 65536);
#pragma unroll 1
            for (int i = 0; i < 8; i++) tma2d(ring + i * 8192, &mwo, cb * 64, i * 64, bar_wo);
        }
        if (wq >= 2) {
            mbar_wait(bars + 8 * (B_OW + wq - 2), 0);
            if (elect_one()) {
                signal_cnt(C_O + qb * 8 + 2 * wq - 4);
                asm volatile("red.relaxed.gpu.global.add.u32 [%0], 1;" :: "l"(g_cnt + (C_O + qb * 8 + 2 * wq - 3) * 8) : "memory");
            }
        }
#pragma unroll 1
        for (int tl = 0; tl < 2; tl++) {
            const int rb = rb0 + 4 * tl;
            uint32_t xr[16];
            const uint32_t* px = reinterpret_cast<const uint32_t*>(x + (size_t)(rb * 64 + wq * 16 + g) * DM + cb * 64) + t4;
#pragma unroll
            for (int j = 0; j < 8; j++) { xr[2 * j] = __ldg(px + j * 4); xr[2 * j + 1] = __ldg(px + 8 * DM / 2 + j * 4); }
            if (wq == 0) {
                if (tl == 1) mbar_wait(bars + 8 * B_DONE, 0);
                wait_cnt(C_O + rb, 32 * tag, tl ? 20 : 200);
                if (elect_one()) {
                    fence_async_all();
                    TSTAMP(22 + 2 * tl);
#pragma unroll 1
                    for (int i = 0; i < (tl ? 8 : 2); i++) {
                        mbar_expect(bars + 8 * (B_O + i), 8192);
                        bulk_load((tl ? sb : ring + 65536) + i * 8192, g_o + (rb * 8 + i) * 512, 8192, bars + 8 * (B_O + i));
                    }
                }
            }
            if (tl == 0) mbar_wait(bar_wo, 0);
#pragma unroll 1
            for (int kb = 0; kb < 8; kb++) {
                mbar_wait(bars + 8 * (B_O + kb), tl);
                const uint32_t a = tl == 0 ? OFF_RING + 65536 + (kb & 1) * 8192 : kb * 8192;
                const uint64_t da = mkdesc(a, 128, 1024, 0), db = mkdesc(OFF_RING + kb * 8192, 8192, 1024, 1);
                wg_fence();
#pragma unroll
                for (int k = 0; k < 4; k++) wgmma_ss_n64(acc, da + k * 16, db + k * 128, (kb | k) != 0);
                wg_commit();
                if (tl == 0) {
                    wg_wait<0>();
                    bar_sync(5, 128);
                    if (wq == 0 && kb < 6 && elect_one()) { mbar_expect(bars + 8 * (B_O + kb + 2), 8192); bulk_load(sb + a, g_o + (rb * 8 + kb + 2) * 512, 8192, bars + 8 * (B_O + kb + 2)); }
                }
            }
            wg_wait<0>();
            pin<32>(acc);
            uint32_t* po = reinterpret_cast<uint32_t*>(out + (size_t)(rb * 64 + wq * 16 + g) * DM + cb * 64) + t4;
#pragma unroll
            for (int i = 0; i < 16; i++) {
                const uint32_t r = pack_bf16(fmaf(acc[2 * i], bf_lo(gate[0][i]), bf_lo(xr[i])), fmaf(acc[2 * i + 1], bf_hi(gate[0][i]), bf_hi(xr[i])));
                po[(i & 1) * (8 * DM / 2) + (i >> 1) * 4] = r;
                gate[0][i] = gate[1][i];
            }
            if (tid == 512) TSTAMP(23 + 2 * tl);
        }
    }
}

typedef CUresult (*EncodeFn)(CUtensorMap*, CUtensorMapDataType, cuuint32_t, void*, const cuuint64_t*, const cuuint64_t*, const cuuint32_t*,
                             const cuuint32_t*, CUtensorMapInterleave, CUtensorMapSwizzle, CUtensorMapL2promotion, CUtensorMapFloatOOBfill);

void make_map(EncodeFn fn, CUtensorMap* m, const void* p, int rows, int cols, int box_rows) {
    cuuint64_t dims[2] = {(cuuint64_t)cols, (cuuint64_t)rows};
    cuuint64_t strides[1] = {(cuuint64_t)cols * 2};
    cuuint32_t box[2] = {64, (cuuint32_t)box_rows};
    cuuint32_t es[2] = {1, 1};
    fn(m, CU_TENSOR_MAP_DATA_TYPE_BFLOAT16, 2, const_cast<void*>(p), dims, strides, box, es, CU_TENSOR_MAP_INTERLEAVE_NONE,
       CU_TENSOR_MAP_SWIZZLE_128B, CU_TENSOR_MAP_L2_PROMOTION_L2_128B, CU_TENSOR_MAP_FLOAT_OOB_FILL_NONE);
}

}

extern "C" void kernel_launch(void* const* d_in, const int* in_sizes, int n_in, void* d_out, int out_size) {
    const __nv_bfloat16* x = (const __nv_bfloat16*)d_in[0];
    static EncodeFn fn = nullptr;
    if (!fn) {
        cudaDriverEntryPointQueryResult qr;
        cudaGetDriverEntryPoint("cuTensorMapEncodeTiled", (void**)&fn, cudaEnableDefault, &qr);
        cudaFuncSetAttribute(mega_kernel, cudaFuncAttributeMaxDynamicSharedMemorySize, SMEM_BYTES);
    }
    CUtensorMap mx, mqkv, mw1, mw3, mw2, mwo;
    make_map(fn, &mx, d_in[0], SEQ, DM, 128);
    make_map(fn, &mqkv, d_in[1], DM, 3 * DM, 64);
    make_map(fn, &mwo, d_in[2], DM, DM, 64);
    make_map(fn, &mw1, d_in[4], DM, FF, 64);
    make_map(fn, &mw3, d_in[5], DM, FF, 64);
    make_map(fn, &mw2, d_in[6], FF, DM, 64);
    mega_kernel<<<128, 640, SMEM_BYTES, cudaStreamPerThread>>>(x, (const __nv_bfloat16*)d_in[1], (const __nv_bfloat16*)d_in[4], (const __nv_bfloat16*)d_in[5],
                                                               (__nv_bfloat16*)d_out, mx, mqkv, mw1, mw3, mw2, mwo, 0x3F003F00u);
}
```

```cpp
#include <cuda_runtime.h>
#include <cuda_bf16.h>
#include <cuda.h>
#include <stdint.h>

namespace {

constexpr int SEQ = 2048, DM = 512, FF = 1792;

__device__ uint4 g_q[32 * 128 * 32];
__device__ uint4 g_k[32 * 4096];
__device__ uint4 g_v[32 * 4096];
__device__ uint4 g_h[32 * 28 * 512];
__device__ uint4 g_o[32 * 8 * 512];
__device__ ulonglong2 g_cs[40 * 8 * 64];
__device__ ulonglong2 g_rs[SEQ / 2];
constexpr int C_QKV = 0, C_H = 12, C_O = 28, C_NUM = 60;
__device__ unsigned g_cnt[C_NUM * 8];
__device__ unsigned g_epoch[128];
#define TSTAMP(i)
#define TS2(k, i)

__device__ __forceinline__ uint32_t smem_u32(const void* p) { return (uint32_t)__cvta_generic_to_shared(p); }
__device__ __forceinline__ void mbar_init(uint32_t a, int c) { asm volatile("mbarrier.init.shared::cta.b64 [%0], %1;" :: "r"(a), "r"(c)); }
__device__ __forceinline__ void mbar_expect(uint32_t a, int b) { asm volatile("mbarrier.arrive.expect_tx.shared::cta.b64 _, [%0], %1;" :: "r"(a), "r"(b) : "memory"); }
__device__ __forceinline__ void mbar_arrive(uint32_t a) { asm volatile("mbarrier.arrive.shared::cta.b64 _, [%0];" :: "r"(a) : "memory"); }
__device__ __forceinline__ void mbar_arrive_remote(uint32_t a) { asm volatile("mbarrier.arrive.shared::cluster.b64 _, [%0];" :: "r"(a) : "memory"); }
__device__ __forceinline__ bool mbar_try(uint32_t a, uint32_t ph) {
    uint32_t ok;
    asm volatile("{\n.reg .pred p;\nmbarrier.try_wait.parity.shared::cta.b64 p, [%1], %2;\nselp.u32 %0, 1, 0, p;\n}" : "=r"(ok) : "r"(a), "r"(ph) : "memory");
    return ok;
}
__device__ __forceinline__ void mbar_wait(uint32_t a, uint32_t ph) {
    int n = 1 << 22;
#pragma unroll 1
    do { n = __all_sync(0xffffffffu, mbar_try(a, ph)) ? 0 : n - 1; } while (n > 0);
}
__device__ __forceinline__ bool elect_one() {
    uint32_t p;
    asm volatile("{\n.reg .pred P;\nelect.sync _|P, 0xffffffff;\nselp.u32 %0, 1, 0, P;\n}" : "=r"(p));
    return p;
}
__device__ __forceinline__ void signal_cnt(int c) {
    asm volatile("fence.release.gpu;\nred.relaxed.gpu.global.add.u32 [%0], 1;" :: "l"(g_cnt + c * 8) : "memory");
}
__device__ __forceinline__ void wait_cnt(int c, unsigned target, int ns) {
#pragma unroll 1
    for (int n = 0; n < 2000000; n++) {
        unsigned v;
        asm volatile("ld.relaxed.gpu.global.u32 %0, [%1];" : "=r"(v) : "l"(g_cnt + c * 8) : "memory");
        if (__all_sync(0xffffffffu, (int)(v - target) >= 0)) break;
        __nanosleep(ns);
    }
}
__device__ __forceinline__ void st_tagged(void* p, uint32_t v, uint32_t tag) {
    asm volatile("st.relaxed.gpu.global.b64 [%0], %1;" :: "l"(p), "l"((unsigned long long)tag << 32 | v) : "memory");
}
__device__ __forceinline__ uint32_t ld_tagged2(const ulonglong2* p, uint32_t tag, uint32_t& a, uint32_t& b) {
    unsigned long long u, v;
    asm volatile("ld.relaxed.gpu.global.v2.b64 {%0,%1}, [%2];" : "=l"(u), "=l"(v) : "l"(p) : "memory");
    a = (uint32_t)u; b = (uint32_t)v;
    return ((uint32_t)(u >> 32) ^ tag) | ((uint32_t)(v >> 32) ^ tag);
}
__device__ __forceinline__ void tma2d(uint32_t dst, const CUtensorMap* m, int c0, int c1, uint32_t bar) {
    asm volatile("cp.async.bulk.tensor.2d.shared::cluster.global.mbarrier::complete_tx::bytes [%0], [%1, {%3, %4}], [%2];"
                 :: "r"(dst), "l"(m), "r"(bar), "r"(c0), "r"(c1) : "memory");
}
__device__ __forceinline__ void tma2d_mc(uint32_t dst, const CUtensorMap* m, int c0, int c1, uint32_t bar) {
    asm volatile("cp.async.bulk.tensor.2d.shared::cluster.global.mbarrier::complete_tx::bytes.multicast::cluster [%0], [%1, {%3, %4}], [%2], %5;"
                 :: "r"(dst), "l"(m), "r"(bar), "r"(c0), "r"(c1), "h"((uint16_t)3) : "memory");
}
__device__ __forceinline__ void bulk_load(uint32_t dst, const void* src, int bytes, uint32_t bar) {
    asm volatile("cp.async.bulk.shared::cluster.global.mbarrier::complete_tx::bytes [%0], [%1], %2, [%3];"
                 :: "r"(dst), "l"(src), "r"(bytes), "r"(bar) : "memory");
}
__device__ __forceinline__ void bar_sync(int id, int n) { asm volatile("bar.sync %0, %1;" :: "r"(id), "r"(n) : "memory"); }
__device__ __forceinline__ void fence_async_smem() { asm volatile("fence.proxy.async.shared::cta;" ::: "memory"); }
__device__ __forceinline__ void fence_async_all() { asm volatile("fence.acquire.gpu;\nfence.proxy.async.global;" ::: "memory"); }
__device__ __forceinline__ void wg_fence() { asm volatile("wgmma.fence.sync.aligned;" ::: "memory"); }
__device__ __forceinline__ void wg_commit() { asm volatile("wgmma.commit_group.sync.aligned;" ::: "memory"); }
template <int N> __device__ __forceinline__ void wg_wait() { asm volatile("wgmma.wait_group.sync.aligned %0;" :: "n"(N) : "memory"); }
template <int N> __device__ __forceinline__ void pin(float* d) {
#pragma unroll
    for (int i = 0; i < N; i++) asm volatile("" : "+f"(d[i]) :: "memory");
}
template <int N> __device__ __forceinline__ void pin(uint32_t* d) {
#pragma unroll
    for (int i = 0; i < N; i++) asm volatile("" : "+r"(d[i]) :: "memory");
}
constexpr uint32_t SMEM_BASE = 1024;
__device__ __forceinline__ uint64_t mkdesc(uint32_t off, uint32_t lbo, uint32_t sbo, uint32_t swz) {
    return (uint64_t)((SMEM_BASE + off) >> 4) | ((uint64_t)(lbo >> 4) << 16) | ((uint64_t)(sbo >> 4) << 32) | ((uint64_t)swz << 62);
}
__device__ __forceinline__ float ex2f(float x) { float y; asm("ex2.approx.ftz.f32 %0, %1;" : "=f"(y) : "f"(x)); return y; }
__device__ __forceinline__ float rcpf(float x) { float y; asm("rcp.approx.ftz.f32 %0, %1;" : "=f"(y) : "f"(x)); return y; }
__device__ __forceinline__ uint32_t pack_bf16(float lo, float hi) { uint32_t r; asm("cvt.rn.bf16x2.f32 %0, %1, %2;" : "=r"(r) : "f"(hi), "f"(lo)); return r; }
__device__ __forceinline__ float bf_lo(uint32_t v) { return __uint_as_float(v << 16); }
__device__ __forceinline__ float bf_hi(uint32_t v) { return __uint_as_float(v & 0xFFFF0000u); }
__device__ __forceinline__ float bf_round(float x) { return __bfloat162float(__float2bfloat16_rn(x)); }
__device__ __forceinline__ float siluf(float g) { return g * rcpf(1.0f + ex2f(g * -1.4426950408889634f)); }

__device__ __forceinline__ void wgmma_ss_n256(float* d, uint64_t da, uint64_t db, int acc) {
    asm volatile("{\n.reg .pred p;\nsetp.ne.b32 p, %130, 0;\nwgmma.mma_async.sync.aligned.m64n256k16.f32.bf16.bf16 {"
        "%0,%1,%2,%3,%4,%5,%6,%7,%8,%9,%10,%11,%12,%13,%14,%15,%16,%17,%18,%19,%20,%21,%22,%23,%24,%25,%26,%27,%28,%29,%30,%31,%32,%33,%34,%35,%36,%37,%38,%39,"
        "%40,%41,%42,%43,%44,%45,%46,%47,%48,%49,%50,%51,%52,%53,%54,%55,%56,%57,%58,%59,%60,%61,%62,%63,%64,%65,%66,%67,%68,%69,%70,%71,%72,%73,%74,%75,%76,"
        "%77,%78,%79,%80,%81,%82,%83,%84,%85,%86,%87,%88,%89,%90,%91,%92,%93,%94,%95,%96,%97,%98,%99,%100,%101,%102,%103,%104,%105,%106,%107,%108,%109,%110,"
        "%111,%112,%113,%114,%115,%116,%117,%118,%119,%120,%121,%122,%123,%124,%125,%126,%127"
        "}, %128, %129, p, 1, 1, 0, 1;\n}\n"
        : "+f"(d[0]),"+f"(d[1]),"+f"(d[2]),"+f"(d[3]),"+f"(d[4]),"+f"(d[5]),"+f"(d[6]),"+f"(d[7]),"+f"(d[8]),"+f"(d[9]),"+f"(d[10]),"+f"(d[11]),"+f"(d[12]),
          "+f"(d[13]),"+f"(d[14]),"+f"(d[15]),"+f"(d[16]),"+f"(d[17]),"+f"(d[18]),"+f"(d[19]),"+f"(d[20]),"+f"(d[21]),"+f"(d[22]),"+f"(d[23]),"+f"(d[24]),
          "+f"(d[25]),"+f"(d[26]),"+f"(d[27]),"+f"(d[28]),"+f"(d[29]),"+f"(d[30]),"+f"(d[31]),"+f"(d[32]),"+f"(d[33]),"+f"(d[34]),"+f"(d[35]),"+f"(d[36]),
          "+f"(d[37]),"+f"(d[38]),"+f"(d[39]),"+f"(d[40]),"+f"(d[41]),"+f"(d[42]),"+f"(d[43]),"+f"(d[44]),"+f"(d[45]),"+f"(d[46]),"+f"(d[47]),"+f"(d[48]),
          "+f"(d[49]),"+f"(d[50]),"+f"(d[51]),"+f"(d[52]),"+f"(d[53]),"+f"(d[54]),"+f"(d[55]),"+f"(d[56]),"+f"(d[57]),"+f"(d[58]),"+f"(d[59]),"+f"(d[60]),
          "+f"(d[61]),"+f"(d[62]),"+f"(d[63]),"+f"(d[64]),"+f"(d[65]),"+f"(d[66]),"+f"(d[67]),"+f"(d[68]),"+f"(d[69]),"+f"(d[70]),"+f"(d[71]),"+f"(d[72]),
          "+f"(d[73]),"+f"(d[74]),"+f"(d[75]),"+f"(d[76]),"+f"(d[77]),"+f"(d[78]),"+f"(d[79]),"+f"(d[80]),"+f"(d[81]),"+f"(d[82]),"+f"(d[83]),"+f"(d[84]),
          "+f"(d[85]),"+f"(d[86]),"+f"(d[87]),"+f"(d[88]),"+f"(d[89]),"+f"(d[90]),"+f"(d[91]),"+f"(d[92]),"+f"(d[93]),"+f"(d[94]),"+f"(d[95]),"+f"(d[96]),
          "+f"(d[97]),"+f"(d[98]),"+f"(d[99]),"+f"(d[100]),"+f"(d[101]),"+f"(d[102]),"+f"(d[103]),"+f"(d[104]),"+f"(d[105]),"+f"(d[106]),"+f"(d[107]),
          "+f"(d[108]),"+f"(d[109]),"+f"(d[110]),"+f"(d[111]),"+f"(d[112]),"+f"(d[113]),"+f"(d[114]),"+f"(d[115]),"+f"(d[116]),"+f"(d[117]),"+f"(d[118]),
          "+f"(d[119]),"+f"(d[120]),"+f"(d[121]),"+f"(d[122]),"+f"(d[123]),"+f"(d[124]),"+f"(d[125]),"+f"(d[126]),"+f"(d[127])
        : "l"(da), "l"(db), "r"(acc));
}
__device__ __forceinline__ void wgmma_ss_n128(float* d, uint64_t da, uint64_t db, int acc) {
    asm volatile("{\n.reg .pred p;\nsetp.ne.b32 p, %66, 0;\nwgmma.mma_async.sync.aligned.m64n128k16.f32.bf16.bf16 {"
        "%0,%1,%2,%3,%4,%5,%6,%7,%8,%9,%10,%11,%12,%13,%14,%15,%16,%17,%18,%19,%20,%21,%22,%23,%24,%25,%26,%27,%28,%29,%30,%31,%32,%33,%34,%35,%36,%37,%38,%39,"
        "%40,%41,%42,%43,%44,%45,%46,%47,%48,%49,%50,%51,%52,%53,%54,%55,%56,%57,%58,%59,%60,%61,%62,%63"
        "}, %64, %65, p, 1, 1, 0, 1;\n}\n"
        : "+f"(d[0]),"+f"(d[1]),"+f"(d[2]),"+f"(d[3]),"+f"(d[4]),"+f"(d[5]),"+f"(d[6]),"+f"(d[7]),"+f"(d[8]),"+f"(d[9]),"+f"(d[10]),"+f"(d[11]),"+f"(d[12]),
          "+f"(d[13]),"+f"(d[14]),"+f"(d[15]),"+f"(d[16]),"+f"(d[17]),"+f"(d[18]),"+f"(d[19]),"+f"(d[20]),"+f"(d[21]),"+f"(d[22]),"+f"(d[23]),"+f"(d[24]),
          "+f"(d[25]),"+f"(d[26]),"+f"(d[27]),"+f"(d[28]),"+f"(d[29]),"+f"(d[30]),"+f"(d[31]),"+f"(d[32]),"+f"(d[33]),"+f"(d[34]),"+f"(d[35]),"+f"(d[36]),
          "+f"(d[37]),"+f"(d[38]),"+f"(d[39]),"+f"(d[40]),"+f"(d[41]),"+f"(d[42]),"+f"(d[43]),"+f"(d[44]),"+f"(d[45]),"+f"(d[46]),"+f"(d[47]),"+f"(d[48]),
          "+f"(d[49]),"+f"(d[50]),"+f"(d[51]),"+f"(d[52]),"+f"(d[53]),"+f"(d[54]),"+f"(d[55]),"+f"(d[56]),"+f"(d[57]),"+f"(d[58]),"+f"(d[59]),"+f"(d[60]),
          "+f"(d[61]),"+f"(d[62]),"+f"(d[63])
        : "l"(da), "l"(db), "r"(acc));
}
__device__ __forceinline__ void wgmma_ss_n64(float* d, uint64_t da, uint64_t db, int acc) {
    asm volatile("{\n.reg .pred p;\nsetp.ne.b32 p, %34, 0;\nwgmma.mma_async.sync.aligned.m64n64k16.f32.bf16.bf16 {"
        "%0,%1,%2,%3,%4,%5,%6,%7,%8,%9,%10,%11,%12,%13,%14,%15,%16,%17,%18,%19,%20,%21,%22,%23,%24,%25,%26,%27,%28,%29,%30,%31"
        "}, %32, %33, p, 1, 1, 0, 1;\n}\n"
        : "+f"(d[0]),"+f"(d[1]),"+f"(d[2]),"+f"(d[3]),"+f"(d[4]),"+f"(d[5]),"+f"(d[6]),"+f"(d[7]),"+f"(d[8]),"+f"(d[9]),"+f"(d[10]),"+f"(d[11]),"+f"(d[12]),
          "+f"(d[13]),"+f"(d[14]),"+f"(d[15]),"+f"(d[16]),"+f"(d[17]),"+f"(d[18]),"+f"(d[19]),"+f"(d[20]),"+f"(d[21]),"+f"(d[22]),"+f"(d[23]),"+f"(d[24]),
          "+f"(d[25]),"+f"(d[26]),"+f"(d[27]),"+f"(d[28]),"+f"(d[29]),"+f"(d[30]),"+f"(d[31])
        : "l"(da), "l"(db), "r"(acc));
}
__device__ __forceinline__ void wgmma_rs_n64_zero(float* d, const uint32_t* a, uint64_t db) {
    asm volatile("wgmma.mma_async.sync.aligned.m64n64k16.f32.bf16.bf16 {"
        "%0,%1,%2,%3,%4,%5,%6,%7,%8,%9,%10,%11,%12,%13,%14,%15,%16,%17,%18,%19,%20,%21,%22,%23,%24,%25,%26,%27,%28,%29,%30,%31"
        "}, {%32,%33,%34,%35}, %36, 0, 1, 1, 0;\n"
        : "=f"(d[0]),"=f"(d[1]),"=f"(d[2]),"=f"(d[3]),"=f"(d[4]),"=f"(d[5]),"=f"(d[6]),"=f"(d[7]),"=f"(d[8]),"=f"(d[9]),"=f"(d[10]),"=f"(d[11]),"=f"(d[12]),
          "=f"(d[13]),"=f"(d[14]),"=f"(d[15]),"=f"(d[16]),"=f"(d[17]),"=f"(d[18]),"=f"(d[19]),"=f"(d[20]),"=f"(d[21]),"=f"(d[22]),"=f"(d[23]),"=f"(d[24]),
          "=f"(d[25]),"=f"(d[26]),"=f"(d[27]),"=f"(d[28]),"=f"(d[29]),"=f"(d[30]),"=f"(d[31])
        : "r"(a[0]), "r"(a[1]), "r"(a[2]), "r"(a[3]), "l"(db));
}
__device__ __forceinline__ void wgmma_rs_n64_acc(float* d, const uint32_t* a, uint64_t db) {
    asm volatile("wgmma.mma_async.sync.aligned.m64n64k16.f32.bf16.bf16 {"
        "%0,%1,%2,%3,%4,%5,%6,%7,%8,%9,%10,%11,%12,%13,%14,%15,%16,%17,%18,%19,%20,%21,%22,%23,%24,%25,%26,%27,%28,%29,%30,%31"
        "}, {%32,%33,%34,%35}, %36, 1, 1, 1, 0;\n"
        : "+f"(d[0]),"+f"(d[1]),"+f"(d[2]),"+f"(d[3]),"+f"(d[4]),"+f"(d[5]),"+f"(d[6]),"+f"(d[7]),"+f"(d[8]),"+f"(d[9]),"+f"(d[10]),"+f"(d[11]),"+f"(d[12]),
          "+f"(d[13]),"+f"(d[14]),"+f"(d[15]),"+f"(d[16]),"+f"(d[17]),"+f"(d[18]),"+f"(d[19]),"+f"(d[20]),"+f"(d[21]),"+f"(d[22]),"+f"(d[23]),"+f"(d[24]),
          "+f"(d[25]),"+f"(d[26]),"+f"(d[27]),"+f"(d[28]),"+f"(d[29]),"+f"(d[30]),"+f"(d[31])
        : "r"(a[0]), "r"(a[1]), "r"(a[2]), "r"(a[3]), "l"(db));
}
__device__ __forceinline__ void wgmma_rs_n24_acc(float* d, const uint32_t* a, uint64_t db) {
    asm volatile("wgmma.mma_async.sync.aligned.m64n24k16.f32.bf16.bf16 {"
        "%0,%1,%2,%3,%4,%5,%6,%7,%8,%9,%10,%11"
        "}, {%12,%13,%14,%15}, %16, 1, 1, 1, 1;\n"
        : "+f"(d[0]),"+f"(d[1]),"+f"(d[2]),"+f"(d[3]),"+f"(d[4]),"+f"(d[5]),"+f"(d[6]),"+f"(d[7]),"+f"(d[8]),"+f"(d[9]),"+f"(d[10]),"+f"(d[11])
        : "r"(a[0]), "r"(a[1]), "r"(a[2]), "r"(a[3]), "l"(db));
}
__device__ __forceinline__ void wgmma_rs_n24_zero(float* d, const uint32_t* a, uint64_t db) {
    asm volatile("wgmma.mma_async.sync.aligned.m64n24k16.f32.bf16.bf16 {"
        "%0,%1,%2,%3,%4,%5,%6,%7,%8,%9,%10,%11"
        "}, {%12,%13,%14,%15}, %16, 0, 1, 1, 1;\n"
        : "=f"(d[0]),"=f"(d[1]),"=f"(d[2]),"=f"(d[3]),"=f"(d[4]),"=f"(d[5]),"=f"(d[6]),"=f"(d[7]),"=f"(d[8]),"=f"(d[9]),"=f"(d[10]),"=f"(d[11])
        : "r"(a[0]), "r"(a[1]), "r"(a[2]), "r"(a[3]), "l"(db));
}

constexpr int OFF_ONES = 131072;
constexpr int OFF_RING = OFF_ONES + 4096;
constexpr int NRING = 5;
constexpr int OFF_UNIT = OFF_RING + NRING * 16384;
constexpr int OFF_B2 = OFF_UNIT + 8192;
constexpr int OFF_CS = OFF_B2 + 2048;
constexpr int OFF_RS = OFF_CS + 2560;
constexpr int OFF_BAR = OFF_RS + 512;
enum { B_FULL = 0, B_STATS = 40, B_KV = 45, B_RING = 53, B_WO = 56, B_O = 57, B_SIN = 65, B_UNIT = 66, B_CNT2 = 67,
       B_AFREE = 67, B_ORD = 71, B_QKV = 76, B_CNT4 = 77, B_EMPTY = 77, B_AFREE0 = 82, B_DONE = 83, B_CNT8 = 84, B_TILE = 84, B_OW = 89, B_SOUT = 91, B_NUM = 100 };
constexpr int OFF_TS = OFF_BAR + 1024;
constexpr int SMEM_BYTES = OFF_BAR + B_NUM * 8;
constexpr unsigned FIXED_MASK = 0xB5;
constexpr float P71 = 2361183241434822606848.0f, M71 = 4.235164736271502e-22f;

__device__ __forceinline__ uint32_t exp2_fixed(float lo, float hi, uint32_t half2) {
    uint32_t y, g, d;
    asm("cvt.pack.sat.s16.s32 %0, %1, %2;" : "=r"(y) : "r"(__float_as_uint(hi)), "r"(__float_as_uint(lo)));
    asm("lop3.b32 %0, %1, 0x007F007F, %2, 0xEA;" : "=r"(g) : "r"(y), "r"(half2));
    asm("fma.rn.bf16x2 %0, %1, %2, %3;" : "=r"(d) : "r"(y), "r"(g), "r"(y & 0xFF80FF80u));
    return d;
}
__device__ __forceinline__ uint32_t k_tile_addr(uint32_t base, int tile) {
    const int c = tile >> 2;
    return base + ((tile & 2) ? 98304 + c * 4096 : (2 * c + 1) * 4096) + (tile & 1) * 2048;
}
constexpr uint32_t POS_STD = 0x76543210u, POS_LAST = 0xB75A9640u;

__device__ __forceinline__ void colsum_load(uint32_t blk, int qc, int lane, uint32_t* w) {
#pragma unroll
    for (int j = 0; j < 4; j++)
        asm volatile("ld.shared.v4.b32 {%0,%1,%2,%3}, [%4];" : "=r"(w[4 * j]), "=r"(w[4 * j + 1]), "=r"(w[4 * j + 2]), "=r"(w[4 * j + 3])
                     : "r"(blk + j * 2048 + (lane & 15) * 128 + (((qc * 2 + (lane >> 4)) ^ (lane & 7)) << 4)));
}
__device__ __forceinline__ void colsum_publish(const uint32_t* w, int idx, int lane, uint32_t tag) {
    float c[8];
#pragma unroll
    for (int e = 0; e < 4; e++) {
        c[2 * e] = (bf_lo(w[e]) + bf_lo(w[4 + e])) + (bf_lo(w[8 + e]) + bf_lo(w[12 + e]));
        c[2 * e + 1] = (bf_hi(w[e]) + bf_hi(w[4 + e])) + (bf_hi(w[8 + e]) + bf_hi(w[12 + e]));
    }
#pragma unroll
    for (int n = 4; n > 0; n >>= 1) {
        const bool up = lane & (2 * n);
#pragma unroll
        for (int e = 0; e < n; e++) c[e] = (up ? c[e + n] : c[e]) + __shfl_xor_sync(0xffffffffu, up ? c[e] : c[e + n], 2 * n);
    }
    c[0] += __shfl_xor_sync(0xffffffffu, c[0], 1);
    if (!(lane & 1)) st_tagged(reinterpret_cast<unsigned long long*>(g_cs) + idx + (lane >> 1), __float_as_uint(c[0]), tag);
}

__global__ void __cluster_dims__(2, 1, 1) __launch_bounds__(640, 1)
mega_kernel(const __nv_bfloat16* __restrict__ x, __nv_bfloat16* __restrict__ out,
            const __grid_constant__ CUtensorMap mx, const __grid_constant__ CUtensorMap mqkv, const __grid_constant__ CUtensorMap mw1,
            const __grid_constant__ CUtensorMap mw3, const __grid_constant__ CUtensorMap mw2, const __grid_constant__ CUtensorMap mwo,
            uint32_t half2) {
    extern __shared__ __align__(1024) uint8_t smem_raw[];
    const uint32_t sb = __shfl_sync(0xffffffffu, smem_u32(smem_raw), 0);
    if ((sb & 0xFFFFFF) != SMEM_BASE) __trap();
    const uint32_t bars = sb + OFF_BAR, ring = sb + OFF_RING;
    const int tid = threadIdx.x, lane = tid & 31, g = lane >> 2, t4 = lane & 3;
    const int warp = __shfl_sync(0xffffffffu, tid >> 5, 0), wg = warp >> 2, wq = warp & 3;
    const int rank = blockIdx.x & 1, cl = blockIdx.x >> 1;
    const int grp = cl < 4 ? 4 + cl : cl < 36 ? (cl - 4) >> 3 : 4 + (cl - 36) / 7;
    const int rot = cl < 4 ? 7 : cl < 36 ? (cl - 4) & 7 : (cl - 36) % 7;
    const int mblk = rot * 2 + rank;
    const int nq = grp < 4 ? 2 : 1;
    const int qt0 = grp < 4 ? 2 * grp : 4 + grp;
    const int gu0 = (grp < 4 ? 3 * grp : 4 * grp - 4) - nq;
    const int head = blockIdx.x >> 2, qb = blockIdx.x & 3;

    if (elect_one()) {
#pragma unroll
        for (int i = 0; i < 5; i++) { const int b = warp * 5 + i; mbar_init(bars + 8 * b, b < B_CNT2 ? 1 : b < B_CNT4 ? 2 : b < B_CNT8 ? 4 : 8); }
        if (warp == 0) {
            fence_async_smem();
#pragma unroll
            for (int j = 0; j < 2; j++) {
                tma2d(sb + j * 16384, &mx, j * 64, mblk * 128, bars + 8 * (B_FULL + j));
                tma2d(ring + j * 16384, &mqkv, qt0 * 128, j * 64, bars + 8 * (B_FULL + j));
                tma2d(ring + j * 16384 + 8192, &mqkv, qt0 * 128 + 64, j * 64, bars + 8 * (B_FULL + j));
            }
        }
        if (warp < 8) {
#pragma unroll
            for (int i = 0; i < 5; i++) mbar_expect(bars + 8 * (warp * 5 + i), warp * 5 + i < 8 ? 32768 : 16384);
        }
        if (warp == 16) asm volatile("prefetch.tensormap [%0];" :: "l"(rank ? &mw3 : &mw1) : "memory");
        asm volatile("fence.mbarrier_init.release.cluster;" ::: "memory");
    }
    const uint32_t tag = __ldcg(g_epoch + blockIdx.x) + 1;
    __syncthreads();
    if (tid == 512) TSTAMP(26);
    asm volatile("barrier.cluster.arrive.relaxed.aligned;" ::: "memory");

    if (wg < 4) {
        const int pair = wg >> 1, half = wg & 1;
        if (pair == 1) {
            const int row = mblk * 128 + grp * 16 + (warp - 8) * 2 + (lane >> 4);
            uint32_t w[16], u[16];
            mbar_wait(bars + 8 * B_SIN, 0);
#pragma unroll
            for (int j = 0; j < 4; j++)
                asm volatile("ld.shared.v4.b32 {%0,%1,%2,%3}, [%4];" : "=r"(w[4 * j]), "=r"(w[4 * j + 1]), "=r"(w[4 * j + 2]), "=r"(w[4 * j + 3])
                             : "r"(sb + 7 * 16384 + (warp - 8) * 2048 + (lane >> 4) * 1024 + j * 256 + (lane & 15) * 16));
            colsum_load(sb + 6 * 16384 + half * 8192, wq, lane, u);
            __syncwarp();
            if (elect_one()) mbar_arrive(bars + 8 * B_SOUT);
            colsum_publish(u, ((grp * 5 + half) * 8 + rot) * 128 + rank * 64 + wq * 16, lane, tag);
            float s0 = 0.f, v0 = 0.f;
#pragma unroll
            for (int j = 0; j < 16; j++) s0 += bf_lo(w[j]) + bf_hi(w[j]);
#pragma unroll
            for (int d = 1; d < 16; d <<= 1) s0 += __shfl_xor_sync(0xffffffffu, s0, d);
            const float mean = s0 * (1.0f / DM);
#pragma unroll
            for (int j = 0; j < 16; j++) { const float a = bf_lo(w[j]) - mean, b = bf_hi(w[j]) - mean; v0 += fmaf(a, a, b * b); }
#pragma unroll
            for (int d = 1; d < 16; d <<= 1) v0 += __shfl_xor_sync(0xffffffffu, v0, d);
            if ((lane & 15) == 0) st_tagged(reinterpret_cast<unsigned long long*>(g_rs) + row, pack_bf16(mean, sqrtf(bf_round(bf_round(v0 * (1.0f / DM)) + 1e-5f))), tag);
            if (tid == 256) TSTAMP(40);
        }

        uint32_t q[4], qn[6];
        {
            float acc[64];
            const int rowblk = mblk * 2 + half, tile16 = rowblk * 4 + wq;
            const bool rel = wq < 2 && lane == 0, rel2 = wq == 2 && lane == 0;
            uint32_t empty;
            asm("mapa.shared::cluster.u32 %0, %1, %2;" : "=r"(empty) : "r"(bars + 8 * B_EMPTY), "r"(wq & 1));
#pragma unroll 1
            for (int t = pair; t < 5; t += 2) {
                uint32_t po = t == 4 ? POS_LAST : POS_STD, full = bars + 8 * (B_FULL + 8 * t), slot = (0x24130u >> (4 * t)) & 7, prev = 0;
                uint64_t da = mkdesc(half * 8192, 16, 1024, 1), db = mkdesc(OFF_RING, 8192, 1024, 1) + slot * 1024;
                if (tid == 0 && t == 0) TSTAMP(30);
                mbar_wait(full, 0);
                if (t > 0) mbar_wait(bars + 8 * (B_ORD + t - 1), 0);
#pragma unroll 1
                for (int j = 0; j < 8; j++) {
                    wg_fence();
#pragma unroll
                    for (int k = 0; k < 4; k++) wgmma_ss_n128(acc, da + k * 2, db + k * 128, (j | k) != 0);
                    wg_commit();
                    const uint32_t rel_a = empty + prev * 8, rel_b = bars + 8 * (j == 3 ? B_AFREE0 : B_AFREE + (j >> 1) - 1);
                    const bool do_a = j > 0 && rel, do_b = (po & 8) && rel2;
                    prev = slot; slot = slot == NRING - 1 ? 0 : slot + 1; po >>= 4; full += 8;
                    da = mkdesc(half * 8192, 16, 1024, 1) + (po & 7) * 1024; db = mkdesc(OFF_RING, 8192, 1024, 1) + slot * 1024;
                    if (j < 7) mbar_wait(full, 0); else if (rel2) mbar_arrive(bars + 8 * (B_ORD + t));
                    wg_wait<1>();
                    if (do_a) mbar_arrive_remote(rel_a);
                    if (do_b) mbar_arrive(rel_b);
                }
                if (t >= 3) {
                    mbar_wait(bars + 8 * B_QKV, 0);
                    const uint4* pq = g_q + (head * 128 + (qb * 8 + wg) * 4 + wq) * 32 + lane;
                    const uint4 v = __ldcg(pq), u = __ldcg(pq + 512);
                    qn[0] = v.x; qn[1] = v.y; qn[2] = v.z; qn[3] = v.w; q[0] = u.x; q[1] = u.y; q[2] = u.z; q[3] = u.w;
                }
                wg_wait<0>();
                if (rel) mbar_arrive_remote(empty + prev * 8);
                if (t >= 3 && rel2) mbar_arrive(bars + 8 * (t == 4 ? B_AFREE + 3 : B_AFREE0));
                pin<64>(acc);
                if (wq == 0 && half == 0 && lane == 0) TSTAMP(2 + 2 * t);
                mbar_wait(bars + 8 * (B_STATS + t), 0);
                uint32_t rs0, rs1;
                asm volatile("ld.shared.b32 %0, [%1];" : "=r"(rs0) : "r"(sb + OFF_RS + (half * 64 + wq * 16 + g) * 4));
                asm volatile("ld.shared.b32 %0, [%1];" : "=r"(rs1) : "r"(sb + OFF_RS + (half * 64 + wq * 16 + g + 8) * 4));
                const float m0 = bf_lo(rs0), m1 = bf_lo(rs1);
                float d0 = bf_hi(rs0), d1 = bf_hi(rs1);
#pragma unroll
                for (int j = 0; j < 16; j++) {
                    float c0, c1;
                    asm volatile("ld.shared.v2.f32 {%0,%1}, [%2];" : "=f"(c0), "=f"(c1) : "r"(sb + OFF_CS + (t * 128 + j * 8 + t4 * 2) * 4));
                    acc[4 * j] = fmaf(-m0, c0, acc[4 * j]); acc[4 * j + 1] = fmaf(-m0, c1, acc[4 * j + 1]);
                    acc[4 * j + 2] = fmaf(-m1, c0, acc[4 * j + 2]); acc[4 * j + 3] = fmaf(-m1, c1, acc[4 * j + 3]);
                }
                float r0 = __frcp_rn(d0), r1 = __frcp_rn(d1);
                if (t < nq) {
                    const int qt = qt0 + t, h0 = (qt & 3) * 8;
                    if (qt < 4) {
                        r0 *= 0.25f * 1.4426950408889634f * M71; r1 *= 0.25f * 1.4426950408889634f * M71;
                    } else if (qt < 8) {
                        r0 *= ((FIXED_MASK >> (2 * wq)) & 1) ? M71 : P71; r1 *= ((FIXED_MASK >> (2 * wq + 1)) & 1) ? M71 : P71;
                    }
                    uint32_t* p; int s8, sh;
                    if (qt < 8) { p = reinterpret_cast<uint32_t*>(g_k + h0 * 4096) + tile16 * 128 + lane; s8 = 64; sh = 32; }
                    else        { p = reinterpret_cast<uint32_t*>(g_v + h0 * 4096) + tile16 * 64 + lane;  s8 = 32; sh = 8192; }
#pragma unroll
                    for (int hh = 0; hh < 8; hh++) {
                        const float* a = acc + hh * 8;
                        const uint32_t e0 = pack_bf16(a[0] * r0, a[1] * r0), e1 = pack_bf16(a[2] * r1, a[3] * r1);
                        const uint32_t e2 = pack_bf16(a[4] * r0, a[5] * r0), e3 = pack_bf16(a[6] * r1, a[7] * r1);
                        if (qt < 4) g_q[((h0 + hh) * 128 + tile16) * 32 + lane] = make_uint4(e0, e1, e2, e3);
                        else { uint32_t* pp = p + hh * 16384; pp[0] = e0; pp[s8] = e1; pp[sh] = e2; pp[sh + s8] = e3; }
                    }
                } else {
                    uint32_t* p = reinterpret_cast<uint32_t*>(g_h + (rowblk * 28 + gu0 + t) * 512) + wq * 512 + lane;
                    r0 *= -1.4426950408889634f; r1 *= -1.4426950408889634f; d0 *= d0; d1 *= d1;
#pragma unroll
                    for (int j = 0; j < 8; j++) {
                        const float* a = acc + j * 4; const float* b = a + 32;
                        p[j * 32] = pack_bf16(a[0] * b[0] * rcpf(fmaf(ex2f(a[0] * r0), d0, d0)), a[1] * b[1] * rcpf(fmaf(ex2f(a[1] * r0), d0, d0)));
                        p[256 + j * 32] = pack_bf16(a[2] * b[2] * rcpf(fmaf(ex2f(a[2] * r1), d1, d1)), a[3] * b[3] * rcpf(fmaf(ex2f(a[3] * r1), d1, d1)));
                    }
                }
                __syncwarp();
                if (elect_one()) mbar_arrive(bars + 8 * (B_TILE + t));
                if (wq == 0 && half == 0 && lane == 0) TSTAMP(3 + 2 * t);
            }
        }
        const uint64_t db2 = mkdesc(OFF_B2, 128, 256, 0);
        float s[32];
        auto ref_point = [&](int ntile, uint32_t& b0, uint32_t& b1) {
            float m0 = -INFINITY, m1 = -INFINITY, f0 = -INFINITY, f1 = -INFINITY;
#pragma unroll 1
            for (int t = 0; t < ntile; t++) {
                wg_fence();
                wgmma_rs_n64_zero(s, q, mkdesc(k_tile_addr(0, t), 128, 256, 0));
                wg_commit();
                wg_wait<0>();
                pin<32>(s);
#pragma unroll
                for (int i = 0; i < 8; i++) {
                    if ((FIXED_MASK >> i) & 1) { f0 = fmaxf(f0, fmaxf(s[4 * i], s[4 * i + 1])); f1 = fmaxf(f1, fmaxf(s[4 * i + 2], s[4 * i + 3])); }
                    else                       { m0 = fmaxf(m0, fmaxf(s[4 * i], s[4 * i + 1])); m1 = fmaxf(m1, fmaxf(s[4 * i + 2], s[4 * i + 3])); }
                }
            }
            m0 = fmaxf(m0, f0 * P71 * P71); m1 = fmaxf(m1, f1 * P71 * P71);
            m0 = fmaxf(m0, __shfl_xor_sync(0xffffffffu, m0, 1)); m1 = fmaxf(m1, __shfl_xor_sync(0xffffffffu, m1, 1));
            m0 = fmaxf(m0, __shfl_xor_sync(0xffffffffu, m0, 2)); m1 = fmaxf(m1, __shfl_xor_sync(0xffffffffu, m1, 2));
#pragma unroll
            for (int r = 0; r < 2; r++) {
                const float m = -rintf(r ? m1 : m0), mh = bf_round(m), mm = bf_round(m - mh), ml = m - mh - mm;
                const float lo = t4 == 0 ? mh : t4 == 1 ? ml : t4 == 2 ? 1.f : 0.f, hi = t4 == 0 ? mm : t4 == 1 ? 1.f : 0.f;
                (r ? b1 : b0) = pack_bf16(lo * M71, hi * M71);
            }
        };
        uint32_t q2[4];
        int redo = 1;
        mbar_wait(bars + 8 * B_KV, 0);
#pragma unroll 1
        for (int round = -1; round < 2;) {
            if (redo) ref_point(redo, q2[0], q2[1]);
            if (round < 0) {
#pragma unroll
                for (int i = 0; i < 4; i++) { const uint32_t tq = q[i]; q[i] = qn[i]; qn[i] = tq; }
                qn[4] = q2[0]; qn[5] = q2[1];
                q2[2] = __shfl_sync(0xffffffffu, q2[0], 3); q2[3] = __shfl_sync(0xffffffffu, q2[1], 3);
                round = 0;
                continue;
            }
            float o[12]; uint32_t p[16];
#pragma unroll
            for (int i = 0; i < 12; i++) o[i] = 0.f;
            pin<12>(o); pin<4>(q2);
            if (wq == 0 && half == 0 && lane == 0) TSTAMP(12 + 4 * round + pair);
            uint64_t dk0 = mkdesc(4096, 128, 256, 0), dk1 = mkdesc(98304, 128, 256, 0), dv = mkdesc(0, 128, 65536, 0);
#pragma unroll 1
            for (int c = 0; c < 8; c++, dk0 += 512, dk1 += 256, dv += 512 - (256ull << 32)) {
                if (round == 0) mbar_wait(bars + 8 * (B_KV + c), 0);
#pragma unroll
                for (int t = 0; t < 4; t++) {
                    wg_fence();
                    wgmma_rs_n64_zero(s, q, (t & 2 ? dk1 : dk0) + (t & 1) * 128);
                    wgmma_rs_n64_acc(s, q2, db2);
                    wg_commit();
                    wg_wait<0>();
                    pin<32>(s); pin<16>(p);
#pragma unroll
                    for (int i = 0; i < 16; i++) {
                        if ((FIXED_MASK >> (i >> 1)) & 1) p[i] = exp2_fixed(s[2 * i], s[2 * i + 1], half2);
                        else                              p[i] = pack_bf16(ex2f(s[2 * i]), ex2f(s[2 * i + 1]));
                    }
                    wg_fence();
#pragma unroll
                    for (int k = 0; k < 4; k++) wgmma_rs_n24_acc(o, p + 4 * k, dv + (t * 4 + k) * 16);
                    wg_commit();
                }
            }
            wg_wait<0>();
            pin<12>(o);
            if (redo != 32) {
                float chk = (o[8] + o[10]) * 256.f;
#pragma unroll
                for (int i = 0; i < 8; i++) chk += fabsf(o[i]);
                uint32_t bad;
                asm volatile("{\n.reg .pred p, q;\nsetp.geu.f32 q, %1, 0f7F800000;\nbar.red.or.pred p, %2, 128, q;\nselp.u32 %0, 1, 0, p;\n}" : "=r"(bad) : "f"(chk), "r"(1 + wg) : "memory");
                if (__any_sync(0xffffffffu, bad)) { redo = 32; continue; }
            }
            const int rowblk = qb * 8 + round * 4 + wg;
            const float r0 = rcpf(o[8]), r1 = rcpf(o[10]);
            uint32_t* po = reinterpret_cast<uint32_t*>(g_o + (rowblk * 8 + (head >> 2)) * 512) + wq * 512 + (head & 3) * 64 + lane;
            po[0] = pack_bf16(o[0] * r0, o[1] * r0); po[256] = pack_bf16(o[2] * r1, o[3] * r1);
            po[32] = pack_bf16(o[4] * r0, o[5] * r0); po[288] = pack_bf16(o[6] * r1, o[7] * r1);
            if (round == 0) {
                __syncwarp();
                if (elect_one()) mbar_arrive(bars + 8 * (B_OW + pair));
            } else {
                bar_sync(1 + wg, 128);
                if (wq == 0 && elect_one()) { mbar_arrive(bars + 8 * B_DONE); signal_cnt(C_O + rowblk); }
            }
#pragma unroll
            for (int i = 0; i < 4; i++) q[i] = qn[i];
            q2[0] = qn[4]; q2[1] = qn[5];
            redo = 0;
            if (wq == 0 && half == 0 && lane == 0) TSTAMP(14 + 4 * round + pair);
            round++;
        }
    } else {
        if (wq == 0) {
            asm volatile("barrier.cluster.wait.aligned;" ::: "memory");
            if (tid == 512) TSTAMP(27);
            uint32_t slot = 2, ph = 1;
#pragma unroll 1
            for (int n = 2; n < 40; n++) {
                const int t = n >> 3, j = n & 7;
                const int kc = (n < 32 ? j : (POS_LAST >> (4 * j)) & 7) * 64;
                const CUtensorMap* m = t < nq ? &mqkv : rank ? &mw3 : &mw1;
                const int col = t < nq ? (qt0 + t) * 128 + rank * 64 : (gu0 + t) * 64;
                const uint32_t dst = ring + slot * 16384 + rank * 8192, fb = bars + 8 * (B_FULL + n);
                if (n == 3 && elect_one()) {
                    const uint32_t b = bars + 8 * B_SIN;
                    mbar_expect(b, 32768);
                    bulk_load(sb + 7 * 16384, x + (size_t)(mblk * 128 + grp * 16) * DM, 16384, b);
                    tma2d(sb + 6 * 16384, &mqkv, col, rot * 64, b);
                    tma2d(sb + 6 * 16384 + 8192, nq == 2 ? &mqkv : rank ? &mw3 : &mw1, nq == 2 ? col + 128 : (gu0 + 1) * 64, rot * 64, b);
                }
                if (n == 6) mbar_wait(bars + 8 * B_SOUT, 0);
                if (n < 8 && elect_one()) tma2d(sb + n * 16384, &mx, kc, mblk * 128, fb);
                mbar_wait(bars + 8 * (B_EMPTY + slot), ph);
                if (elect_one()) { TS2(0, n); tma2d_mc(dst, m, col, kc, fb); }
                if (++slot == NRING) { slot = 0; ph ^= 1; }
            }
        } else if (wq == 1) {
            mbar_wait(bars + 8 * B_SOUT, 0);
            __nanosleep(500);
#pragma unroll 1
            for (int t = 0; t < 5; t++) {
                float a[4];
#pragma unroll 1
                for (int n = 0; n < 2000000; n++) {
                    uint32_t stale = 0;
                    a[0] = a[1] = a[2] = a[3] = 0.f;
#pragma unroll
                    for (int i = 0; i < 16; i++) {
                        uint32_t u, v;
                        stale |= ld_tagged2(g_cs + (grp * 5 + t) * 512 + i * 32 + lane, tag, u, v);
                        a[(i & 1) * 2] += __uint_as_float(u); a[(i & 1) * 2 + 1] += __uint_as_float(v);
                    }
                    if (__all_sync(0xffffffffu, stale == 0)) break;
                    __nanosleep(400);
                }
                asm volatile("st.shared.v2.f32 [%0], {%1,%2};" :: "r"(sb + OFF_CS + t * 512 + lane * 8), "f"(a[0]), "f"(a[1]) : "memory");
                asm volatile("st.shared.v2.f32 [%0], {%1,%2};" :: "r"(sb + OFF_CS + t * 512 + 256 + lane * 8), "f"(a[2]), "f"(a[3]) : "memory");
                if (t == 0) {
                    uint32_t a, b, c, d;
#pragma unroll 1
                    for (int n = 0; n < 2000000; n++) {
                        const uint32_t stale = ld_tagged2(g_rs + mblk * 64 + lane * 2, tag, a, b) | ld_tagged2(g_rs + mblk * 64 + lane * 2 + 1, tag, c, d);
                        if (__all_sync(0xffffffffu, stale == 0)) break;
                    }
                    asm volatile("st.shared.v4.b32 [%0], {%1,%2,%3,%4};" :: "r"(sb + OFF_RS + lane * 16), "r"(a), "r"(b), "r"(c), "r"(d) : "memory");
                }
                __syncwarp();
                if (elect_one()) { mbar_arrive(bars + 8 * (B_STATS + t)); TSTAMP(32 + t); }
            }
        } else if (wq == 3) {
            mbar_wait(bars + 8 * B_SOUT, 0);
#pragma unroll 1
            for (int t = 2; t < 5; t++) {
                if (elect_one()) { mbar_expect(bars + 8 * B_UNIT, 8192); tma2d(sb + OFF_UNIT, rank ? &mw3 : &mw1, (gu0 + t) * 64, rot * 64, bars + 8 * B_UNIT); }
                mbar_wait(bars + 8 * B_UNIT, t & 1);
#pragma unroll 1
                for (int qc = 0; qc < 4; qc++) {
                    uint32_t u[16];
                    colsum_load(sb + OFF_UNIT, qc, lane, u);
                    colsum_publish(u, ((grp * 5 + t) * 8 + rot) * 128 + rank * 64 + qc * 16, lane, tag);
                }
                if (lane == 0) TSTAMP(40 + t);
            }
        }
        if (wq == 3) {
            if (lane == 0) g_epoch[blockIdx.x] = tag;
#pragma unroll 1
            for (int i = lane; i < 256; i += 32) asm volatile("st.shared.v4.b32 [%0], {%1,%1,%1,%1};" :: "r"(sb + OFF_ONES + i * 16), "r"(0x3F803F80u) : "memory");
#pragma unroll 1
            for (int i = lane; i < 128; i += 32) {
                const bool fx = (FIXED_MASK >> (i >> 4)) & 1;
                uint32_t a = fx ? pack_bf16(M71, M71) : pack_bf16(P71, P71);
                uint32_t b = fx ? pack_bf16(M71, 47.0f * M71) : pack_bf16(P71, -79.5f * P71);
                uint32_t c = fx ? 0u : pack_bf16(0.08214f * P71, 0.f);
                if (i & 8) a = b = c = 0;
                asm volatile("st.shared.v4.b32 [%0], {%1,%2,%3,%4};" :: "r"(sb + OFF_B2 + i * 16), "r"(a), "r"(b), "r"(c), "r"(0) : "memory");
            }
            fence_async_smem();
            __syncwarp();
            if (elect_one()) mbar_arrive(bars + 8 * B_QKV);
        } else if (wq == 1) {
#pragma unroll 1
            for (int i = 0; i < 3; i++) wait_cnt(C_QKV + i * 4 + (head >> 3), 16 * tag, 100);
            fence_async_all();
            if (elect_one()) { mbar_arrive(bars + 8 * B_QKV); TSTAMP(29); }
            const uint8_t* gk = reinterpret_cast<const uint8_t*>(g_k + head * 4096);
            const uint8_t* gv = reinterpret_cast<const uint8_t*>(g_v + head * 4096);
#pragma unroll 1
            for (int c = 0; c < 8; c++) {
                if (!(c & 1)) mbar_wait(bars + 8 * (c ? B_AFREE + (c >> 1) : B_AFREE0), 0);
                if (elect_one()) {
                    const uint32_t b = bars + 8 * (B_KV + c);
                    mbar_expect(b, 16384);
                    bulk_load(sb + (2 * c + 1) * 4096, gk + c * 8192, 4096, b);
                    bulk_load(sb + 2 * c * 4096, gv + c * 4096, 4096, b);
                    bulk_load(sb + 65536 + c * 4096, gv + 32768 + c * 4096, 4096, b);
                    bulk_load(sb + 98304 + c * 4096, gk + c * 8192 + 4096, 4096, b);
                }
            }
        } else if (wq == 2) {
#pragma unroll 1
            for (int t = 0; t < 5; t++) {
                mbar_wait(bars + 8 * (B_TILE + t), 0);
                if (elect_one()) signal_cnt(t < nq ? C_QKV + qt0 + t : C_H + mblk);
            }
        }
        bar_sync(5, 128);
        const int cb = blockIdx.x & 7, pr = blockIdx.x >> 3;
        const int rb0 = (pr >> 2) * 8 + (pr & 3);
        uint32_t gate[2][16];
        {
            float dn[64];
            auto load_stage = [&](int kb, int st) {
                const uint32_t b = bars + 8 * (B_RING + st), dst = ring + st * 24576;
                mbar_expect(b, 24576);
                bulk_load(dst, g_h + (rb0 * 28 + kb) * 512, 8192, b);
                bulk_load(dst + 8192, g_h + ((rb0 + 4) * 28 + kb) * 512, 8192, b);
                tma2d(dst + 16384, &mw2, cb * 64, kb * 64, b);
            };
            if (wq == 0) {
                wait_cnt(C_H + (rb0 >> 1), 28 * tag, 200);
                wait_cnt(C_H + (rb0 >> 1) + 2, 28 * tag, 200);
                if (elect_one()) { TSTAMP(20); fence_async_all(); load_stage(0, 0); load_stage(1, 1); }
            }
            int st = 0; uint32_t ph = 0;
#pragma unroll 1
            for (int kb = 0; kb < 28; kb++) {
                mbar_wait(bars + 8 * (B_RING + st), ph);
                const uint64_t da = mkdesc(OFF_RING + st * 24576, 128, 1024, 0), db = mkdesc(OFF_RING + st * 24576 + 16384, 8192, 1024, 1);
                wg_fence();
#pragma unroll
                for (int k = 0; k < 4; k++) { wgmma_ss_n64(dn, da + k * 16, db + k * 128, (kb | k) != 0); wgmma_ss_n64(dn + 32, da + 512 + k * 16, db + k * 128, (kb | k) != 0); }
                wg_commit();
                wg_wait<1>();
                if (wq == 0 && kb < 26 && elect_one()) load_stage(kb + 2, st == 0 ? 2 : st - 1);
                if (++st == 3) { st = 0; ph ^= 1; }
            }
            wg_wait<0>();
            pin<64>(dn);
#pragma unroll
            for (int i = 0; i < 32; i++) gate[i >> 4][i & 15] = pack_bf16(siluf(dn[2 * i]), siluf(dn[2 * i + 1]));
        }
        float acc[32];
        if (tid == 512) TSTAMP(21);
        const uint32_t bar_wo = bars + 8 * B_WO;
        if (wq == 0 && elect_one()) {
            mbar_expect(bar_wo, 65536);
#pragma unroll 1
            for (int i = 0; i < 8; i++) tma2d(ring + i * 8192, &mwo, cb * 64, i * 64, bar_wo);
        }
        if (wq >= 2) {
            mbar_wait(bars + 8 * (B_OW + wq - 2), 0);
            if (elect_one()) {
                signal_cnt(C_O + qb * 8 + 2 * wq - 4);
                asm volatile("red.relaxed.gpu.global.add.u32 [%0], 1;" :: "l"(g_cnt + (C_O + qb * 8 + 2 * wq - 3) * 8) : "memory");
            }
        }
#pragma unroll 1
        for (int tl = 0; tl < 2; tl++) {
            const int rb = rb0 + 4 * tl;
            uint32_t xr[16];
            const uint32_t* px = reinterpret_cast<const uint32_t*>(x + (size_t)(rb * 64 + wq * 16 + g) * DM + cb * 64) + t4;
#pragma unroll
            for (int j = 0; j < 8; j++) { xr[2 * j] = __ldg(px + j * 4); xr[2 * j + 1] = __ldg(px + 8 * DM / 2 + j * 4); }
            if (wq == 0) {
                if (tl == 1) mbar_wait(bars + 8 * B_DONE, 0);
                wait_cnt(C_O + rb, 32 * tag, tl ? 20 : 200);
                if (elect_one()) {
                    fence_async_all();
                    TSTAMP(22 + 2 * tl);
#pragma unroll 1
                    for (int i = 0; i < (tl ? 8 : 2); i++) {
                        mbar_expect(bars + 8 * (B_O + i), 8192);
                        bulk_load((tl ? sb : ring + 65536) + i * 8192, g_o + (rb * 8 + i) * 512, 8192, bars + 8 * (B_O + i));
                    }
                }
            }
            if (tl == 0) mbar_wait(bar_wo, 0);
#pragma unroll 1
            for (int kb = 0; kb < 8; kb++) {
                mbar_wait(bars + 8 * (B_O + kb), tl);
                const uint32_t a = tl == 0 ? OFF_RING + 65536 + (kb & 1) * 8192 : kb * 8192;
                const uint64_t da = mkdesc(a, 128, 1024, 0), db = mkdesc(OFF_RING + kb * 8192, 8192, 1024, 1);
                wg_fence();
#pragma unroll
                for (int k = 0; k < 4; k++) wgmma_ss_n64(acc, da + k * 16, db + k * 128, (kb | k) != 0);
                wg_commit();
                if (tl == 0) {
                    wg_wait<0>();
                    bar_sync(5, 128);
                    if (wq == 0 && kb < 6 && elect_one()) { mbar_expect(bars + 8 * (B_O + kb + 2), 8192); bulk_load(sb + a, g_o + (rb * 8 + kb + 2) * 512, 8192, bars + 8 * (B_O + kb + 2)); }
                }
            }
            wg_wait<0>();
            pin<32>(acc);
            uint32_t* po = reinterpret_cast<uint32_t*>(out + (size_t)(rb * 64 + wq * 16 + g) * DM + cb * 64) + t4;
#pragma unroll
            for (int i = 0; i < 16; i++) {
                const uint32_t r = pack_bf16(fmaf(acc[2 * i], bf_lo(gate[0][i]), bf_lo(xr[i])), fmaf(acc[2 * i + 1], bf_hi(gate[0][i]), bf_hi(xr[i])));
                po[(i & 1) * (8 * DM / 2) + (i >> 1) * 4] = r;
                gate[0][i] = gate[1][i];
            }
            if (tid == 512) TSTAMP(23 + 2 * tl);
        }
    }
}

typedef CUresult (*EncodeFn)(CUtensorMap*, CUtensorMapDataType, cuuint32_t, void*, const cuuint64_t*, const cuuint64_t*, const cuuint32_t*,
                             const cuuint32_t*, CUtensorMapInterleave, CUtensorMapSwizzle, CUtensorMapL2promotion, CUtensorMapFloatOOBfill);

void make_map(EncodeFn fn, CUtensorMap* m, const void* p, int rows, int cols, int box_rows) {
    cuuint64_t dims[2] = {(cuuint64_t)cols, (cuuint64_t)rows};
    cuuint64_t strides[1] = {(cuuint64_t)cols * 2};
    cuuint32_t box[2] = {64, (cuuint32_t)box_rows};
    cuuint32_t es[2] = {1, 1};
    fn(m, CU_TENSOR_MAP_DATA_TYPE_BFLOAT16, 2, const_cast<void*>(p), dims, strides, box, es, CU_TENSOR_MAP_INTERLEAVE_NONE,
       CU_TENSOR_MAP_SWIZZLE_128B, CU_TENSOR_MAP_L2_PROMOTION_L2_128B, CU_TENSOR_MAP_FLOAT_OOB_FILL_NONE);
}

}

extern "C" void kernel_launch(void* const* d_in, const int* in_sizes, int n_in, void* d_out, int out_size) {
    const __nv_bfloat16* x = (const __nv_bfloat16*)d_in[0];
    static EncodeFn fn = nullptr;
    if (!fn) {
        cudaDriverEntryPointQueryResult qr;
        cudaGetDriverEntryPoint("cuTensorMapEncodeTiled", (void**)&fn, cudaEnableDefault, &qr);
        cudaFuncSetAttribute(mega_kernel, cudaFuncAttributeMaxDynamicSharedMemorySize, SMEM_BYTES);
    }
    CUtensorMap mx, mqkv, mw1, mw3, mw2, mwo;
    make_map(fn, &mx, d_in[0], SEQ, DM, 128);
    make_map(fn, &mqkv, d_in[1], DM, 3 * DM, 64);
    make_map(fn, &mwo, d_in[2], DM, DM, 64);
    make_map(fn, &mw1, d_in[4], DM, FF, 64);
    make_map(fn, &mw3, d_in[5], DM, FF, 64);
    make_map(fn, &mw2, d_in[6], FF, DM, 64);
    mega_kernel<<<128, 640, SMEM_BYTES, cudaStreamPerThread>>>(x, (__nv_bfloat16*)d_out, mx, mqkv, mw1, mw3, mw2, mwo, 0x3F003F00u);
}
```

```cpp
#include <cuda_runtime.h>
#include <cuda_bf16.h>
#include <cuda.h>
#include <stdint.h>

namespace {

constexpr int SEQ = 2048, DM = 512, FF = 1792;

__device__ uint4 g_q[32 * 128 * 32];
__device__ uint4 g_k[32 * 4096];
__device__ uint4 g_v[32 * 4096];
__device__ uint4 g_h[32 * 28 * 512];
__device__ uint4 g_o[32 * 8 * 512];
__device__ ulonglong2 g_cs[40 * 8 * 64];
__device__ ulonglong2 g_rs[SEQ / 2];
constexpr int C_QKV = 0, C_H = 12, C_O = 28, C_NUM = 60;
__device__ unsigned g_cnt[C_NUM * 8];
__device__ unsigned g_epoch[128];
#define TSTAMP(i)
#define TS2(k, i)

__device__ __forceinline__ uint32_t smem_u32(const void* p) { return (uint32_t)__cvta_generic_to_shared(p); }
__device__ __forceinline__ void mbar_init(uint32_t a, int c) { asm volatile("mbarrier.init.shared::cta.b64 [%0], %1;" :: "r"(a), "r"(c)); }
__device__ __forceinline__ void mbar_expect(uint32_t a, int b) { asm volatile("mbarrier.arrive.expect_tx.shared::cta.b64 _, [%0], %1;" :: "r"(a), "r"(b) : "memory"); }
__device__ __forceinline__ void mbar_arrive(uint32_t a) { asm volatile("mbarrier.arrive.shared::cta.b64 _, [%0];" :: "r"(a) : "memory"); }
__device__ __forceinline__ void mbar_arrive_remote(uint32_t a) { asm volatile("mbarrier.arrive.shared::cluster.b64 _, [%0];" :: "r"(a) : "memory"); }
__device__ __forceinline__ bool mbar_try(uint32_t a, uint32_t ph) {
    uint32_t ok;
    asm volatile("{\n.reg .pred p;\nmbarrier.try_wait.parity.shared::cta.b64 p, [%1], %2;\nselp.u32 %0, 1, 0, p;\n}" : "=r"(ok) : "r"(a), "r"(ph) : "memory");
    return ok;
}
__device__ __forceinline__ void mbar_wait(uint32_t a, uint32_t ph) {
    int n = 1 << 22;
#pragma unroll 1
    do { n = __all_sync(0xffffffffu, mbar_try(a, ph)) ? 0 : n - 1; } while (n > 0);
}
__device__ __forceinline__ bool elect_one() {
    uint32_t p;
    asm volatile("{\n.reg .pred P;\nelect.sync _|P, 0xffffffff;\nselp.u32 %0, 1, 0, P;\n}" : "=r"(p));
    return p;
}
__device__ __forceinline__ void signal_cnt(int c) {
    asm volatile("fence.release.gpu;\nred.relaxed.gpu.global.add.u32 [%0], 1;" :: "l"(g_cnt + c * 8) : "memory");
}
__device__ __forceinline__ void wait_cnt(int c, unsigned target, int ns) {
#pragma unroll 1
    for (int n = 0; n < 2000000; n++) {
        unsigned v;
        asm volatile("ld.relaxed.gpu.global.u32 %0, [%1];" : "=r"(v) : "l"(g_cnt + c * 8) : "memory");
        if (__all_sync(0xffffffffu, (int)(v - target) >= 0)) break;
        __nanosleep(ns);
    }
}
__device__ __forceinline__ uint32_t ld_epoch() {
    uint32_t e;
    asm volatile("ld.relaxed.gpu.global.u32 %0, [%1];" : "=r"(e) : "l"(g_epoch + blockIdx.x) : "memory");
    return e;
}
__device__ __forceinline__ void st_tagged(void* p, uint32_t v, uint32_t tag) {
    asm volatile("st.relaxed.gpu.global.b64 [%0], %1;" :: "l"(p), "l"((unsigned long long)tag << 32 | v) : "memory");
}
__device__ __forceinline__ uint32_t ld_tagged2(const ulonglong2* p, uint32_t tag, uint32_t& a, uint32_t& b) {
    unsigned long long u, v;
    asm volatile("ld.relaxed.gpu.global.v2.b64 {%0,%1}, [%2];" : "=l"(u), "=l"(v) : "l"(p) : "memory");
    a = (uint32_t)u; b = (uint32_t)v;
    return ((uint32_t)(u >> 32) ^ tag) | ((uint32_t)(v >> 32) ^ tag);
}
__device__ __forceinline__ void tma2d(uint32_t dst, const CUtensorMap* m, int c0, int c1, uint32_t bar) {
    asm volatile("cp.async.bulk.tensor.2d.shared::cluster.global.mbarrier::complete_tx::bytes [%0], [%1, {%3, %4}], [%2];"
                 :: "r"(dst), "l"(m), "r"(bar), "r"(c0), "r"(c1) : "memory");
}
__device__ __forceinline__ void tma2d_mc(uint32_t dst, const CUtensorMap* m, int c0, int c1, uint32_t bar) {
    asm volatile("cp.async.bulk.tensor.2d.shared::cluster.global.mbarrier::complete_tx::bytes.multicast::cluster [%0], [%1, {%3, %4}], [%2], %5;"
                 :: "r"(dst), "l"(m), "r"(bar), "r"(c0), "r"(c1), "h"((uint16_t)3) : "memory");
}
__device__ __forceinline__ void bulk_load(uint32_t dst, const void* src, int bytes, uint32_t bar) {
    asm volatile("cp.async.bulk.shared::cluster.global.mbarrier::complete_tx::bytes [%0], [%1], %2, [%3];"
                 :: "r"(dst), "l"(src), "r"(bytes), "r"(bar) : "memory");
}
__device__ __forceinline__ void bar_sync(int id, int n) { asm volatile("bar.sync %0, %1;" :: "r"(id), "r"(n) : "memory"); }
__device__ __forceinline__ void fence_async_smem() { asm volatile("fence.proxy.async.shared::cta;" ::: "memory"); }
__device__ __forceinline__ void fence_async_all() { asm volatile("fence.acquire.gpu;\nfence.proxy.async.global;" ::: "memory"); }
__device__ __forceinline__ void wg_fence() { asm volatile("wgmma.fence.sync.aligned;" ::: "memory"); }
__device__ __forceinline__ void wg_commit() { asm volatile("wgmma.commit_group.sync.aligned;" ::: "memory"); }
template <int N> __device__ __forceinline__ void wg_wait() { asm volatile("wgmma.wait_group.sync.aligned %0;" :: "n"(N) : "memory"); }
template <int N> __device__ __forceinline__ void pin(float* d) {
#pragma unroll
    for (int i = 0; i < N; i++) asm volatile("" : "+f"(d[i]) :: "memory");
}
template <int N> __device__ __forceinline__ void pin(uint32_t* d) {
#pragma unroll
    for (int i = 0; i < N; i++) asm volatile("" : "+r"(d[i]) :: "memory");
}
constexpr uint32_t SMEM_BASE = 1024;
__device__ __forceinline__ uint64_t mkdesc(uint32_t off, uint32_t lbo, uint32_t sbo, uint32_t swz) {
    return (uint64_t)((SMEM_BASE + off) >> 4) | ((uint64_t)(lbo >> 4) << 16) | ((uint64_t)(sbo >> 4) << 32) | ((uint64_t)swz << 62);
}
__device__ __forceinline__ float ex2f(float x) { float y; asm("ex2.approx.ftz.f32 %0, %1;" : "=f"(y) : "f"(x)); return y; }
__device__ __forceinline__ float rcpf(float x) { float y; asm("rcp.approx.ftz.f32 %0, %1;" : "=f"(y) : "f"(x)); return y; }
__device__ __forceinline__ uint32_t pack_bf16(float lo, float hi) { uint32_t r; asm("cvt.rn.bf16x2.f32 %0, %1, %2;" : "=r"(r) : "f"(hi), "f"(lo)); return r; }
__device__ __forceinline__ float bf_lo(uint32_t v) { return __uint_as_float(v << 16); }
__device__ __forceinline__ float bf_hi(uint32_t v) { return __uint_as_float(v & 0xFFFF0000u); }
__device__ __forceinline__ float bf_round(float x) { return __bfloat162float(__float2bfloat16_rn(x)); }
__device__ __forceinline__ float siluf(float g) { return g * rcpf(1.0f + ex2f(g * -1.4426950408889634f)); }

__device__ __forceinline__ void wgmma_ss_n256(float* d, uint64_t da, uint64_t db, int acc) {
    asm volatile("{\n.reg .pred p;\nsetp.ne.b32 p, %130, 0;\nwgmma.mma_async.sync.aligned.m64n256k16.f32.bf16.bf16 {"
        "%0,%1,%2,%3,%4,%5,%6,%7,%8,%9,%10,%11,%12,%13,%14,%15,%16,%17,%18,%19,%20,%21,%22,%23,%24,%25,%26,%27,%28,%29,%30,%31,%32,%33,%34,%35,%36,%37,%38,%39,"
        "%40,%41,%42,%43,%44,%45,%46,%47,%48,%49,%50,%51,%52,%53,%54,%55,%56,%57,%58,%59,%60,%61,%62,%63,%64,%65,%66,%67,%68,%69,%70,%71,%72,%73,%74,%75,%76,"
        "%77,%78,%79,%80,%81,%82,%83,%84,%85,%86,%87,%88,%89,%90,%91,%92,%93,%94,%95,%96,%97,%98,%99,%100,%101,%102,%103,%104,%105,%106,%107,%108,%109,%110,"
        "%111,%112,%113,%114,%115,%116,%117,%118,%119,%120,%121,%122,%123,%124,%125,%126,%127"
        "}, %128, %129, p, 1, 1, 0, 1;\n}\n"
        : "+f"(d[0]),"+f"(d[1]),"+f"(d[2]),"+f"(d[3]),"+f"(d[4]),"+f"(d[5]),"+f"(d[6]),"+f"(d[7]),"+f"(d[8]),"+f"(d[9]),"+f"(d[10]),"+f"(d[11]),"+f"(d[12]),
          "+f"(d[13]),"+f"(d[14]),"+f"(d[15]),"+f"(d[16]),"+f"(d[17]),"+f"(d[18]),"+f"(d[19]),"+f"(d[20]),"+f"(d[21]),"+f"(d[22]),"+f"(d[23]),"+f"(d[24]),
          "+f"(d[25]),"+f"(d[26]),"+f"(d[27]),"+f"(d[28]),"+f"(d[29]),"+f"(d[30]),"+f"(d[31]),"+f"(d[32]),"+f"(d[33]),"+f"(d[34]),"+f"(d[35]),"+f"(d[36]),
          "+f"(d[37]),"+f"(d[38]),"+f"(d[39]),"+f"(d[40]),"+f"(d[41]),"+f"(d[42]),"+f"(d[43]),"+f"(d[44]),"+f"(d[45]),"+f"(d[46]),"+f"(d[47]),"+f"(d[48]),
          "+f"(d[49]),"+f"(d[50]),"+f"(d[51]),"+f"(d[52]),"+f"(d[53]),"+f"(d[54]),"+f"(d[55]),"+f"(d[56]),"+f"(d[57]),"+f"(d[58]),"+f"(d[59]),"+f"(d[60]),
          "+f"(d[61]),"+f"(d[62]),"+f"(d[63]),"+f"(d[64]),"+f"(d[65]),"+f"(d[66]),"+f"(d[67]),"+f"(d[68]),"+f"(d[69]),"+f"(d[70]),"+f"(d[71]),"+f"(d[72]),
          "+f"(d[73]),"+f"(d[74]),"+f"(d[75]),"+f"(d[76]),"+f"(d[77]),"+f"(d[78]),"+f"(d[79]),"+f"(d[80]),"+f"(d[81]),"+f"(d[82]),"+f"(d[83]),"+f"(d[84]),
          "+f"(d[85]),"+f"(d[86]),"+f"(d[87]),"+f"(d[88]),"+f"(d[89]),"+f"(d[90]),"+f"(d[91]),"+f"(d[92]),"+f"(d[93]),"+f"(d[94]),"+f"(d[95]),"+f"(d[96]),
          "+f"(d[97]),"+f"(d[98]),"+f"(d[99]),"+f"(d[100]),"+f"(d[101]),"+f"(d[102]),"+f"(d[103]),"+f"(d[104]),"+f"(d[105]),"+f"(d[106]),"+f"(d[107]),
          "+f"(d[108]),"+f"(d[109]),"+f"(d[110]),"+f"(d[111]),"+f"(d[112]),"+f"(d[113]),"+f"(d[114]),"+f"(d[115]),"+f"(d[116]),"+f"(d[117]),"+f"(d[118]),
          "+f"(d[119]),"+f"(d[120]),"+f"(d[121]),"+f"(d[122]),"+f"(d[123]),"+f"(d[124]),"+f"(d[125]),"+f"(d[126]),"+f"(d[127])
        : "l"(da), "l"(db), "r"(acc));
}
__device__ __forceinline__ void wgmma_ss_n128(float* d, uint64_t da, uint64_t db, int acc) {
    asm volatile("{\n.reg .pred p;\nsetp.ne.b32 p, %66, 0;\nwgmma.mma_async.sync.aligned.m64n128k16.f32.bf16.bf16 {"
        "%0,%1,%2,%3,%4,%5,%6,%7,%8,%9,%10,%11,%12,%13,%14,%15,%16,%17,%18,%19,%20,%21,%22,%23,%24,%25,%26,%27,%28,%29,%30,%31,%32,%33,%34,%35,%36,%37,%38,%39,"
        "%40,%41,%42,%43,%44,%45,%46,%47,%48,%49,%50,%51,%52,%53,%54,%55,%56,%57,%58,%59,%60,%61,%62,%63"
        "}, %64, %65, p, 1, 1, 0, 1;\n}\n"
        : "+f"(d[0]),"+f"(d[1]),"+f"(d[2]),"+f"(d[3]),"+f"(d[4]),"+f"(d[5]),"+f"(d[6]),"+f"(d[7]),"+f"(d[8]),"+f"(d[9]),"+f"(d[10]),"+f"(d[11]),"+f"(d[12]),
          "+f"(d[13]),"+f"(d[14]),"+f"(d[15]),"+f"(d[16]),"+f"(d[17]),"+f"(d[18]),"+f"(d[19]),"+f"(d[20]),"+f"(d[21]),"+f"(d[22]),"+f"(d[23]),"+f"(d[24]),
          "+f"(d[25]),"+f"(d[26]),"+f"(d[27]),"+f"(d[28]),"+f"(d[29]),"+f"(d[30]),"+f"(d[31]),"+f"(d[32]),"+f"(d[33]),"+f"(d[34]),"+f"(d[35]),"+f"(d[36]),
          "+f"(d[37]),"+f"(d[38]),"+f"(d[39]),"+f"(d[40]),"+f"(d[41]),"+f"(d[42]),"+f"(d[43]),"+f"(d[44]),"+f"(d[45]),"+f"(d[46]),"+f"(d[47]),"+f"(d[48]),
          "+f"(d[49]),"+f"(d[50]),"+f"(d[51]),"+f"(d[52]),"+f"(d[53]),"+f"(d[54]),"+f"(d[55]),"+f"(d[56]),"+f"(d[57]),"+f"(d[58]),"+f"(d[59]),"+f"(d[60]),
          "+f"(d[61]),"+f"(d[62]),"+f"(d[63])
        : "l"(da), "l"(db), "r"(acc));
}
__device__ __forceinline__ void wgmma_ss_n64(float* d, uint64_t da, uint64_t db, int acc) {
    asm volatile("{\n.reg .pred p;\nsetp.ne.b32 p, %34, 0;\nwgmma.mma_async.sync.aligned.m64n64k16.f32.bf16.bf16 {"
        "%0,%1,%2,%3,%4,%5,%6,%7,%8,%9,%10,%11,%12,%13,%14,%15,%16,%17,%18,%19,%20,%21,%22,%23,%24,%25,%26,%27,%28,%29,%30,%31"
        "}, %32, %33, p, 1, 1, 0, 1;\n}\n"
        : "+f"(d[0]),"+f"(d[1]),"+f"(d[2]),"+f"(d[3]),"+f"(d[4]),"+f"(d[5]),"+f"(d[6]),"+f"(d[7]),"+f"(d[8]),"+f"(d[9]),"+f"(d[10]),"+f"(d[11]),"+f"(d[12]),
          "+f"(d[13]),"+f"(d[14]),"+f"(d[15]),"+f"(d[16]),"+f"(d[17]),"+f"(d[18]),"+f"(d[19]),"+f"(d[20]),"+f"(d[21]),"+f"(d[22]),"+f"(d[23]),"+f"(d[24]),
          "+f"(d[25]),"+f"(d[26]),"+f"(d[27]),"+f"(d[28]),"+f"(d[29]),"+f"(d[30]),"+f"(d[31])
        : "l"(da), "l"(db), "r"(acc));
}
__device__ __forceinline__ void wgmma_rs_n64_zero(float* d, const uint32_t* a, uint64_t db) {
    asm volatile("wgmma.mma_async.sync.aligned.m64n64k16.f32.bf16.bf16 {"
        "%0,%1,%2,%3,%4,%5,%6,%7,%8,%9,%10,%11,%12,%13,%14,%15,%16,%17,%18,%19,%20,%21,%22,%23,%24,%25,%26,%27,%28,%29,%30,%31"
        "}, {%32,%33,%34,%35}, %36, 0, 1, 1, 0;\n"
        : "=f"(d[0]),"=f"(d[1]),"=f"(d[2]),"=f"(d[3]),"=f"(d[4]),"=f"(d[5]),"=f"(d[6]),"=f"(d[7]),"=f"(d[8]),"=f"(d[9]),"=f"(d[10]),"=f"(d[11]),"=f"(d[12]),
          "=f"(d[13]),"=f"(d[14]),"=f"(d[15]),"=f"(d[16]),"=f"(d[17]),"=f"(d[18]),"=f"(d[19]),"=f"(d[20]),"=f"(d[21]),"=f"(d[22]),"=f"(d[23]),"=f"(d[24]),
          "=f"(d[25]),"=f"(d[26]),"=f"(d[27]),"=f"(d[28]),"=f"(d[29]),"=f"(d[30]),"=f"(d[31])
        : "r"(a[0]), "r"(a[1]), "r"(a[2]), "r"(a[3]), "l"(db));
}
__device__ __forceinline__ void wgmma_rs_n64_acc(float* d, const uint32_t* a, uint64_t db) {
    asm volatile("wgmma.mma_async.sync.aligned.m64n64k16.f32.bf16.bf16 {"
        "%0,%1,%2,%3,%4,%5,%6,%7,%8,%9,%10,%11,%12,%13,%14,%15,%16,%17,%18,%19,%20,%21,%22,%23,%24,%25,%26,%27,%28,%29,%30,%31"
        "}, {%32,%33,%34,%35}, %36, 1, 1, 1, 0;\n"
        : "+f"(d[0]),"+f"(d[1]),"+f"(d[2]),"+f"(d[3]),"+f"(d[4]),"+f"(d[5]),"+f"(d[6]),"+f"(d[7]),"+f"(d[8]),"+f"(d[9]),"+f"(d[10]),"+f"(d[11]),"+f"(d[12]),
          "+f"(d[13]),"+f"(d[14]),"+f"(d[15]),"+f"(d[16]),"+f"(d[17]),"+f"(d[18]),"+f"(d[19]),"+f"(d[20]),"+f"(d[21]),"+f"(d[22]),"+f"(d[23]),"+f"(d[24]),
          "+f"(d[25]),"+f"(d[26]),"+f"(d[27]),"+f"(d[28]),"+f"(d[29]),"+f"(d[30]),"+f"(d[31])
        : "r"(a[0]), "r"(a[1]), "r"(a[2]), "r"(a[3]), "l"(db));
}
__device__ __forceinline__ void wgmma_rs_n24_acc(float* d, const uint32_t* a, uint64_t db) {
    asm volatile("wgmma.mma_async.sync.aligned.m64n24k16.f32.bf16.bf16 {"
        "%0,%1,%2,%3,%4,%5,%6,%7,%8,%9,%10,%11"
        "}, {%12,%13,%14,%15}, %16, 1, 1, 1, 1;\n"
        : "+f"(d[0]),"+f"(d[1]),"+f"(d[2]),"+f"(d[3]),"+f"(d[4]),"+f"(d[5]),"+f"(d[6]),"+f"(d[7]),"+f"(d[8]),"+f"(d[9]),"+f"(d[10]),"+f"(d[11])
        : "r"(a[0]), "r"(a[1]), "r"(a[2]), "r"(a[3]), "l"(db));
}
__device__ __forceinline__ void wgmma_rs_n24_zero(float* d, const uint32_t* a, uint64_t db) {
    asm volatile("wgmma.mma_async.sync.aligned.m64n24k16.f32.bf16.bf16 {"
        "%0,%1,%2,%3,%4,%5,%6,%7,%8,%9,%10,%11"
        "}, {%12,%13,%14,%15}, %16, 0, 1, 1, 1;\n"
        : "=f"(d[0]),"=f"(d[1]),"=f"(d[2]),"=f"(d[3]),"=f"(d[4]),"=f"(d[5]),"=f"(d[6]),"=f"(d[7]),"=f"(d[8]),"=f"(d[9]),"=f"(d[10]),"=f"(d[11])
        : "r"(a[0]), "r"(a[1]), "r"(a[2]), "r"(a[3]), "l"(db));
}

constexpr int OFF_ONES = 131072;
constexpr int OFF_RING = OFF_ONES + 4096;
constexpr int NRING = 5;
constexpr int OFF_B2 = OFF_RING + NRING * 16384;
constexpr int OFF_CS = OFF_B2 + 2048;
constexpr int OFF_RS = OFF_CS + 2560;
constexpr int OFF_BAR = OFF_RS + 1024;
enum { B_FULL = 0, B_STATS = 40, B_KV = 45, B_RING = 53, B_WO = 56, B_O = 57, B_CNT2 = 65,
       B_AFREE = 65, B_ORD = 69, B_QKV = 74, B_CNT4 = 75, B_EMPTY = 75, B_AFREE0 = 80, B_DONE = 81, B_CNT8 = 82, B_TILE = 82, B_OW = 87, B_NUM = 100 };
constexpr int OFF_TS = OFF_BAR + 1024;
constexpr int SMEM_BYTES = OFF_BAR + B_NUM * 8;
constexpr unsigned FIXED_MASK = 0xB5;
constexpr float P71 = 2361183241434822606848.0f, M71 = 4.235164736271502e-22f;

__device__ __forceinline__ uint32_t exp2_fixed(float lo, float hi, uint32_t half2) {
    uint32_t y, g, d;
    asm("cvt.pack.sat.s16.s32 %0, %1, %2;" : "=r"(y) : "r"(__float_as_uint(hi)), "r"(__float_as_uint(lo)));
    asm("lop3.b32 %0, %1, 0x007F007F, %2, 0xEA;" : "=r"(g) : "r"(y), "r"(half2));
    asm("fma.rn.bf16x2 %0, %1, %2, %3;" : "=r"(d) : "r"(y), "r"(g), "r"(y & 0xFF80FF80u));
    return d;
}
__device__ __forceinline__ uint32_t k_tile_addr(uint32_t base, int tile) {
    const int c = tile >> 2;
    return base + ((tile & 2) ? 98304 + c * 4096 : (2 * c + 1) * 4096) + (tile & 1) * 2048;
}
constexpr uint32_t POS_STD = 0x76543210u, POS_LAST = 0xB75A9640u;

__global__ void __cluster_dims__(2, 1, 1) __launch_bounds__(640, 1)
mega_kernel(const __nv_bfloat16* __restrict__ x, const __nv_bfloat16* __restrict__ wqkv, const __nv_bfloat16* __restrict__ w1,
            const __nv_bfloat16* __restrict__ w3, __nv_bfloat16* __restrict__ out,
            const __grid_constant__ CUtensorMap mx, const __grid_constant__ CUtensorMap mqkv, const __grid_constant__ CUtensorMap mw1,
            const __grid_constant__ CUtensorMap mw3, const __grid_constant__ CUtensorMap mw2, const __grid_constant__ CUtensorMap mwo,
            uint32_t half2) {
    extern __shared__ __align__(1024) uint8_t smem_raw[];
    const uint32_t sb = __shfl_sync(0xffffffffu, smem_u32(smem_raw), 0);
    if ((sb & 0xFFFFFF) != SMEM_BASE) __trap();
    const uint32_t bars = sb + OFF_BAR, ring = sb + OFF_RING;
    const int tid = threadIdx.x, lane = tid & 31, g = lane >> 2, t4 = lane & 3;
    const int warp = __shfl_sync(0xffffffffu, tid >> 5, 0), wg = warp >> 2, wq = warp & 3;
    const int rank = blockIdx.x & 1, cl = blockIdx.x >> 1;
    const int grp = cl < 4 ? 4 + cl : cl < 36 ? (cl - 4) >> 3 : 4 + (cl - 36) / 7;
    const int rot = cl < 4 ? 7 : cl < 36 ? (cl - 4) & 7 : (cl - 36) % 7;
    const int mblk = rot * 2 + rank;
    const int nq = grp < 4 ? 2 : 1;
    const int qt0 = grp < 4 ? 2 * grp : 4 + grp;
    const int gu0 = (grp < 4 ? 3 * grp : 4 * grp - 4) - nq;
    const int head = blockIdx.x >> 2, qb = blockIdx.x & 3;

    if (elect_one()) {
#pragma unroll
        for (int i = 0; i < 5; i++) { const int b = warp * 5 + i; mbar_init(bars + 8 * b, b < B_CNT2 ? 1 : b < B_CNT4 ? 2 : b < B_CNT8 ? 4 : 8); }
        if (warp == 0) {
            fence_async_smem();
#pragma unroll
            for (int j = 0; j < 2; j++) {
                tma2d(sb + j * 16384, &mx, j * 64, mblk * 128, bars + 8 * (B_FULL + j));
                tma2d(ring + j * 16384, &mqkv, qt0 * 128, j * 64, bars + 8 * (B_FULL + j));
                tma2d(ring + j * 16384 + 8192, &mqkv, qt0 * 128 + 64, j * 64, bars + 8 * (B_FULL + j));
            }
        }
        if (warp < 8) {
#pragma unroll
            for (int i = 0; i < 5; i++) mbar_expect(bars + 8 * (warp * 5 + i), warp * 5 + i < 8 ? 32768 : 16384);
        }
        if (warp == 16) asm volatile("prefetch.tensormap [%0];" :: "l"(rank ? &mw3 : &mw1) : "memory");
        asm volatile("fence.mbarrier_init.release.cluster;" ::: "memory");
    }
    __syncthreads();
    if (tid == 512) TSTAMP(26);
    asm volatile("barrier.cluster.arrive.relaxed.aligned;" ::: "memory");

    if (wg < 4) {
        const int pair = wg >> 1, half = wg & 1;
        if (pair == 1) {
            const int row = mblk * 128 + grp * 16 + (warp - 8) * 2 + (lane >> 4);
            const uint32_t tag = ld_epoch() + 1;
            uint4 v[4];
            const uint32_t* w = reinterpret_cast<const uint32_t*>(v);
#pragma unroll
            for (int j = 0; j < 4; j++) v[j] = __ldg(reinterpret_cast<const uint4*>(x + (size_t)row * DM) + j * 16 + (lane & 15));
            float s0 = 0.f, v0 = 0.f;
#pragma unroll
            for (int j = 0; j < 16; j++) s0 += bf_lo(w[j]) + bf_hi(w[j]);
#pragma unroll
            for (int d = 1; d < 16; d <<= 1) s0 += __shfl_xor_sync(0xffffffffu, s0, d);
            const float mean = s0 * (1.0f / DM);
#pragma unroll
            for (int j = 0; j < 16; j++) { const float a = bf_lo(w[j]) - mean, b = bf_hi(w[j]) - mean; v0 += fmaf(a, a, b * b); }
#pragma unroll
            for (int d = 1; d < 16; d <<= 1) v0 += __shfl_xor_sync(0xffffffffu, v0, d);
            if ((lane & 15) == 0) st_tagged(reinterpret_cast<unsigned long long*>(g_rs) + row, pack_bf16(mean, sqrtf(bf_round(bf_round(v0 * (1.0f / DM)) + 1e-5f))), tag);
            if (tid == 256) TSTAMP(45);
        }

        uint32_t q[4], qn[6];
        {
            float acc[64];
            const int rowblk = mblk * 2 + half, tile16 = rowblk * 4 + wq;
            const bool rel = wq < 2 && lane == 0, rel2 = wq == 2 && lane == 0;
            uint32_t empty;
            asm("mapa.shared::cluster.u32 %0, %1, %2;" : "=r"(empty) : "r"(bars + 8 * B_EMPTY), "r"(wq & 1));
#pragma unroll 1
            for (int t = pair; t < 5; t += 2) {
                uint32_t po = t == 4 ? POS_LAST : POS_STD, full = bars + 8 * (B_FULL + 8 * t), slot = (0x24130u >> (4 * t)) & 7, prev = 0;
                uint64_t da = mkdesc(half * 8192, 16, 1024, 1), db = mkdesc(OFF_RING, 8192, 1024, 1) + slot * 1024;
                if (tid == 0 && t == 0) TSTAMP(30);
                mbar_wait(full, 0);
                if (t > 0) mbar_wait(bars + 8 * (B_ORD + t - 1), 0);
#pragma unroll 1
                for (int j = 0; j < 8; j++) {
                    wg_fence();
#pragma unroll
                    for (int k = 0; k < 4; k++) wgmma_ss_n128(acc, da + k * 2, db + k * 128, (j | k) != 0);
                    wg_commit();
                    const uint32_t rel_a = empty + prev * 8, rel_b = bars + 8 * (j == 3 ? B_AFREE0 : B_AFREE + (j >> 1) - 1);
                    const bool do_a = j > 0 && rel, do_b = (po & 8) && rel2;
                    prev = slot; slot = slot == NRING - 1 ? 0 : slot + 1; po >>= 4; full += 8;
                    da = mkdesc(half * 8192, 16, 1024, 1) + (po & 7) * 1024; db = mkdesc(OFF_RING, 8192, 1024, 1) + slot * 1024;
                    if (j < 7) mbar_wait(full, 0); else if (rel2) mbar_arrive(bars + 8 * (B_ORD + t));
                    wg_wait<1>();
                    if (do_a) mbar_arrive_remote(rel_a);
                    if (do_b) mbar_arrive(rel_b);
                }
                if (t >= 3) {
                    mbar_wait(bars + 8 * B_QKV, 0);
                    const uint4* pq = g_q + (head * 128 + (qb * 8 + wg) * 4 + wq) * 32 + lane;
                    const uint4 v = __ldcg(pq), u = __ldcg(pq + 512);
                    qn[0] = v.x; qn[1] = v.y; qn[2] = v.z; qn[3] = v.w; q[0] = u.x; q[1] = u.y; q[2] = u.z; q[3] = u.w;
                }
                wg_wait<0>();
                if (rel) mbar_arrive_remote(empty + prev * 8);
                if (t >= 3 && rel2) mbar_arrive(bars + 8 * (t == 4 ? B_AFREE + 3 : B_AFREE0));
                pin<64>(acc);
                if (wq == 0 && half == 0 && lane == 0) TSTAMP(2 + 2 * t);
                mbar_wait(bars + 8 * (B_STATS + t), 0);
                uint32_t rs0, rs1;
                asm volatile("ld.shared.b32 %0, [%1];" : "=r"(rs0) : "r"(sb + OFF_RS + (half * 64 + wq * 16 + g) * 4));
                asm volatile("ld.shared.b32 %0, [%1];" : "=r"(rs1) : "r"(sb + OFF_RS + (half * 64 + wq * 16 + g + 8) * 4));
                const float m0 = bf_lo(rs0), m1 = bf_lo(rs1);
                float d0 = bf_hi(rs0), d1 = bf_hi(rs1);
#pragma unroll
                for (int j = 0; j < 16; j++) {
                    float c0, c1;
                    asm volatile("ld.shared.v2.f32 {%0,%1}, [%2];" : "=f"(c0), "=f"(c1) : "r"(sb + OFF_CS + (t * 128 + j * 8 + t4 * 2) * 4));
                    acc[4 * j] = fmaf(-m0, c0, acc[4 * j]); acc[4 * j + 1] = fmaf(-m0, c1, acc[4 * j + 1]);
                    acc[4 * j + 2] = fmaf(-m1, c0, acc[4 * j + 2]); acc[4 * j + 3] = fmaf(-m1, c1, acc[4 * j + 3]);
                }
                float r0 = __frcp_rn(d0), r1 = __frcp_rn(d1);
                if (t < nq) {
                    const int qt = qt0 + t, h0 = (qt & 3) * 8;
                    if (qt < 4) {
                        r0 *= 0.25f * 1.4426950408889634f * M71; r1 *= 0.25f * 1.4426950408889634f * M71;
                    } else if (qt < 8) {
                        r0 *= ((FIXED_MASK >> (2 * wq)) & 1) ? M71 : P71; r1 *= ((FIXED_MASK >> (2 * wq + 1)) & 1) ? M71 : P71;
                    }
                    uint32_t* p; int s8, sh;
                    if (qt < 8) { p = reinterpret_cast<uint32_t*>(g_k + h0 * 4096) + tile16 * 128 + lane; s8 = 64; sh = 32; }
                    else        { p = reinterpret_cast<uint32_t*>(g_v + h0 * 4096) + tile16 * 64 + lane;  s8 = 32; sh = 8192; }
#pragma unroll
                    for (int hh = 0; hh < 8; hh++) {
                        const float* a = acc + hh * 8;
                        const uint32_t e0 = pack_bf16(a[0] * r0, a[1] * r0), e1 = pack_bf16(a[2] * r1, a[3] * r1);
                        const uint32_t e2 = pack_bf16(a[4] * r0, a[5] * r0), e3 = pack_bf16(a[6] * r1, a[7] * r1);
                        if (qt < 4) g_q[((h0 + hh) * 128 + tile16) * 32 + lane] = make_uint4(e0, e1, e2, e3);
                        else { uint32_t* pp = p + hh * 16384; pp[0] = e0; pp[s8] = e1; pp[sh] = e2; pp[sh + s8] = e3; }
                    }
                } else {
                    uint32_t* p = reinterpret_cast<uint32_t*>(g_h + (rowblk * 28 + gu0 + t) * 512) + wq * 512 + lane;
                    r0 *= -1.4426950408889634f; r1 *= -1.4426950408889634f; d0 *= d0; d1 *= d1;
#pragma unroll
                    for (int j = 0; j < 8; j++) {
                        const float* a = acc + j * 4; const float* b = a + 32;
                        p[j * 32] = pack_bf16(a[0] * b[0] * rcpf(fmaf(ex2f(a[0] * r0), d0, d0)), a[1] * b[1] * rcpf(fmaf(ex2f(a[1] * r0), d0, d0)));
                        p[256 + j * 32] = pack_bf16(a[2] * b[2] * rcpf(fmaf(ex2f(a[2] * r1), d1, d1)), a[3] * b[3] * rcpf(fmaf(ex2f(a[3] * r1), d1, d1)));
                    }
                }
                __syncwarp();
                if (elect_one()) mbar_arrive(bars + 8 * (B_TILE + t));
                if (wq == 0 && half == 0 && lane == 0) TSTAMP(3 + 2 * t);
            }
        }
        const uint64_t db2 = mkdesc(OFF_B2, 128, 256, 0);
        float s[32];
        auto ref_point = [&](int ntile, uint32_t& b0, uint32_t& b1) {
            float m0 = -INFINITY, m1 = -INFINITY, f0 = -INFINITY, f1 = -INFINITY;
#pragma unroll 1
            for (int t = 0; t < ntile; t++) {
                wg_fence();
                wgmma_rs_n64_zero(s, q, mkdesc(k_tile_addr(0, t), 128, 256, 0));
                wg_commit();
                wg_wait<0>();
                pin<32>(s);
#pragma unroll
                for (int i = 0; i < 8; i++) {
                    if ((FIXED_MASK >> i) & 1) { f0 = fmaxf(f0, fmaxf(s[4 * i], s[4 * i + 1])); f1 = fmaxf(f1, fmaxf(s[4 * i + 2], s[4 * i + 3])); }
                    else                       { m0 = fmaxf(m0, fmaxf(s[4 * i], s[4 * i + 1])); m1 = fmaxf(m1, fmaxf(s[4 * i + 2], s[4 * i + 3])); }
                }
            }
            m0 = fmaxf(m0, f0 * P71 * P71); m1 = fmaxf(m1, f1 * P71 * P71);
            m0 = fmaxf(m0, __shfl_xor_sync(0xffffffffu, m0, 1)); m1 = fmaxf(m1, __shfl_xor_sync(0xffffffffu, m1, 1));
            m0 = fmaxf(m0, __shfl_xor_sync(0xffffffffu, m0, 2)); m1 = fmaxf(m1, __shfl_xor_sync(0xffffffffu, m1, 2));
#pragma unroll
            for (int r = 0; r < 2; r++) {
                const float m = -rintf(r ? m1 : m0), mh = bf_round(m), mm = bf_round(m - mh), ml = m - mh - mm;
                const float lo = t4 == 0 ? mh : t4 == 1 ? ml : t4 == 2 ? 1.f : 0.f, hi = t4 == 0 ? mm : t4 == 1 ? 1.f : 0.f;
                (r ? b1 : b0) = pack_bf16(lo * M71, hi * M71);
            }
        };
        uint32_t q2[4];
        int redo = 1;
        mbar_wait(bars + 8 * B_KV, 0);
#pragma unroll 1
        for (int round = -1; round < 2;) {
            if (redo) ref_point(redo, q2[0], q2[1]);
            if (round < 0) {
#pragma unroll
                for (int i = 0; i < 4; i++) { const uint32_t tq = q[i]; q[i] = qn[i]; qn[i] = tq; }
                qn[4] = q2[0]; qn[5] = q2[1];
                q2[2] = __shfl_sync(0xffffffffu, q2[0], 3); q2[3] = __shfl_sync(0xffffffffu, q2[1], 3);
                round = 0;
                continue;
            }
            float o[12]; uint32_t p[16];
#pragma unroll
            for (int i = 0; i < 12; i++) o[i] = 0.f;
            pin<12>(o); pin<4>(q2);
            if (wq == 0 && half == 0 && lane == 0) TSTAMP(12 + 4 * round + pair);
            uint64_t dk0 = mkdesc(4096, 128, 256, 0), dk1 = mkdesc(98304, 128, 256, 0), dv = mkdesc(0, 128, 65536, 0);
#pragma unroll 1
            for (int c = 0; c < 8; c++, dk0 += 512, dk1 += 256, dv += 512 - (256ull << 32)) {
                if (round == 0) mbar_wait(bars + 8 * (B_KV + c), 0);
#pragma unroll
                for (int t = 0; t < 4; t++) {
                    wg_fence();
                    wgmma_rs_n64_zero(s, q, (t & 2 ? dk1 : dk0) + (t & 1) * 128);
                    wgmma_rs_n64_acc(s, q2, db2);
                    wg_commit();
                    wg_wait<0>();
                    pin<32>(s); pin<16>(p);
#pragma unroll
                    for (int i = 0; i < 16; i++) {
                        if ((FIXED_MASK >> (i >> 1)) & 1) p[i] = exp2_fixed(s[2 * i], s[2 * i + 1], half2);
                        else                              p[i] = pack_bf16(ex2f(s[2 * i]), ex2f(s[2 * i + 1]));
                    }
                    wg_fence();
#pragma unroll
                    for (int k = 0; k < 4; k++) wgmma_rs_n24_acc(o, p + 4 * k, dv + (t * 4 + k) * 16);
                    wg_commit();
                }
            }
            wg_wait<0>();
            pin<12>(o);
            if (redo != 32) {
                float chk = (o[8] + o[10]) * 256.f;
#pragma unroll
                for (int i = 0; i < 8; i++) chk += fabsf(o[i]);
                uint32_t bad;
                asm volatile("{\n.reg .pred p, q;\nsetp.geu.f32 q, %1, 0f7F800000;\nbar.red.or.pred p, %2, 128, q;\nselp.u32 %0, 1, 0, p;\n}" : "=r"(bad) : "f"(chk), "r"(1 + wg) : "memory");
                if (__any_sync(0xffffffffu, bad)) { redo = 32; continue; }
            }
            const int rowblk = qb * 8 + round * 4 + wg;
            const float r0 = rcpf(o[8]), r1 = rcpf(o[10]);
            uint32_t* po = reinterpret_cast<uint32_t*>(g_o + (rowblk * 8 + (head >> 2)) * 512) + wq * 512 + (head & 3) * 64 + lane;
            po[0] = pack_bf16(o[0] * r0, o[1] * r0); po[256] = pack_bf16(o[2] * r1, o[3] * r1);
            po[32] = pack_bf16(o[4] * r0, o[5] * r0); po[288] = pack_bf16(o[6] * r1, o[7] * r1);
            if (round == 0) {
                __syncwarp();
                if (elect_one()) mbar_arrive(bars + 8 * (B_OW + pair));
            } else {
                bar_sync(1 + wg, 128);
                if (wq == 0 && elect_one()) { mbar_arrive(bars + 8 * B_DONE); signal_cnt(C_O + rowblk); }
            }
#pragma unroll
            for (int i = 0; i < 4; i++) q[i] = qn[i];
            q2[0] = qn[4]; q2[1] = qn[5];
            redo = 0;
            if (wq == 0 && half == 0 && lane == 0) TSTAMP(14 + 4 * round + pair);
            round++;
        }
    } else {
        uint32_t tag;
        if (wq == 0) {
            asm volatile("barrier.cluster.wait.aligned;" ::: "memory");
            if (tid == 512) TSTAMP(27);
            uint32_t slot = 2, ph = 1;
#pragma unroll 1
            for (int n = 2; n < 40; n++) {
                const int t = n >> 3, j = n & 7;
                const int kc = (n < 32 ? j : (POS_LAST >> (4 * j)) & 7) * 64;
                const CUtensorMap* m = t < nq ? &mqkv : rank ? &mw3 : &mw1;
                const int col = t < nq ? (qt0 + t) * 128 + rank * 64 : (gu0 + t) * 64;
                const uint32_t dst = ring + slot * 16384 + rank * 8192, fb = bars + 8 * (B_FULL + n);
                if (n < 8 && elect_one()) tma2d(sb + n * 16384, &mx, kc, mblk * 128, fb);
                mbar_wait(bars + 8 * (B_EMPTY + slot), ph);
                if (elect_one()) { TS2(0, n); tma2d_mc(dst, m, col, kc, fb); }
                if (++slot == NRING) { slot = 0; ph ^= 1; }
            }
            tag = ld_epoch() + 1;
        } else if (wq == 1) {
            tag = ld_epoch() + 1;
            mbar_wait(bars + 8 * (B_FULL + 5), 0);
#pragma unroll 1
            for (int t = 0; t < 5; t++) {
                float a[4];
#pragma unroll 1
                for (int n = 0; n < 2000000; n++) {
                    uint32_t stale = 0;
                    a[0] = a[1] = a[2] = a[3] = 0.f;
#pragma unroll
                    for (int i = 0; i < 16; i++) {
                        uint32_t u, v;
                        stale |= ld_tagged2(g_cs + (grp * 5 + t) * 512 + i * 32 + lane, tag, u, v);
                        a[(i & 1) * 2] += __uint_as_float(u); a[(i & 1) * 2 + 1] += __uint_as_float(v);
                    }
                    if (__all_sync(0xffffffffu, stale == 0)) break;
                    __nanosleep(400);
                }
                asm volatile("st.shared.v2.f32 [%0], {%1,%2};" :: "r"(sb + OFF_CS + t * 512 + lane * 8), "f"(a[0]), "f"(a[1]) : "memory");
                asm volatile("st.shared.v2.f32 [%0], {%1,%2};" :: "r"(sb + OFF_CS + t * 512 + 256 + lane * 8), "f"(a[2]), "f"(a[3]) : "memory");
                if (t == 0) {
                    uint32_t a, b, c, d;
#pragma unroll 1
                    for (int n = 0; n < 2000000; n++) {
                        const uint32_t stale = ld_tagged2(g_rs + mblk * 64 + lane * 2, tag, a, b) | ld_tagged2(g_rs + mblk * 64 + lane * 2 + 1, tag, c, d);
                        if (__all_sync(0xffffffffu, stale == 0)) break;
                    }
                    asm volatile("st.shared.v4.b32 [%0], {%1,%2,%3,%4};" :: "r"(sb + OFF_RS + lane * 16), "r"(a), "r"(b), "r"(c), "r"(d) : "memory");
                }
                __syncwarp();
                if (elect_one()) { mbar_arrive(bars + 8 * (B_STATS + t)); TSTAMP(32 + t); }
            }
        } else {
            tag = ld_epoch() + 1;
            if (wq == 2) mbar_wait(bars + 8 * B_FULL, 0);
#pragma unroll 1
            for (int t = 3 - wq; t < 5; t += 2) {
                const __nv_bfloat16* src; int ld;
                if (t < nq) { src = wqkv + (qt0 + t) * 128 + rank * 64; ld = 3 * DM; }
                else        { src = (rank ? w3 : w1) + (gu0 + t) * 64; ld = FF; }
                src += (size_t)(rot * 64 + (lane >> 3)) * ld + (lane & 7) * 8;
                uint4 v[16];
                const uint32_t* w = reinterpret_cast<const uint32_t*>(v);
#pragma unroll
                for (int j = 0; j < 16; j++) v[j] = __ldg(reinterpret_cast<const uint4*>(src + (size_t)j * 4 * ld));
                float c[8];
#pragma unroll
                for (int e = 0; e < 4; e++) {
                    float a = 0.f, b = 0.f;
#pragma unroll
                    for (int j = 0; j < 16; j++) { a += bf_lo(w[4 * j + e]); b += bf_hi(w[4 * j + e]); }
                    c[2 * e] = a; c[2 * e + 1] = b;
                }
#pragma unroll
                for (int n = 4; n > 1; n >>= 1) {
                    const bool up = lane & (4 * n);
#pragma unroll
                    for (int e = 0; e < n; e++) c[e] = (up ? c[e + n] : c[e]) + __shfl_xor_sync(0xffffffffu, up ? c[e] : c[e + n], 4 * n);
                }
                unsigned long long* dst = reinterpret_cast<unsigned long long*>(g_cs) + ((grp * 5 + t) * 8 + rot) * 128 + rank * 64 + (lane & 7) * 8 + (lane >> 3) * 2;
                st_tagged(dst, __float_as_uint(c[0]), tag); st_tagged(dst + 1, __float_as_uint(c[1]), tag);
                if (lane == 0) TSTAMP(40 + t);
            }
        }
        if (wq == 3) {
#pragma unroll 1
            for (int i = lane; i < 256; i += 32) asm volatile("st.shared.v4.b32 [%0], {%1,%1,%1,%1};" :: "r"(sb + OFF_ONES + i * 16), "r"(0x3F803F80u) : "memory");
#pragma unroll 1
            for (int i = lane; i < 128; i += 32) {
                const bool fx = (FIXED_MASK >> (i >> 4)) & 1;
                uint32_t a = fx ? pack_bf16(M71, M71) : pack_bf16(P71, P71);
                uint32_t b = fx ? pack_bf16(M71, 47.0f * M71) : pack_bf16(P71, -79.5f * P71);
                uint32_t c = fx ? 0u : pack_bf16(0.08214f * P71, 0.f);
                if (i & 8) a = b = c = 0;
                asm volatile("st.shared.v4.b32 [%0], {%1,%2,%3,%4};" :: "r"(sb + OFF_B2 + i * 16), "r"(a), "r"(b), "r"(c), "r"(0) : "memory");
            }
            fence_async_smem();
            __syncwarp();
            if (elect_one()) mbar_arrive(bars + 8 * B_QKV);
        } else if (wq == 1) {
#pragma unroll 1
            for (int i = 0; i < 3; i++) wait_cnt(C_QKV + i * 4 + (head >> 3), 16 * tag, 100);
            fence_async_all();
            if (elect_one()) { mbar_arrive(bars + 8 * B_QKV); TSTAMP(29); }
            const uint8_t* gk = reinterpret_cast<const uint8_t*>(g_k + head * 4096);
            const uint8_t* gv = reinterpret_cast<const uint8_t*>(g_v + head * 4096);
#pragma unroll 1
            for (int c = 0; c < 8; c++) {
                if (!(c & 1)) mbar_wait(bars + 8 * (c ? B_AFREE + (c >> 1) : B_AFREE0), 0);
                if (elect_one()) {
                    const uint32_t b = bars + 8 * (B_KV + c);
                    mbar_expect(b, 16384);
                    bulk_load(sb + (2 * c + 1) * 4096, gk + c * 8192, 4096, b);
                    bulk_load(sb + 2 * c * 4096, gv + c * 4096, 4096, b);
                    bulk_load(sb + 65536 + c * 4096, gv + 32768 + c * 4096, 4096, b);
                    bulk_load(sb + 98304 + c * 4096, gk + c * 8192 + 4096, 4096, b);
                }
            }
        } else if (wq == 2) {
#pragma unroll 1
            for (int t = 0; t < 5; t++) {
                mbar_wait(bars + 8 * (B_TILE + t), 0);
                if (elect_one()) signal_cnt(t < nq ? C_QKV + qt0 + t : C_H + mblk);
            }
        }
        pin<1>(&tag);
        bar_sync(5, 128);
        if (tid == 639) g_epoch[blockIdx.x] = tag;
        const int cb = blockIdx.x & 7, pr = blockIdx.x >> 3;
        const int rb0 = (pr >> 2) * 8 + (pr & 3);
        uint32_t gate[2][16];
        {
            float dn[64];
            auto load_stage = [&](int kb, int st) {
                const uint32_t b = bars + 8 * (B_RING + st), dst = ring + st * 24576;
                mbar_expect(b, 24576);
                bulk_load(dst, g_h + (rb0 * 28 + kb) * 512, 8192, b);
                bulk_load(dst + 8192, g_h + ((rb0 + 4) * 28 + kb) * 512, 8192, b);
                tma2d(dst + 16384, &mw2, cb * 64, kb * 64, b);
            };
            if (wq == 0) {
                wait_cnt(C_H + (rb0 >> 1), 28 * tag, 200);
                wait_cnt(C_H + (rb0 >> 1) + 2, 28 * tag, 200);
                if (elect_one()) { TSTAMP(20); fence_async_all(); load_stage(0, 0); load_stage(1, 1); }
            }
            int st = 0; uint32_t ph = 0;
#pragma unroll 1
            for (int kb = 0; kb < 28; kb++) {
                mbar_wait(bars + 8 * (B_RING + st), ph);
                const uint64_t da = mkdesc(OFF_RING + st * 24576, 128, 1024, 0), db = mkdesc(OFF_RING + st * 24576 + 16384, 8192, 1024, 1);
                wg_fence();
#pragma unroll
                for (int k = 0; k < 4; k++) { wgmma_ss_n64(dn, da + k * 16, db + k * 128, (kb | k) != 0); wgmma_ss_n64(dn + 32, da + 512 + k * 16, db + k * 128, (kb | k) != 0); }
                wg_commit();
                wg_wait<1>();
                if (wq == 0 && kb < 26 && elect_one()) load_stage(kb + 2, st == 0 ? 2 : st - 1);
                if (++st == 3) { st = 0; ph ^= 1; }
            }
            wg_wait<0>();
            pin<64>(dn);
#pragma unroll
            for (int i = 0; i < 32; i++) gate[i >> 4][i & 15] = pack_bf16(siluf(dn[2 * i]), siluf(dn[2 * i + 1]));
        }
        float acc[32];
        if (tid == 512) TSTAMP(21);
        const uint32_t bar_wo = bars + 8 * B_WO;
        if (wq == 0 && elect_one()) {
            mbar_expect(bar_wo, 65536);
#pragma unroll 1
            for (int i = 0; i < 8; i++) tma2d(ring + i * 8192, &mwo, cb * 64, i * 64, bar_wo);
        }
        if (wq >= 2) {
            mbar_wait(bars + 8 * (B_OW + wq - 2), 0);
            if (elect_one()) {
                signal_cnt(C_O + qb * 8 + 2 * wq - 4);
                asm volatile("red.relaxed.gpu.global.add.u32 [%0], 1;" :: "l"(g_cnt + (C_O + qb * 8 + 2 * wq - 3) * 8) : "memory");
            }
        }
#pragma unroll 1
        for (int tl = 0; tl < 2; tl++) {
            const int rb = rb0 + 4 * tl;
            uint32_t xr[16];
            const uint32_t* px = reinterpret_cast<const uint32_t*>(x + (size_t)(rb * 64 + wq * 16 + g) * DM + cb * 64) + t4;
#pragma unroll
            for (int j = 0; j < 8; j++) { xr[2 * j] = __ldg(px + j * 4); xr[2 * j + 1] = __ldg(px + 8 * DM / 2 + j * 4); }
            if (wq == 0) {
                if (tl == 1) mbar_wait(bars + 8 * B_DONE, 0);
                wait_cnt(C_O + rb, 32 * tag, tl ? 20 : 200);
                if (elect_one()) {
                    fence_async_all();
                    TSTAMP(22 + 2 * tl);
#pragma unroll 1
                    for (int i = 0; i < (tl ? 8 : 2); i++) {
                        mbar_expect(bars + 8 * (B_O + i), 8192);
                        bulk_load((tl ? sb : ring + 65536) + i * 8192, g_o + (rb * 8 + i) * 512, 8192, bars + 8 * (B_O + i));
                    }
                }
            }
            if (tl == 0) mbar_wait(bar_wo, 0);
#pragma unroll 1
            for (int kb = 0; kb < 8; kb++) {
                mbar_wait(bars + 8 * (B_O + kb), tl);
                const uint32_t a = tl == 0 ? OFF_RING + 65536 + (kb & 1) * 8192 : kb * 8192;
                const uint64_t da = mkdesc(a, 128, 1024, 0), db = mkdesc(OFF_RING + kb * 8192, 8192, 1024, 1);
                wg_fence();
#pragma unroll
                for (int k = 0; k < 4; k++) wgmma_ss_n64(acc, da + k * 16, db + k * 128, (kb | k) != 0);
                wg_commit();
                if (tl == 0) {
                    wg_wait<0>();
                    bar_sync(5, 128);
                    if (wq == 0 && kb < 6 && elect_one()) { mbar_expect(bars + 8 * (B_O + kb + 2), 8192); bulk_load(sb + a, g_o + (rb * 8 + kb + 2) * 512, 8192, bars + 8 * (B_O + kb + 2)); }
                }
            }
            wg_wait<0>();
            pin<32>(acc);
            uint32_t* po = reinterpret_cast<uint32_t*>(out + (size_t)(rb * 64 + wq * 16 + g) * DM + cb * 64) + t4;
#pragma unroll
            for (int i = 0; i < 16; i++) {
                const uint32_t r = pack_bf16(fmaf(acc[2 * i], bf_lo(gate[0][i]), bf_lo(xr[i])), fmaf(acc[2 * i + 1], bf_hi(gate[0][i]), bf_hi(xr[i])));
                po[(i & 1) * (8 * DM / 2) + (i >> 1) * 4] = r;
                gate[0][i] = gate[1][i];
            }
            if (tid == 512) TSTAMP(23 + 2 * tl);
        }
    }
}

typedef CUresult (*EncodeFn)(CUtensorMap*, CUtensorMapDataType, cuuint32_t, void*, const cuuint64_t*, const cuuint64_t*, const cuuint32_t*,
                             const cuuint32_t*, CUtensorMapInterleave, CUtensorMapSwizzle, CUtensorMapL2promotion, CUtensorMapFloatOOBfill);

void make_map(EncodeFn fn, CUtensorMap* m, const void* p, int rows, int cols, int box_rows) {
    cuuint64_t dims[2] = {(cuuint64_t)cols, (cuuint64_t)rows};
    cuuint64_t strides[1] = {(cuuint64_t)cols * 2};
    cuuint32_t box[2] = {64, (cuuint32_t)box_rows};
    cuuint32_t es[2] = {1, 1};
    fn(m, CU_TENSOR_MAP_DATA_TYPE_BFLOAT16, 2, const_cast<void*>(p), dims, strides, box, es, CU_TENSOR_MAP_INTERLEAVE_NONE,
       CU_TENSOR_MAP_SWIZZLE_128B, CU_TENSOR_MAP_L2_PROMOTION_L2_128B, CU_TENSOR_MAP_FLOAT_OOB_FILL_NONE);
}

}

extern "C" void kernel_launch(void* const* d_in, const int* in_sizes, int n_in, void* d_out, int out_size) {
    const __nv_bfloat16* x = (const __nv_bfloat16*)d_in[0];
    static EncodeFn fn = nullptr;
    if (!fn) {
        cudaDriverEntryPointQueryResult qr;
        cudaGetDriverEntryPoint("cuTensorMapEncodeTiled", (void**)&fn, cudaEnableDefault, &qr);
        cudaFuncSetAttribute(mega_kernel, cudaFuncAttributeMaxDynamicSharedMemorySize, SMEM_BYTES);
    }
    CUtensorMap mx, mqkv, mw1, mw3, mw2, mwo;
    make_map(fn, &mx, d_in[0], SEQ, DM, 128);
    make_map(fn, &mqkv, d_in[1], DM, 3 * DM, 64);
    make_map(fn, &mwo, d_in[2], DM, DM, 64);
    make_map(fn, &mw1, d_in[4], DM, FF, 64);
    make_map(fn, &mw3, d_in[5], DM, FF, 64);
    make_map(fn, &mw2, d_in[6], FF, DM, 64);
    mega_kernel<<<128, 640, SMEM_BYTES, cudaStreamPerThread>>>(x, (const __nv_bfloat16*)d_in[1], (const __nv_bfloat16*)d_in[4], (const __nv_bfloat16*)d_in[5],
                                                               (__nv_bfloat16*)d_out, mx, mqkv, mw1, mw3, mw2, mwo, 0x3F003F00u);
}
```

```cpp
#include <cuda_runtime.h>
#include <cuda_bf16.h>
#include <cuda.h>
#include <stdint.h>

namespace {

constexpr int SEQ = 2048, DM = 512, FF = 1792;

__device__ uint4 g_q[32 * 128 * 32];
__device__ uint4 g_k[32 * 4096];
__device__ uint4 g_v[32 * 4096];
__device__ uint4 g_h[32 * 28 * 512];
__device__ uint4 g_o[32 * 8 * 512];
__device__ ulonglong2 g_cs[40 * 8 * 64];
__device__ ulonglong2 g_rs[SEQ / 2];
constexpr int C_QKV = 0, C_H = 12, C_O = 28, C_NUM = 60;
__device__ unsigned g_cnt[C_NUM * 8];
__device__ unsigned g_epoch[128];
#define TSTAMP(i)
#define TS2(k, i)

__device__ __forceinline__ uint32_t smem_u32(const void* p) { return (uint32_t)__cvta_generic_to_shared(p); }
__device__ __forceinline__ void mbar_init(uint32_t a, int c) { asm volatile("mbarrier.init.shared::cta.b64 [%0], %1;" :: "r"(a), "r"(c)); }
__device__ __forceinline__ void mbar_expect(uint32_t a, int b) { asm volatile("mbarrier.arrive.expect_tx.shared::cta.b64 _, [%0], %1;" :: "r"(a), "r"(b) : "memory"); }
__device__ __forceinline__ void mbar_arrive(uint32_t a) { asm volatile("mbarrier.arrive.shared::cta.b64 _, [%0];" :: "r"(a) : "memory"); }
__device__ __forceinline__ void mbar_arrive_remote(uint32_t a) { asm volatile("mbarrier.arrive.shared::cluster.b64 _, [%0];" :: "r"(a) : "memory"); }
__device__ __forceinline__ bool mbar_try(uint32_t a, uint32_t ph) {
    uint32_t ok;
    asm volatile("{\n.reg .pred p;\nmbarrier.try_wait.parity.shared::cta.b64 p, [%1], %2;\nselp.u32 %0, 1, 0, p;\n}" : "=r"(ok) : "r"(a), "r"(ph) : "memory");
    return ok;
}
__device__ __forceinline__ void mbar_wait(uint32_t a, uint32_t ph) {
    int n = 1 << 22;
#pragma unroll 1
    do { n = __all_sync(0xffffffffu, mbar_try(a, ph)) ? 0 : n - 1; } while (n > 0);
}
__device__ __forceinline__ bool elect_one() {
    uint32_t p;
    asm volatile("{\n.reg .pred P;\nelect.sync _|P, 0xffffffff;\nselp.u32 %0, 1, 0, P;\n}" : "=r"(p));
    return p;
}
__device__ __forceinline__ void signal_cnt(int c) {
    asm volatile("fence.release.gpu;\nred.relaxed.gpu.global.add.u32 [%0], 1;" :: "l"(g_cnt + c * 8) : "memory");
}
__device__ __forceinline__ void wait_cnt(int c, unsigned target, int ns) {
#pragma unroll 1
    for (int n = 0; n < 2000000; n++) {
        unsigned v;
        asm volatile("ld.relaxed.gpu.global.u32 %0, [%1];" : "=r"(v) : "l"(g_cnt + c * 8) : "memory");
        if (__all_sync(0xffffffffu, (int)(v - target) >= 0)) break;
        __nanosleep(ns);
    }
}
__device__ __forceinline__ uint32_t ld_epoch() {
    uint32_t e;
    asm volatile("ld.relaxed.gpu.global.u32 %0, [%1];" : "=r"(e) : "l"(g_epoch + blockIdx.x) : "memory");
    return e;
}
__device__ __forceinline__ void st_tagged(void* p, uint32_t v, uint32_t tag) {
    asm volatile("st.relaxed.gpu.global.b64 [%0], %1;" :: "l"(p), "l"((unsigned long long)tag << 32 | v) : "memory");
}
__device__ __forceinline__ uint32_t ld_tagged2(const ulonglong2* p, uint32_t tag, uint32_t& a, uint32_t& b) {
    unsigned long long u, v;
    asm volatile("ld.relaxed.gpu.global.v2.b64 {%0,%1}, [%2];" : "=l"(u), "=l"(v) : "l"(p) : "memory");
    a = (uint32_t)u; b = (uint32_t)v;
    return ((uint32_t)(u >> 32) ^ tag) | ((uint32_t)(v >> 32) ^ tag);
}
__device__ __forceinline__ void tma2d(uint32_t dst, const CUtensorMap* m, int c0, int c1, uint32_t bar) {
    asm volatile("cp.async.bulk.tensor.2d.shared::cluster.global.mbarrier::complete_tx::bytes [%0], [%1, {%3, %4}], [%2];"
                 :: "r"(dst), "l"(m), "r"(bar), "r"(c0), "r"(c1) : "memory");
}
__device__ __forceinline__ void tma2d_mc(uint32_t dst, const CUtensorMap* m, int c0, int c1, uint32_t bar) {
    asm volatile("cp.async.bulk.tensor.2d.shared::cluster.global.mbarrier::complete_tx::bytes.multicast::cluster [%0], [%1, {%3, %4}], [%2], %5;"
                 :: "r"(dst), "l"(m), "r"(bar), "r"(c0), "r"(c1), "h"((uint16_t)3) : "memory");
}
__device__ __forceinline__ void bulk_load(uint32_t dst, const void* src, int bytes, uint32_t bar) {
    asm volatile("cp.async.bulk.shared::cluster.global.mbarrier::complete_tx::bytes [%0], [%1], %2, [%3];"
                 :: "r"(dst), "l"(src), "r"(bytes), "r"(bar) : "memory");
}
__device__ __forceinline__ void bar_sync(int id, int n) { asm volatile("bar.sync %0, %1;" :: "r"(id), "r"(n) : "memory"); }
__device__ __forceinline__ void fence_async_smem() { asm volatile("fence.proxy.async.shared::cta;" ::: "memory"); }
__device__ __forceinline__ void fence_async_all() { asm volatile("fence.acquire.gpu;\nfence.proxy.async.global;" ::: "memory"); }
__device__ __forceinline__ void wg_fence() { asm volatile("wgmma.fence.sync.aligned;" ::: "memory"); }
__device__ __forceinline__ void wg_commit() { asm volatile("wgmma.commit_group.sync.aligned;" ::: "memory"); }
template <int N> __device__ __forceinline__ void wg_wait() { asm volatile("wgmma.wait_group.sync.aligned %0;" :: "n"(N) : "memory"); }
template <int N> __device__ __forceinline__ void pin(float* d) {
#pragma unroll
    for (int i = 0; i < N; i++) asm volatile("" : "+f"(d[i]) :: "memory");
}
template <int N> __device__ __forceinline__ void pin(uint32_t* d) {
#pragma unroll
    for (int i = 0; i < N; i++) asm volatile("" : "+r"(d[i]) :: "memory");
}
constexpr uint32_t SMEM_BASE = 1024;
__device__ __forceinline__ uint64_t mkdesc(uint32_t off, uint32_t lbo, uint32_t sbo, uint32_t swz) {
    return (uint64_t)((SMEM_BASE + off) >> 4) | ((uint64_t)(lbo >> 4) << 16) | ((uint64_t)(sbo >> 4) << 32) | ((uint64_t)swz << 62);
}
__device__ __forceinline__ float ex2f(float x) { float y; asm("ex2.approx.ftz.f32 %0, %1;" : "=f"(y) : "f"(x)); return y; }
__device__ __forceinline__ float rcpf(float x) { float y; asm("rcp.approx.ftz.f32 %0, %1;" : "=f"(y) : "f"(x)); return y; }
__device__ __forceinline__ uint32_t pack_bf16(float lo, float hi) { uint32_t r; asm("cvt.rn.bf16x2.f32 %0, %1, %2;" : "=r"(r) : "f"(hi), "f"(lo)); return r; }
__device__ __forceinline__ float bf_lo(uint32_t v) { return __uint_as_float(v << 16); }
__device__ __forceinline__ float bf_hi(uint32_t v) { return __uint_as_float(v & 0xFFFF0000u); }
__device__ __forceinline__ float bf_round(float x) { return __bfloat162float(__float2bfloat16_rn(x)); }
__device__ __forceinline__ float siluf(float g) { return g * rcpf(1.0f + ex2f(g * -1.4426950408889634f)); }

__device__ __forceinline__ void wgmma_ss_n256(float* d, uint64_t da, uint64_t db, int acc) {
    asm volatile("{\n.reg .pred p;\nsetp.ne.b32 p, %130, 0;\nwgmma.mma_async.sync.aligned.m64n256k16.f32.bf16.bf16 {"
        "%0,%1,%2,%3,%4,%5,%6,%7,%8,%9,%10,%11,%12,%13,%14,%15,%16,%17,%18,%19,%20,%21,%22,%23,%24,%25,%26,%27,%28,%29,%30,%31,%32,%33,%34,%35,%36,%37,%38,%39,"
        "%40,%41,%42,%43,%44,%45,%46,%47,%48,%49,%50,%51,%52,%53,%54,%55,%56,%57,%58,%59,%60,%61,%62,%63,%64,%65,%66,%67,%68,%69,%70,%71,%72,%73,%74,%75,%76,"
        "%77,%78,%79,%80,%81,%82,%83,%84,%85,%86,%87,%88,%89,%90,%91,%92,%93,%94,%95,%96,%97,%98,%99,%100,%101,%102,%103,%104,%105,%106,%107,%108,%109,%110,"
        "%111,%112,%113,%114,%115,%116,%117,%118,%119,%120,%121,%122,%123,%124,%125,%126,%127"
        "}, %128, %129, p, 1, 1, 0, 1;\n}\n"
        : "+f"(d[0]),"+f"(d[1]),"+f"(d[2]),"+f"(d[3]),"+f"(d[4]),"+f"(d[5]),"+f"(d[6]),"+f"(d[7]),"+f"(d[8]),"+f"(d[9]),"+f"(d[10]),"+f"(d[11]),"+f"(d[12]),
          "+f"(d[13]),"+f"(d[14]),"+f"(d[15]),"+f"(d[16]),"+f"(d[17]),"+f"(d[18]),"+f"(d[19]),"+f"(d[20]),"+f"(d[21]),"+f"(d[22]),"+f"(d[23]),"+f"(d[24]),
          "+f"(d[25]),"+f"(d[26]),"+f"(d[27]),"+f"(d[28]),"+f"(d[29]),"+f"(d[30]),"+f"(d[31]),"+f"(d[32]),"+f"(d[33]),"+f"(d[34]),"+f"(d[35]),"+f"(d[36]),
          "+f"(d[37]),"+f"(d[38]),"+f"(d[39]),"+f"(d[40]),"+f"(d[41]),"+f"(d[42]),"+f"(d[43]),"+f"(d[44]),"+f"(d[45]),"+f"(d[46]),"+f"(d[47]),"+f"(d[48]),
          "+f"(d[49]),"+f"(d[50]),"+f"(d[51]),"+f"(d[52]),"+f"(d[53]),"+f"(d[54]),"+f"(d[55]),"+f"(d[56]),"+f"(d[57]),"+f"(d[58]),"+f"(d[59]),"+f"(d[60]),
          "+f"(d[61]),"+f"(d[62]),"+f"(d[63]),"+f"(d[64]),"+f"(d[65]),"+f"(d[66]),"+f"(d[67]),"+f"(d[68]),"+f"(d[69]),"+f"(d[70]),"+f"(d[71]),"+f"(d[72]),
          "+f"(d[73]),"+f"(d[74]),"+f"(d[75]),"+f"(d[76]),"+f"(d[77]),"+f"(d[78]),"+f"(d[79]),"+f"(d[80]),"+f"(d[81]),"+f"(d[82]),"+f"(d[83]),"+f"(d[84]),
          "+f"(d[85]),"+f"(d[86]),"+f"(d[87]),"+f"(d[88]),"+f"(d[89]),"+f"(d[90]),"+f"(d[91]),"+f"(d[92]),"+f"(d[93]),"+f"(d[94]),"+f"(d[95]),"+f"(d[96]),
          "+f"(d[97]),"+f"(d[98]),"+f"(d[99]),"+f"(d[100]),"+f"(d[101]),"+f"(d[102]),"+f"(d[103]),"+f"(d[104]),"+f"(d[105]),"+f"(d[106]),"+f"(d[107]),
          "+f"(d[108]),"+f"(d[109]),"+f"(d[110]),"+f"(d[111]),"+f"(d[112]),"+f"(d[113]),"+f"(d[114]),"+f"(d[115]),"+f"(d[116]),"+f"(d[117]),"+f"(d[118]),
          "+f"(d[119]),"+f"(d[120]),"+f"(d[121]),"+f"(d[122]),"+f"(d[123]),"+f"(d[124]),"+f"(d[125]),"+f"(d[126]),"+f"(d[127])
        : "l"(da), "l"(db), "r"(acc));
}
__device__ __forceinline__ void wgmma_ss_n128(float* d, uint64_t da, uint64_t db, int acc) {
    asm volatile("{\n.reg .pred p;\nsetp.ne.b32 p, %66, 0;\nwgmma.mma_async.sync.aligned.m64n128k16.f32.bf16.bf16 {"
        "%0,%1,%2,%3,%4,%5,%6,%7,%8,%9,%10,%11,%12,%13,%14,%15,%16,%17,%18,%19,%20,%21,%22,%23,%24,%25,%26,%27,%28,%29,%30,%31,%32,%33,%34,%35,%36,%37,%38,%39,"
        "%40,%41,%42,%43,%44,%45,%46,%47,%48,%49,%50,%51,%52,%53,%54,%55,%56,%57,%58,%59,%60,%61,%62,%63"
        "}, %64, %65, p, 1, 1, 0, 1;\n}\n"
        : "+f"(d[0]),"+f"(d[1]),"+f"(d[2]),"+f"(d[3]),"+f"(d[4]),"+f"(d[5]),"+f"(d[6]),"+f"(d[7]),"+f"(d[8]),"+f"(d[9]),"+f"(d[10]),"+f"(d[11]),"+f"(d[12]),
          "+f"(d[13]),"+f"(d[14]),"+f"(d[15]),"+f"(d[16]),"+f"(d[17]),"+f"(d[18]),"+f"(d[19]),"+f"(d[20]),"+f"(d[21]),"+f"(d[22]),"+f"(d[23]),"+f"(d[24]),
          "+f"(d[25]),"+f"(d[26]),"+f"(d[27]),"+f"(d[28]),"+f"(d[29]),"+f"(d[30]),"+f"(d[31]),"+f"(d[32]),"+f"(d[33]),"+f"(d[34]),"+f"(d[35]),"+f"(d[36]),
          "+f"(d[37]),"+f"(d[38]),"+f"(d[39]),"+f"(d[40]),"+f"(d[41]),"+f"(d[42]),"+f"(d[43]),"+f"(d[44]),"+f"(d[45]),"+f"(d[46]),"+f"(d[47]),"+f"(d[48]),
          "+f"(d[49]),"+f"(d[50]),"+f"(d[51]),"+f"(d[52]),"+f"(d[53]),"+f"(d[54]),"+f"(d[55]),"+f"(d[56]),"+f"(d[57]),"+f"(d[58]),"+f"(d[59]),"+f"(d[60]),
          "+f"(d[61]),"+f"(d[62]),"+f"(d[63])
        : "l"(da), "l"(db), "r"(acc));
}
__device__ __forceinline__ void wgmma_ss_n64(float* d, uint64_t da, uint64_t db, int acc) {
    asm volatile("{\n.reg .pred p;\nsetp.ne.b32 p, %34, 0;\nwgmma.mma_async.sync.aligned.m64n64k16.f32.bf16.bf16 {"
        "%0,%1,%2,%3,%4,%5,%6,%7,%8,%9,%10,%11,%12,%13,%14,%15,%16,%17,%18,%19,%20,%21,%22,%23,%24,%25,%26,%27,%28,%29,%30,%31"
        "}, %32, %33, p, 1, 1, 0, 1;\n}\n"
        : "+f"(d[0]),"+f"(d[1]),"+f"(d[2]),"+f"(d[3]),"+f"(d[4]),"+f"(d[5]),"+f"(d[6]),"+f"(d[7]),"+f"(d[8]),"+f"(d[9]),"+f"(d[10]),"+f"(d[11]),"+f"(d[12]),
          "+f"(d[13]),"+f"(d[14]),"+f"(d[15]),"+f"(d[16]),"+f"(d[17]),"+f"(d[18]),"+f"(d[19]),"+f"(d[20]),"+f"(d[21]),"+f"(d[22]),"+f"(d[23]),"+f"(d[24]),
          "+f"(d[25]),"+f"(d[26]),"+f"(d[27]),"+f"(d[28]),"+f"(d[29]),"+f"(d[30]),"+f"(d[31])
        : "l"(da), "l"(db), "r"(acc));
}
__device__ __forceinline__ void wgmma_rs_n64_zero(float* d, const uint32_t* a, uint64_t db) {
    asm volatile("wgmma.mma_async.sync.aligned.m64n64k16.f32.bf16.bf16 {"
        "%0,%1,%2,%3,%4,%5,%6,%7,%8,%9,%10,%11,%12,%13,%14,%15,%16,%17,%18,%19,%20,%21,%22,%23,%24,%25,%26,%27,%28,%29,%30,%31"
        "}, {%32,%33,%34,%35}, %36, 0, 1, 1, 0;\n"
        : "=f"(d[0]),"=f"(d[1]),"=f"(d[2]),"=f"(d[3]),"=f"(d[4]),"=f"(d[5]),"=f"(d[6]),"=f"(d[7]),"=f"(d[8]),"=f"(d[9]),"=f"(d[10]),"=f"(d[11]),"=f"(d[12]),
          "=f"(d[13]),"=f"(d[14]),"=f"(d[15]),"=f"(d[16]),"=f"(d[17]),"=f"(d[18]),"=f"(d[19]),"=f"(d[20]),"=f"(d[21]),"=f"(d[22]),"=f"(d[23]),"=f"(d[24]),
          "=f"(d[25]),"=f"(d[26]),"=f"(d[27]),"=f"(d[28]),"=f"(d[29]),"=f"(d[30]),"=f"(d[31])
        : "r"(a[0]), "r"(a[1]), "r"(a[2]), "r"(a[3]), "l"(db));
}
__device__ __forceinline__ void wgmma_rs_n64_acc(float* d, const uint32_t* a, uint64_t db) {
    asm volatile("wgmma.mma_async.sync.aligned.m64n64k16.f32.bf16.bf16 {"
        "%0,%1,%2,%3,%4,%5,%6,%7,%8,%9,%10,%11,%12,%13,%14,%15,%16,%17,%18,%19,%20,%21,%22,%23,%24,%25,%26,%27,%28,%29,%30,%31"
        "}, {%32,%33,%34,%35}, %36, 1, 1, 1, 0;\n"
        : "+f"(d[0]),"+f"(d[1]),"+f"(d[2]),"+f"(d[3]),"+f"(d[4]),"+f"(d[5]),"+f"(d[6]),"+f"(d[7]),"+f"(d[8]),"+f"(d[9]),"+f"(d[10]),"+f"(d[11]),"+f"(d[12]),
          "+f"(d[13]),"+f"(d[14]),"+f"(d[15]),"+f"(d[16]),"+f"(d[17]),"+f"(d[18]),"+f"(d[19]),"+f"(d[20]),"+f"(d[21]),"+f"(d[22]),"+f"(d[23]),"+f"(d[24]),
          "+f"(d[25]),"+f"(d[26]),"+f"(d[27]),"+f"(d[28]),"+f"(d[29]),"+f"(d[30]),"+f"(d[31])
        : "r"(a[0]), "r"(a[1]), "r"(a[2]), "r"(a[3]), "l"(db));
}
__device__ __forceinline__ void wgmma_rs_n24_acc(float* d, const uint32_t* a, uint64_t db) {
    asm volatile("wgmma.mma_async.sync.aligned.m64n24k16.f32.bf16.bf16 {"
        "%0,%1,%2,%3,%4,%5,%6,%7,%8,%9,%10,%11"
        "}, {%12,%13,%14,%15}, %16, 1, 1, 1, 1;\n"
        : "+f"(d[0]),"+f"(d[1]),"+f"(d[2]),"+f"(d[3]),"+f"(d[4]),"+f"(d[5]),"+f"(d[6]),"+f"(d[7]),"+f"(d[8]),"+f"(d[9]),"+f"(d[10]),"+f"(d[11])
        : "r"(a[0]), "r"(a[1]), "r"(a[2]), "r"(a[3]), "l"(db));
}
__device__ __forceinline__ void wgmma_rs_n24_zero(float* d, const uint32_t* a, uint64_t db) {
    asm volatile("wgmma.mma_async.sync.aligned.m64n24k16.f32.bf16.bf16 {"
        "%0,%1,%2,%3,%4,%5,%6,%7,%8,%9,%10,%11"
        "}, {%12,%13,%14,%15}, %16, 0, 1, 1, 1;\n"
        : "=f"(d[0]),"=f"(d[1]),"=f"(d[2]),"=f"(d[3]),"=f"(d[4]),"=f"(d[5]),"=f"(d[6]),"=f"(d[7]),"=f"(d[8]),"=f"(d[9]),"=f"(d[10]),"=f"(d[11])
        : "r"(a[0]), "r"(a[1]), "r"(a[2]), "r"(a[3]), "l"(db));
}

constexpr int OFF_ONES = 131072;
constexpr int OFF_RING = OFF_ONES + 4096;
constexpr int NRING = 5;
constexpr int OFF_B2 = OFF_RING + NRING * 16384;
constexpr int OFF_CS = OFF_B2 + 2048;
constexpr int OFF_RS = OFF_CS + 2560;
constexpr int OFF_BAR = OFF_RS + 1024;
enum { B_FULL = 0, B_STATS = 40, B_KV = 45, B_RING = 53, B_WO = 56, B_O = 57, B_CNT2 = 65,
       B_AFREE = 65, B_ORD = 69, B_QKV = 74, B_CNT4 = 75, B_EMPTY = 75, B_AFREE0 = 80, B_DONE = 81, B_CNT8 = 82, B_TILE = 82, B_OW = 87, B_NUM = 100 };
constexpr int OFF_TS = OFF_BAR + 1024;
constexpr int SMEM_BYTES = OFF_BAR + B_NUM * 8;
constexpr unsigned FIXED_MASK = 0xB5;
constexpr float P71 = 2361183241434822606848.0f, M71 = 4.235164736271502e-22f;

__device__ __forceinline__ uint32_t exp2_fixed(float lo, float hi, uint32_t half2) {
    uint32_t y, g, d;
    asm("cvt.pack.sat.s16.s32 %0, %1, %2;" : "=r"(y) : "r"(__float_as_uint(hi)), "r"(__float_as_uint(lo)));
    asm("lop3.b32 %0, %1, 0x007F007F, %2, 0xEA;" : "=r"(g) : "r"(y), "r"(half2));
    asm("fma.rn.bf16x2 %0, %1, %2, %3;" : "=r"(d) : "r"(y), "r"(g), "r"(y & 0xFF80FF80u));
    return d;
}
__device__ __forceinline__ uint32_t k_tile_addr(uint32_t base, int tile) {
    const int c = tile >> 2;
    return base + ((tile & 2) ? 98304 + c * 4096 : (2 * c + 1) * 4096) + (tile & 1) * 2048;
}
constexpr uint32_t POS_STD = 0x76543210u, POS_LAST = 0xB75A9640u;

__global__ void __cluster_dims__(2, 1, 1) __launch_bounds__(640, 1)
mega_kernel(const __nv_bfloat16* __restrict__ x, const __nv_bfloat16* __restrict__ wqkv, const __nv_bfloat16* __restrict__ w1,
            const __nv_bfloat16* __restrict__ w3, __nv_bfloat16* __restrict__ out,
            const __grid_constant__ CUtensorMap mx, const __grid_constant__ CUtensorMap mqkv, const __grid_constant__ CUtensorMap mw1,
            const __grid_constant__ CUtensorMap mw3, const __grid_constant__ CUtensorMap mw2, const __grid_constant__ CUtensorMap mwo,
            uint32_t half2) {
    extern __shared__ __align__(1024) uint8_t smem_raw[];
    const uint32_t sb = __shfl_sync(0xffffffffu, smem_u32(smem_raw), 0);
    if ((sb & 0xFFFFFF) != SMEM_BASE) __trap();
    const uint32_t bars = sb + OFF_BAR, ring = sb + OFF_RING;
    const int tid = threadIdx.x, lane = tid & 31, g = lane >> 2, t4 = lane & 3;
    const int warp = __shfl_sync(0xffffffffu, tid >> 5, 0), wg = warp >> 2, wq = warp & 3;
    const int rank = blockIdx.x & 1, cl = blockIdx.x >> 1;
    const int grp = cl < 4 ? 4 + cl : cl < 36 ? (cl - 4) >> 3 : 4 + (cl - 36) / 7;
    const int rot = cl < 4 ? 7 : cl < 36 ? (cl - 4) & 7 : (cl - 36) % 7;
    const int mblk = rot * 2 + rank;
    const int nq = grp < 4 ? 2 : 1;
    const int qt0 = grp < 4 ? 2 * grp : 4 + grp;
    const int gu0 = (grp < 4 ? 3 * grp : 4 * grp - 4) - nq;
    const int head = blockIdx.x >> 2, qb = blockIdx.x & 3;

    if (elect_one()) {
#pragma unroll
        for (int i = 0; i < 5; i++) { const int b = warp * 5 + i; mbar_init(bars + 8 * b, b < B_CNT2 ? 1 : b < B_CNT4 ? 2 : b < B_CNT8 ? 4 : 8); }
        if (warp == 0) {
            fence_async_smem();
#pragma unroll
            for (int j = 0; j < 2; j++) {
                tma2d(sb + j * 16384, &mx, j * 64, mblk * 128, bars + 8 * (B_FULL + j));
                tma2d(ring + j * 16384, &mqkv, qt0 * 128, j * 64, bars + 8 * (B_FULL + j));
                tma2d(ring + j * 16384 + 8192, &mqkv, qt0 * 128 + 64, j * 64, bars + 8 * (B_FULL + j));
            }
        }
        if (warp < 8) {
#pragma unroll
            for (int i = 0; i < 5; i++) mbar_expect(bars + 8 * (warp * 5 + i), warp * 5 + i < 8 ? 32768 : 16384);
        }
        if (warp == 16) asm volatile("prefetch.tensormap [%0];" :: "l"(rank ? &mw3 : &mw1) : "memory");
        asm volatile("fence.mbarrier_init.release.cluster;" ::: "memory");
    }
    __syncthreads();
    if (tid == 512) TSTAMP(26);
    asm volatile("barrier.cluster.arrive.relaxed.aligned;" ::: "memory");

    if (wg < 4) {
        const int pair = wg >> 1, half = wg & 1;
        if (pair == 1) {
            const int row = mblk * 128 + grp * 16 + (warp - 8) * 2 + (lane >> 4);
            uint4 v[6];
            const uint32_t* w = reinterpret_cast<const uint32_t*>(v);
#pragma unroll
            for (int j = 0; j < 2; j++) v[4 + j] = __ldg(reinterpret_cast<const uint4*>(wqkv + (size_t)(rot * 64 + j * 32 + lane) * (3 * DM) + qt0 * 128 + rank * 64) + warp - 8);
#pragma unroll
            for (int j = 0; j < 4; j++) v[j] = __ldg(reinterpret_cast<const uint4*>(x + (size_t)row * DM) + j * 16 + (lane & 15));
            const uint32_t tag = ld_epoch() + 1;
            float c[8];
#pragma unroll
            for (int e = 0; e < 4; e++) { c[2 * e] = bf_lo(w[16 + e]) + bf_lo(w[20 + e]); c[2 * e + 1] = bf_hi(w[16 + e]) + bf_hi(w[20 + e]); }
#pragma unroll
            for (int n = 4; n > 0; n >>= 1) {
                const bool up = lane & (4 * n);
#pragma unroll
                for (int e = 0; e < n; e++) c[e] = (up ? c[e + n] : c[e]) + __shfl_xor_sync(0xffffffffu, up ? c[e] : c[e + n], 4 * n);
            }
            c[0] += __shfl_xor_sync(0xffffffffu, c[0], 2);
            c[0] += __shfl_xor_sync(0xffffffffu, c[0], 1);
            if (t4 == 0) st_tagged(reinterpret_cast<unsigned long long*>(g_cs) + (grp * 40 + rot) * 128 + rank * 64 + (warp - 8) * 8 + g, __float_as_uint(c[0]), tag);
            float s0 = 0.f, v0 = 0.f;
#pragma unroll
            for (int j = 0; j < 16; j++) s0 += bf_lo(w[j]) + bf_hi(w[j]);
#pragma unroll
            for (int d = 1; d < 16; d <<= 1) s0 += __shfl_xor_sync(0xffffffffu, s0, d);
            const float mean = s0 * (1.0f / DM);
#pragma unroll
            for (int j = 0; j < 16; j++) { const float a = bf_lo(w[j]) - mean, b = bf_hi(w[j]) - mean; v0 += fmaf(a, a, b * b); }
#pragma unroll
            for (int d = 1; d < 16; d <<= 1) v0 += __shfl_xor_sync(0xffffffffu, v0, d);
            if ((lane & 15) == 0) st_tagged(reinterpret_cast<unsigned long long*>(g_rs) + row, pack_bf16(mean, sqrtf(bf_round(bf_round(v0 * (1.0f / DM)) + 1e-5f))), tag);
            if (tid == 256) TSTAMP(45);
        }

        uint32_t q[4], qn[6];
        {
            float acc[64];
            const int rowblk = mblk * 2 + half, tile16 = rowblk * 4 + wq;
            const bool rel = wq < 2 && lane == 0, rel2 = wq == 2 && lane == 0;
            uint32_t empty;
            asm("mapa.shared::cluster.u32 %0, %1, %2;" : "=r"(empty) : "r"(bars + 8 * B_EMPTY), "r"(wq & 1));
#pragma unroll 1
            for (int t = pair; t < 5; t += 2) {
                uint32_t po = t == 4 ? POS_LAST : POS_STD, full = bars + 8 * (B_FULL + 8 * t), slot = (0x24130u >> (4 * t)) & 7, prev = 0;
                uint64_t da = mkdesc(half * 8192, 16, 1024, 1), db = mkdesc(OFF_RING, 8192, 1024, 1) + slot * 1024;
                if (tid == 0 && t == 0) TSTAMP(30);
                mbar_wait(full, 0);
                if (t > 0) mbar_wait(bars + 8 * (B_ORD + t - 1), 0);
#pragma unroll 1
                for (int j = 0; j < 8; j++) {
                    wg_fence();
#pragma unroll
                    for (int k = 0; k < 4; k++) wgmma_ss_n128(acc, da + k * 2, db + k * 128, (j | k) != 0);
                    wg_commit();
                    const uint32_t rel_a = empty + prev * 8, rel_b = bars + 8 * (j == 3 ? B_AFREE0 : B_AFREE + (j >> 1) - 1);
                    const bool do_a = j > 0 && rel, do_b = (po & 8) && rel2;
                    prev = slot; slot = slot == NRING - 1 ? 0 : slot + 1; po >>= 4; full += 8;
                    da = mkdesc(half * 8192, 16, 1024, 1) + (po & 7) * 1024; db = mkdesc(OFF_RING, 8192, 1024, 1) + slot * 1024;
                    if (j < 7) mbar_wait(full, 0); else if (rel2) mbar_arrive(bars + 8 * (B_ORD + t));
                    wg_wait<1>();
                    if (do_a) mbar_arrive_remote(rel_a);
                    if (do_b) mbar_arrive(rel_b);
                }
                if (t >= 3) {
                    mbar_wait(bars + 8 * B_QKV, 0);
                    const uint4* pq = g_q + (head * 128 + (qb * 8 + wg) * 4 + wq) * 32 + lane;
                    const uint4 v = __ldcg(pq), u = __ldcg(pq + 512);
                    qn[0] = v.x; qn[1] = v.y; qn[2] = v.z; qn[3] = v.w; q[0] = u.x; q[1] = u.y; q[2] = u.z; q[3] = u.w;
                }
                wg_wait<0>();
                if (rel) mbar_arrive_remote(empty + prev * 8);
                if (t >= 3 && rel2) mbar_arrive(bars + 8 * (t == 4 ? B_AFREE + 3 : B_AFREE0));
                pin<64>(acc);
                if (wq == 0 && half == 0 && lane == 0) TSTAMP(2 + 2 * t);
                mbar_wait(bars + 8 * (B_STATS + t), 0);
                uint32_t rs0, rs1;
                asm volatile("ld.shared.b32 %0, [%1];" : "=r"(rs0) : "r"(sb + OFF_RS + (half * 64 + wq * 16 + g) * 4));
                asm volatile("ld.shared.b32 %0, [%1];" : "=r"(rs1) : "r"(sb + OFF_RS + (half * 64 + wq * 16 + g + 8) * 4));
                const float m0 = bf_lo(rs0), m1 = bf_lo(rs1);
                float d0 = bf_hi(rs0), d1 = bf_hi(rs1);
#pragma unroll
                for (int j = 0; j < 16; j++) {
                    float c0, c1;
                    asm volatile("ld.shared.v2.f32 {%0,%1}, [%2];" : "=f"(c0), "=f"(c1) : "r"(sb + OFF_CS + (t * 128 + j * 8 + t4 * 2) * 4));
                    acc[4 * j] = fmaf(-m0, c0, acc[4 * j]); acc[4 * j + 1] = fmaf(-m0, c1, acc[4 * j + 1]);
                    acc[4 * j + 2] = fmaf(-m1, c0, acc[4 * j + 2]); acc[4 * j + 3] = fmaf(-m1, c1, acc[4 * j + 3]);
                }
                float r0 = __frcp_rn(d0), r1 = __frcp_rn(d1);
                if (t < nq) {
                    const int qt = qt0 + t, h0 = (qt & 3) * 8;
                    if (qt < 4) {
                        r0 *= 0.25f * 1.4426950408889634f * M71; r1 *= 0.25f * 1.4426950408889634f * M71;
                    } else if (qt < 8) {
                        r0 *= ((FIXED_MASK >> (2 * wq)) & 1) ? M71 : P71; r1 *= ((FIXED_MASK >> (2 * wq + 1)) & 1) ? M71 : P71;
                    }
                    uint32_t* p; int s8, sh;
                    if (qt < 8) { p = reinterpret_cast<uint32_t*>(g_k + h0 * 4096) + tile16 * 128 + lane; s8 = 64; sh = 32; }
                    else        { p = reinterpret_cast<uint32_t*>(g_v + h0 * 4096) + tile16 * 64 + lane;  s8 = 32; sh = 8192; }
#pragma unroll
                    for (int hh = 0; hh < 8; hh++) {
                        const float* a = acc + hh * 8;
                        const uint32_t e0 = pack_bf16(a[0] * r0, a[1] * r0), e1 = pack_bf16(a[2] * r1, a[3] * r1);
                        const uint32_t e2 = pack_bf16(a[4] * r0, a[5] * r0), e3 = pack_bf16(a[6] * r1, a[7] * r1);
                        if (qt < 4) g_q[((h0 + hh) * 128 + tile16) * 32 + lane] = make_uint4(e0, e1, e2, e3);
                        else { uint32_t* pp = p + hh * 16384; pp[0] = e0; pp[s8] = e1; pp[sh] = e2; pp[sh + s8] = e3; }
                    }
                } else {
                    uint32_t* p = reinterpret_cast<uint32_t*>(g_h + (rowblk * 28 + gu0 + t) * 512) + wq * 512 + lane;
                    r0 *= -1.4426950408889634f; r1 *= -1.4426950408889634f; d0 *= d0; d1 *= d1;
#pragma unroll
                    for (int j = 0; j < 8; j++) {
                        const float* a = acc + j * 4; const float* b = a + 32;
                        p[j * 32] = pack_bf16(a[0] * b[0] * rcpf(fmaf(ex2f(a[0] * r0), d0, d0)), a[1] * b[1] * rcpf(fmaf(ex2f(a[1] * r0), d0, d0)));
                        p[256 + j * 32] = pack_bf16(a[2] * b[2] * rcpf(fmaf(ex2f(a[2] * r1), d1, d1)), a[3] * b[3] * rcpf(fmaf(ex2f(a[3] * r1), d1, d1)));
                    }
                }
                __syncwarp();
                if (elect_one()) mbar_arrive(bars + 8 * (B_TILE + t));
                if (wq == 0 && half == 0 && lane == 0) TSTAMP(3 + 2 * t);
            }
        }
        const uint64_t db2 = mkdesc(OFF_B2, 128, 256, 0);
        float s[32];
        auto ref_point = [&](int ntile, uint32_t& b0, uint32_t& b1) {
            float m0 = -INFINITY, m1 = -INFINITY, f0 = -INFINITY, f1 = -INFINITY;
#pragma unroll 1
            for (int t = 0; t < ntile; t++) {
                wg_fence();
                wgmma_rs_n64_zero(s, q, mkdesc(k_tile_addr(0, t), 128, 256, 0));
                wg_commit();
                wg_wait<0>();
                pin<32>(s);
#pragma unroll
                for (int i = 0; i < 8; i++) {
                    if ((FIXED_MASK >> i) & 1) { f0 = fmaxf(f0, fmaxf(s[4 * i], s[4 * i + 1])); f1 = fmaxf(f1, fmaxf(s[4 * i + 2], s[4 * i + 3])); }
                    else                       { m0 = fmaxf(m0, fmaxf(s[4 * i], s[4 * i + 1])); m1 = fmaxf(m1, fmaxf(s[4 * i + 2], s[4 * i + 3])); }
                }
            }
            m0 = fmaxf(m0, f0 * P71 * P71); m1 = fmaxf(m1, f1 * P71 * P71);
            m0 = fmaxf(m0, __shfl_xor_sync(0xffffffffu, m0, 1)); m1 = fmaxf(m1, __shfl_xor_sync(0xffffffffu, m1, 1));
            m0 = fmaxf(m0, __shfl_xor_sync(0xffffffffu, m0, 2)); m1 = fmaxf(m1, __shfl_xor_sync(0xffffffffu, m1, 2));
#pragma unroll
            for (int r = 0; r < 2; r++) {
                const float m = -rintf(r ? m1 : m0), mh = bf_round(m), mm = bf_round(m - mh), ml = m - mh - mm;
                const float lo = t4 == 0 ? mh : t4 == 1 ? ml : t4 == 2 ? 1.f : 0.f, hi = t4 == 0 ? mm : t4 == 1 ? 1.f : 0.f;
                (r ? b1 : b0) = pack_bf16(lo * M71, hi * M71);
            }
        };
        uint32_t q2[4];
        int redo = 1;
        mbar_wait(bars + 8 * B_KV, 0);
#pragma unroll 1
        for (int round = -1; round < 2;) {
            if (redo) ref_point(redo, q2[0], q2[1]);
            if (round < 0) {
#pragma unroll
                for (int i = 0; i < 4; i++) { const uint32_t tq = q[i]; q[i] = qn[i]; qn[i] = tq; }
                qn[4] = q2[0]; qn[5] = q2[1];
                q2[2] = __shfl_sync(0xffffffffu, q2[0], 3); q2[3] = __shfl_sync(0xffffffffu, q2[1], 3);
                round = 0;
                continue;
            }
            float o[12]; uint32_t p[16];
#pragma unroll
            for (int i = 0; i < 12; i++) o[i] = 0.f;
            pin<12>(o); pin<4>(q2);
            if (wq == 0 && half == 0 && lane == 0) TSTAMP(12 + 4 * round + pair);
            uint64_t dk0 = mkdesc(4096, 128, 256, 0), dk1 = mkdesc(98304, 128, 256, 0), dv = mkdesc(0, 128, 65536, 0);
#pragma unroll 1
            for (int c = 0; c < 8; c++, dk0 += 512, dk1 += 256, dv += 512 - (256ull << 32)) {
                if (round == 0) mbar_wait(bars + 8 * (B_KV + c), 0);
#pragma unroll
                for (int t = 0; t < 4; t++) {
                    wg_fence();
                    wgmma_rs_n64_zero(s, q, (t & 2 ? dk1 : dk0) + (t & 1) * 128);
                    wgmma_rs_n64_acc(s, q2, db2);
                    wg_commit();
                    wg_wait<0>();
                    pin<32>(s); pin<16>(p);
#pragma unroll
                    for (int i = 0; i < 16; i++) {
                        if ((FIXED_MASK >> (i >> 1)) & 1) p[i] = exp2_fixed(s[2 * i], s[2 * i + 1], half2);
                        else                              p[i] = pack_bf16(ex2f(s[2 * i]), ex2f(s[2 * i + 1]));
                    }
                    wg_fence();
#pragma unroll
                    for (int k = 0; k < 4; k++) wgmma_rs_n24_acc(o, p + 4 * k, dv + (t * 4 + k) * 16);
                    wg_commit();
                }
            }
            wg_wait<0>();
            pin<12>(o);
            if (redo != 32) {
                float chk = (o[8] + o[10]) * 256.f;
#pragma unroll
                for (int i = 0; i < 8; i++) chk += fabsf(o[i]);
                uint32_t bad;
                asm volatile("{\n.reg .pred p, q;\nsetp.geu.f32 q, %1, 0f7F800000;\nbar.red.or.pred p, %2, 128, q;\nselp.u32 %0, 1, 0, p;\n}" : "=r"(bad) : "f"(chk), "r"(1 + wg) : "memory");
                if (__any_sync(0xffffffffu, bad)) { redo = 32; continue; }
            }
            const int rowblk = qb * 8 + round * 4 + wg;
            const float r0 = rcpf(o[8]), r1 = rcpf(o[10]);
            uint32_t* po = reinterpret_cast<uint32_t*>(g_o + (rowblk * 8 + (head >> 2)) * 512) + wq * 512 + (head & 3) * 64 + lane;
            po[0] = pack_bf16(o[0] * r0, o[1] * r0); po[256] = pack_bf16(o[2] * r1, o[3] * r1);
            po[32] = pack_bf16(o[4] * r0, o[5] * r0); po[288] = pack_bf16(o[6] * r1, o[7] * r1);
            if (round == 0) {
                __syncwarp();
                if (elect_one()) mbar_arrive(bars + 8 * (B_OW + pair));
            } else {
                bar_sync(1 + wg, 128);
                if (wq == 0 && elect_one()) { mbar_arrive(bars + 8 * B_DONE); signal_cnt(C_O + rowblk); }
            }
#pragma unroll
            for (int i = 0; i < 4; i++) q[i] = qn[i];
            q2[0] = qn[4]; q2[1] = qn[5];
            redo = 0;
            if (wq == 0 && half == 0 && lane == 0) TSTAMP(14 + 4 * round + pair);
            round++;
        }
    } else {
        uint32_t tag;
        if (wq == 0) {
            asm volatile("barrier.cluster.wait.aligned;" ::: "memory");
            if (tid == 512) TSTAMP(27);
            uint32_t slot = 2, ph = 1;
#pragma unroll 1
            for (int n = 2; n < 40; n++) {
                const int t = n >> 3, j = n & 7;
                const int kc = (n < 32 ? j : (POS_LAST >> (4 * j)) & 7) * 64;
                const CUtensorMap* m = t < nq ? &mqkv : rank ? &mw3 : &mw1;
                const int col = t < nq ? (qt0 + t) * 128 + rank * 64 : (gu0 + t) * 64;
                const uint32_t dst = ring + slot * 16384 + rank * 8192, fb = bars + 8 * (B_FULL + n);
                if (n < 8 && elect_one()) tma2d(sb + n * 16384, &mx, kc, mblk * 128, fb);
                mbar_wait(bars + 8 * (B_EMPTY + slot), ph);
                if (elect_one()) { TS2(0, n); tma2d_mc(dst, m, col, kc, fb); }
                if (++slot == NRING) { slot = 0; ph ^= 1; }
            }
            tag = ld_epoch() + 1;
        } else if (wq == 1) {
            tag = ld_epoch() + 1;
            mbar_wait(bars + 8 * (B_FULL + 6), 0);
#pragma unroll 1
            for (int t = 0; t < 5; t++) {
                float a[4];
                uint32_t r[4];
#pragma unroll 1
                for (int n = 0; n < 2000000; n++) {
                    uint32_t stale = ld_tagged2(g_rs + mblk * 64 + lane * 2, tag, r[0], r[1]) | ld_tagged2(g_rs + mblk * 64 + lane * 2 + 1, tag, r[2], r[3]);
                    a[0] = a[1] = a[2] = a[3] = 0.f;
#pragma unroll
                    for (int i = 0; i < 16; i++) {
                        uint32_t u, v;
                        stale |= ld_tagged2(g_cs + (grp * 5 + t) * 512 + i * 32 + lane, tag, u, v);
                        a[(i & 1) * 2] += __uint_as_float(u); a[(i & 1) * 2 + 1] += __uint_as_float(v);
                    }
                    if (__all_sync(0xffffffffu, stale == 0)) break;
                    if (t) __nanosleep(400);
                }
                asm volatile("st.shared.v2.f32 [%0], {%1,%2};" :: "r"(sb + OFF_CS + t * 512 + lane * 8), "f"(a[0]), "f"(a[1]) : "memory");
                asm volatile("st.shared.v2.f32 [%0], {%1,%2};" :: "r"(sb + OFF_CS + t * 512 + 256 + lane * 8), "f"(a[2]), "f"(a[3]) : "memory");
                if (t == 0) asm volatile("st.shared.v4.b32 [%0], {%1,%2,%3,%4};" :: "r"(sb + OFF_RS + lane * 16), "r"(r[0]), "r"(r[1]), "r"(r[2]), "r"(r[3]) : "memory");
                __syncwarp();
                if (elect_one()) { mbar_arrive(bars + 8 * (B_STATS + t)); TSTAMP(32 + t); }
            }
        } else {
            tag = ld_epoch() + 1;
            mbar_wait(bars + 8 * (B_FULL + wq - 1), 0);
#pragma unroll 1
            for (int t = wq - 1; t < 5; t += 2) {
                const __nv_bfloat16* src; int ld;
                if (t < nq) { src = wqkv + (qt0 + t) * 128 + rank * 64; ld = 3 * DM; }
                else        { src = (rank ? w3 : w1) + (gu0 + t) * 64; ld = FF; }
                src += (size_t)(rot * 64 + (lane >> 3)) * ld + (lane & 7) * 8;
                uint4 v[16];
                const uint32_t* w = reinterpret_cast<const uint32_t*>(v);
#pragma unroll
                for (int j = 0; j < 16; j++) v[j] = __ldg(reinterpret_cast<const uint4*>(src + (size_t)j * 4 * ld));
                float c[8];
#pragma unroll
                for (int e = 0; e < 4; e++) {
                    float a = 0.f, b = 0.f;
#pragma unroll
                    for (int j = 0; j < 16; j++) { a += bf_lo(w[4 * j + e]); b += bf_hi(w[4 * j + e]); }
                    c[2 * e] = a; c[2 * e + 1] = b;
                }
#pragma unroll
                for (int n = 4; n > 1; n >>= 1) {
                    const bool up = lane & (4 * n);
#pragma unroll
                    for (int e = 0; e < n; e++) c[e] = (up ? c[e + n] : c[e]) + __shfl_xor_sync(0xffffffffu, up ? c[e] : c[e + n], 4 * n);
                }
                unsigned long long* dst = reinterpret_cast<unsigned long long*>(g_cs) + ((grp * 5 + t) * 8 + rot) * 128 + rank * 64 + (lane & 7) * 8 + (lane >> 3) * 2;
                st_tagged(dst, __float_as_uint(c[0]), tag); st_tagged(dst + 1, __float_as_uint(c[1]), tag);
                if (lane == 0) TSTAMP(40 + t);
            }
        }
        if (wq == 3) {
#pragma unroll 1
            for (int i = lane; i < 256; i += 32) asm volatile("st.shared.v4.b32 [%0], {%1,%1,%1,%1};" :: "r"(sb + OFF_ONES + i * 16), "r"(0x3F803F80u) : "memory");
#pragma unroll 1
            for (int i = lane; i < 128; i += 32) {
                const bool fx = (FIXED_MASK >> (i >> 4)) & 1;
                uint32_t a = fx ? pack_bf16(M71, M71) : pack_bf16(P71, P71);
                uint32_t b = fx ? pack_bf16(M71, 47.0f * M71) : pack_bf16(P71, -79.5f * P71);
                uint32_t c = fx ? 0u : pack_bf16(0.08214f * P71, 0.f);
                if (i & 8) a = b = c = 0;
                asm volatile("st.shared.v4.b32 [%0], {%1,%2,%3,%4};" :: "r"(sb + OFF_B2 + i * 16), "r"(a), "r"(b), "r"(c), "r"(0) : "memory");
            }
            fence_async_smem();
            __syncwarp();
            if (elect_one()) mbar_arrive(bars + 8 * B_QKV);
        } else if (wq == 1) {
#pragma unroll 1
            for (int i = 0; i < 3; i++) wait_cnt(C_QKV + i * 4 + (head >> 3), 16 * tag, 100);
            fence_async_all();
            if (elect_one()) { mbar_arrive(bars + 8 * B_QKV); TSTAMP(29); }
            const uint8_t* gk = reinterpret_cast<const uint8_t*>(g_k + head * 4096);
            const uint8_t* gv = reinterpret_cast<const uint8_t*>(g_v + head * 4096);
#pragma unroll 1
            for (int c = 0; c < 8; c++) {
                if (!(c & 1)) mbar_wait(bars + 8 * (c ? B_AFREE + (c >> 1) : B_AFREE0), 0);
                if (elect_one()) {
                    const uint32_t b = bars + 8 * (B_KV + c);
                    mbar_expect(b, 16384);
                    bulk_load(sb + (2 * c + 1) * 4096, gk + c * 8192, 4096, b);
                    bulk_load(sb + 2 * c * 4096, gv + c * 4096, 4096, b);
                    bulk_load(sb + 65536 + c * 4096, gv + 32768 + c * 4096, 4096, b);
                    bulk_load(sb + 98304 + c * 4096, gk + c * 8192 + 4096, 4096, b);
                }
            }
        } else if (wq == 2) {
#pragma unroll 1
            for (int t = 0; t < 5; t++) {
                mbar_wait(bars + 8 * (B_TILE + t), 0);
                if (elect_one()) signal_cnt(t < nq ? C_QKV + qt0 + t : C_H + mblk);
            }
        }
        pin<1>(&tag);
        bar_sync(5, 128);
        if (tid == 639) g_epoch[blockIdx.x] = tag;
        const int cb = blockIdx.x & 7, pr = blockIdx.x >> 3;
        const int rb0 = (pr >> 2) * 8 + (pr & 3);
        uint32_t gate[2][16];
        {
            float dn[64];
            auto load_stage = [&](int kb, int st) {
                const uint32_t b = bars + 8 * (B_RING + st), dst = ring + st * 24576;
                mbar_expect(b, 24576);
                bulk_load(dst, g_h + (rb0 * 28 + kb) * 512, 8192, b);
                bulk_load(dst + 8192, g_h + ((rb0 + 4) * 28 + kb) * 512, 8192, b);
                tma2d(dst + 16384, &mw2, cb * 64, kb * 64, b);
            };
            if (wq == 0) {
                wait_cnt(C_H + (rb0 >> 1), 28 * tag, 200);
                wait_cnt(C_H + (rb0 >> 1) + 2, 28 * tag, 200);
                if (elect_one()) { TSTAMP(20); fence_async_all(); load_stage(0, 0); load_stage(1, 1); }
            }
            int st = 0; uint32_t ph = 0;
#pragma unroll 1
            for (int kb = 0; kb < 28; kb++) {
                mbar_wait(bars + 8 * (B_RING + st), ph);
                const uint64_t da = mkdesc(OFF_RING + st * 24576, 128, 1024, 0), db = mkdesc(OFF_RING + st * 24576 + 16384, 8192, 1024, 1);
                wg_fence();
#pragma unroll
                for (int k = 0; k < 4; k++) { wgmma_ss_n64(dn, da + k * 16, db + k * 128, (kb | k) != 0); wgmma_ss_n64(dn + 32, da + 512 + k * 16, db + k * 128, (kb | k) != 0); }
                wg_commit();
                wg_wait<1>();
                if (wq == 0 && kb < 26 && elect_one()) load_stage(kb + 2, st == 0 ? 2 : st - 1);
                if (++st == 3) { st = 0; ph ^= 1; }
            }
            wg_wait<0>();
            pin<64>(dn);
#pragma unroll
            for (int i = 0; i < 32; i++) gate[i >> 4][i & 15] = pack_bf16(siluf(dn[2 * i]), siluf(dn[2 * i + 1]));
        }
        float acc[32];
        if (tid == 512) TSTAMP(21);
        const uint32_t bar_wo = bars + 8 * B_WO;
        if (wq == 0 && elect_one()) {
            mbar_expect(bar_wo, 65536);
#pragma unroll 1
            for (int i = 0; i < 8; i++) tma2d(ring + i * 8192, &mwo, cb * 64, i * 64, bar_wo);
        }
        if (wq >= 2) {
            mbar_wait(bars + 8 * (B_OW + wq - 2), 0);
            if (elect_one()) {
                signal_cnt(C_O + qb * 8 + 2 * wq - 4);
                asm volatile("red.relaxed.gpu.global.add.u32 [%0], 1;" :: "l"(g_cnt + (C_O + qb * 8 + 2 * wq - 3) * 8) : "memory");
            }
        }
#pragma unroll 1
        for (int tl = 0; tl < 2; tl++) {
            const int rb = rb0 + 4 * tl;
            uint32_t xr[16];
            const uint32_t* px = reinterpret_cast<const uint32_t*>(x + (size_t)(rb * 64 + wq * 16 + g) * DM + cb * 64) + t4;
#pragma unroll
            for (int j = 0; j < 8; j++) { xr[2 * j] = __ldg(px + j * 4); xr[2 * j + 1] = __ldg(px + 8 * DM / 2 + j * 4); }
            if (wq == 0) {
                if (tl == 1) mbar_wait(bars + 8 * B_DONE, 0);
                wait_cnt(C_O + rb, 32 * tag, tl ? 20 : 200);
                if (elect_one()) {
                    fence_async_all();
                    TSTAMP(22 + 2 * tl);
#pragma unroll 1
                    for (int i = 0; i < (tl ? 8 : 2); i++) {
                        mbar_expect(bars + 8 * (B_O + i), 8192);
                        bulk_load((tl ? sb : ring + 65536) + i * 8192, g_o + (rb * 8 + i) * 512, 8192, bars + 8 * (B_O + i));
                    }
                }
            }
            if (tl == 0) mbar_wait(bar_wo, 0);
#pragma unroll 1
            for (int kb = 0; kb < 8; kb++) {
                mbar_wait(bars + 8 * (B_O + kb), tl);
                const uint32_t a = tl == 0 ? OFF_RING + 65536 + (kb & 1) * 8192 : kb * 8192;
                const uint64_t da = mkdesc(a, 128, 1024, 0), db = mkdesc(OFF_RING + kb * 8192, 8192, 1024, 1);
                wg_fence();
#pragma unroll
                for (int k = 0; k < 4; k++) wgmma_ss_n64(acc, da + k * 16, db + k * 128, (kb | k) != 0);
                wg_commit();
                if (tl == 0) {
                    wg_wait<0>();
                    bar_sync(5, 128);
                    if (wq == 0 && kb < 6 && elect_one()) { mbar_expect(bars + 8 * (B_O + kb + 2), 8192); bulk_load(sb + a, g_o + (rb * 8 + kb + 2) * 512, 8192, bars + 8 * (B_O + kb + 2)); }
                }
            }
            wg_wait<0>();
            pin<32>(acc);
            uint32_t* po = reinterpret_cast<uint32_t*>(out + (size_t)(rb * 64 + wq * 16 + g) * DM + cb * 64) + t4;
#pragma unroll
            for (int i = 0; i < 16; i++) {
                const uint32_t r = pack_bf16(fmaf(acc[2 * i], bf_lo(gate[0][i]), bf_lo(xr[i])), fmaf(acc[2 * i + 1], bf_hi(gate[0][i]), bf_hi(xr[i])));
                po[(i & 1) * (8 * DM / 2) + (i >> 1) * 4] = r;
                gate[0][i] = gate[1][i];
            }
            if (tid == 512) TSTAMP(23 + 2 * tl);
        }
    }
}

typedef CUresult (*EncodeFn)(CUtensorMap*, CUtensorMapDataType, cuuint32_t, void*, const cuuint64_t*, const cuuint64_t*, const cuuint32_t*,
                             const cuuint32_t*, CUtensorMapInterleave, CUtensorMapSwizzle, CUtensorMapL2promotion, CUtensorMapFloatOOBfill);

void make_map(EncodeFn fn, CUtensorMap* m, const void* p, int rows, int cols, int box_rows) {
    cuuint64_t dims[2] = {(cuuint64_t)cols, (cuuint64_t)rows};
    cuuint64_t strides[1] = {(cuuint64_t)cols * 2};
    cuuint32_t box[2] = {64, (cuuint32_t)box_rows};
    cuuint32_t es[2] = {1, 1};
    fn(m, CU_TENSOR_MAP_DATA_TYPE_BFLOAT16, 2, const_cast<void*>(p), dims, strides, box, es, CU_TENSOR_MAP_INTERLEAVE_NONE,
       CU_TENSOR_MAP_SWIZZLE_128B, CU_TENSOR_MAP_L2_PROMOTION_L2_128B, CU_TENSOR_MAP_FLOAT_OOB_FILL_NONE);
}

}

extern "C" void kernel_launch(void* const* d_in, const int* in_sizes, int n_in, void* d_out, int out_size) {
    const __nv_bfloat16* x = (const __nv_bfloat16*)d_in[0];
    static EncodeFn fn = nullptr;
    if (!fn) {
        cudaDriverEntryPointQueryResult qr;
        cudaGetDriverEntryPoint("cuTensorMapEncodeTiled", (void**)&fn, cudaEnableDefault, &qr);
        cudaFuncSetAttribute(mega_kernel, cudaFuncAttributeMaxDynamicSharedMemorySize, SMEM_BYTES);
    }
    CUtensorMap mx, mqkv, mw1, mw3, mw2, mwo;
    make_map(fn, &mx, d_in[0], SEQ, DM, 128);
    make_map(fn, &mqkv, d_in[1], DM, 3 * DM, 64);
    make_map(fn, &mwo, d_in[2], DM, DM, 64);
    make_map(fn, &mw1, d_in[4], DM, FF, 64);
    make_map(fn, &mw3, d_in[5], DM, FF, 64);
    make_map(fn, &mw2, d_in[6], FF, DM, 64);
    mega_kernel<<<128, 640, SMEM_BYTES, cudaStreamPerThread>>>(x, (const __nv_bfloat16*)d_in[1], (const __nv_bfloat16*)d_in[4], (const __nv_bfloat16*)d_in[5],
                                                               (__nv_bfloat16*)d_out, mx, mqkv, mw1, mw3, mw2, mwo, 0x3F003F00u);
}
```

```cpp
#include <cuda_runtime.h>
#include <cuda_bf16.h>
#include <cuda.h>
#include <stdint.h>

namespace {

constexpr int SEQ = 2048, DM = 512, FF = 1792;

__device__ uint4 g_q[32 * 128 * 32];
__device__ uint4 g_k[32 * 4096];
__device__ uint4 g_v[32 * 4096];
__device__ uint4 g_h[32 * 28 * 512];
__device__ uint4 g_o[32 * 8 * 512];
__device__ ulonglong2 g_cs[40 * 8 * 64];
__device__ ulonglong2 g_rs[SEQ / 2];
constexpr int C_QKV = 0, C_H = 12, C_O = 28, C_NUM = 60;
__device__ unsigned g_cnt[C_NUM * 8];
__device__ unsigned g_epoch[128];
#define TSTAMP(i)
#define TS2(k, i)

__device__ __forceinline__ uint32_t smem_u32(const void* p) { return (uint32_t)__cvta_generic_to_shared(p); }
__device__ __forceinline__ void mbar_init(uint32_t a, int c) { asm volatile("mbarrier.init.shared::cta.b64 [%0], %1;" :: "r"(a), "r"(c)); }
__device__ __forceinline__ void mbar_expect(uint32_t a, int b) { asm volatile("mbarrier.arrive.expect_tx.shared::cta.b64 _, [%0], %1;" :: "r"(a), "r"(b) : "memory"); }
__device__ __forceinline__ void mbar_arrive(uint32_t a) { asm volatile("mbarrier.arrive.shared::cta.b64 _, [%0];" :: "r"(a) : "memory"); }
__device__ __forceinline__ void mbar_arrive_remote(uint32_t a) { asm volatile("mbarrier.arrive.shared::cluster.b64 _, [%0];" :: "r"(a) : "memory"); }
__device__ __forceinline__ bool mbar_try(uint32_t a, uint32_t ph) {
    uint32_t ok;
    asm volatile("{\n.reg .pred p;\nmbarrier.try_wait.parity.shared::cta.b64 p, [%1], %2;\nselp.u32 %0, 1, 0, p;\n}" : "=r"(ok) : "r"(a), "r"(ph) : "memory");
    return ok;
}
__device__ __forceinline__ void mbar_wait(uint32_t a, uint32_t ph) {
    int n = 1 << 22;
#pragma unroll 1
    do { n = __all_sync(0xffffffffu, mbar_try(a, ph)) ? 0 : n - 1; } while (n > 0);
}
__device__ __forceinline__ bool elect_one() {
    uint32_t p;
    asm volatile("{\n.reg .pred P;\nelect.sync _|P, 0xffffffff;\nselp.u32 %0, 1, 0, P;\n}" : "=r"(p));
    return p;
}
__device__ __forceinline__ void signal_cnt(int c) {
    asm volatile("fence.release.gpu;\nred.relaxed.gpu.global.add.u32 [%0], 1;" :: "l"(g_cnt + c * 8) : "memory");
}
__device__ __forceinline__ void wait_cnt(int c, unsigned target, int ns) {
#pragma unroll 1
    for (int n = 0; n < 2000000; n++) {
        unsigned v;
        asm volatile("ld.relaxed.gpu.global.u32 %0, [%1];" : "=r"(v) : "l"(g_cnt + c * 8) : "memory");
        if (__all_sync(0xffffffffu, (int)(v - target) >= 0)) break;
        __nanosleep(ns);
    }
}
__device__ __forceinline__ uint32_t ld_epoch() {
    uint32_t e;
    asm volatile("ld.relaxed.gpu.global.u32 %0, [%1];" : "=r"(e) : "l"(g_epoch + blockIdx.x) : "memory");
    return e;
}
__device__ __forceinline__ void st_tagged(void* p, uint32_t v, uint32_t tag) {
    asm volatile("st.relaxed.gpu.global.b64 [%0], %1;" :: "l"(p), "l"((unsigned long long)tag << 32 | v) : "memory");
}
__device__ __forceinline__ uint32_t ld_tagged2(const ulonglong2* p, uint32_t tag, uint32_t& a, uint32_t& b) {
    unsigned long long u, v;
    asm volatile("ld.relaxed.gpu.global.v2.b64 {%0,%1}, [%2];" : "=l"(u), "=l"(v) : "l"(p) : "memory");
    a = (uint32_t)u; b = (uint32_t)v;
    return ((uint32_t)(u >> 32) ^ tag) | ((uint32_t)(v >> 32) ^ tag);
}
__device__ __forceinline__ void tma2d(uint32_t dst, const CUtensorMap* m, int c0, int c1, uint32_t bar) {
    asm volatile("cp.async.bulk.tensor.2d.shared::cluster.global.mbarrier::complete_tx::bytes [%0], [%1, {%3, %4}], [%2];"
                 :: "r"(dst), "l"(m), "r"(bar), "r"(c0), "r"(c1) : "memory");
}
__device__ __forceinline__ void tma2d_mc(uint32_t dst, const CUtensorMap* m, int c0, int c1, uint32_t bar) {
    asm volatile("cp.async.bulk.tensor.2d.shared::cluster.global.mbarrier::complete_tx::bytes.multicast::cluster [%0], [%1, {%3, %4}], [%2], %5;"
                 :: "r"(dst), "l"(m), "r"(bar), "r"(c0), "r"(c1), "h"((uint16_t)3) : "memory");
}
__device__ __forceinline__ void bulk_load(uint32_t dst, const void* src, int bytes, uint32_t bar) {
    asm volatile("cp.async.bulk.shared::cluster.global.mbarrier::complete_tx::bytes [%0], [%1], %2, [%3];"
                 :: "r"(dst), "l"(src), "r"(bytes), "r"(bar) : "memory");
}
__device__ __forceinline__ void bar_sync(int id, int n) { asm volatile("bar.sync %0, %1;" :: "r"(id), "r"(n) : "memory"); }
__device__ __forceinline__ void fence_async_smem() { asm volatile("fence.proxy.async.shared::cta;" ::: "memory"); }
__device__ __forceinline__ void fence_async_all() { asm volatile("fence.acquire.gpu;\nfence.proxy.async.global;" ::: "memory"); }
__device__ __forceinline__ void wg_fence() { asm volatile("wgmma.fence.sync.aligned;" ::: "memory"); }
__device__ __forceinline__ void wg_commit() { asm volatile("wgmma.commit_group.sync.aligned;" ::: "memory"); }
template <int N> __device__ __forceinline__ void wg_wait() { asm volatile("wgmma.wait_group.sync.aligned %0;" :: "n"(N) : "memory"); }
template <int N> __device__ __forceinline__ void pin(float* d) {
#pragma unroll
    for (int i = 0; i < N; i++) asm volatile("" : "+f"(d[i]) :: "memory");
}
template <int N> __device__ __forceinline__ void pin(uint32_t* d) {
#pragma unroll
    for (int i = 0; i < N; i++) asm volatile("" : "+r"(d[i]) :: "memory");
}
constexpr uint32_t SMEM_BASE = 1024;
__device__ __forceinline__ uint64_t mkdesc(uint32_t off, uint32_t lbo, uint32_t sbo, uint32_t swz) {
    return (uint64_t)((SMEM_BASE + off) >> 4) | ((uint64_t)(lbo >> 4) << 16) | ((uint64_t)(sbo >> 4) << 32) | ((uint64_t)swz << 62);
}
__device__ __forceinline__ float ex2f(float x) { float y; asm("ex2.approx.ftz.f32 %0, %1;" : "=f"(y) : "f"(x)); return y; }
__device__ __forceinline__ float rcpf(float x) { float y; asm("rcp.approx.ftz.f32 %0, %1;" : "=f"(y) : "f"(x)); return y; }
__device__ __forceinline__ uint32_t pack_bf16(float lo, float hi) { uint32_t r; asm("cvt.rn.bf16x2.f32 %0, %1, %2;" : "=r"(r) : "f"(hi), "f"(lo)); return r; }
__device__ __forceinline__ float bf_lo(uint32_t v) { return __uint_as_float(v << 16); }
__device__ __forceinline__ float bf_hi(uint32_t v) { return __uint_as_float(v & 0xFFFF0000u); }
__device__ __forceinline__ float bf_round(float x) { return __bfloat162float(__float2bfloat16_rn(x)); }
__device__ __forceinline__ float siluf(float g) { return g * rcpf(1.0f + ex2f(g * -1.4426950408889634f)); }

__device__ __forceinline__ void wgmma_ss_n256(float* d, uint64_t da, uint64_t db, int acc) {
    asm volatile("{\n.reg .pred p;\nsetp.ne.b32 p, %130, 0;\nwgmma.mma_async.sync.aligned.m64n256k16.f32.bf16.bf16 {"
        "%0,%1,%2,%3,%4,%5,%6,%7,%8,%9,%10,%11,%12,%13,%14,%15,%16,%17,%18,%19,%20,%21,%22,%23,%24,%25,%26,%27,%28,%29,%30,%31,%32,%33,%34,%35,%36,%37,%38,%39,"
        "%40,%41,%42,%43,%44,%45,%46,%47,%48,%49,%50,%51,%52,%53,%54,%55,%56,%57,%58,%59,%60,%61,%62,%63,%64,%65,%66,%67,%68,%69,%70,%71,%72,%73,%74,%75,%76,"
        "%77,%78,%79,%80,%81,%82,%83,%84,%85,%86,%87,%88,%89,%90,%91,%92,%93,%94,%95,%96,%97,%98,%99,%100,%101,%102,%103,%104,%105,%106,%107,%108,%109,%110,"
        "%111,%112,%113,%114,%115,%116,%117,%118,%119,%120,%121,%122,%123,%124,%125,%126,%127"
        "}, %128, %129, p, 1, 1, 0, 1;\n}\n"
        : "+f"(d[0]),"+f"(d[1]),"+f"(d[2]),"+f"(d[3]),"+f"(d[4]),"+f"(d[5]),"+f"(d[6]),"+f"(d[7]),"+f"(d[8]),"+f"(d[9]),"+f"(d[10]),"+f"(d[11]),"+f"(d[12]),
          "+f"(d[13]),"+f"(d[14]),"+f"(d[15]),"+f"(d[16]),"+f"(d[17]),"+f"(d[18]),"+f"(d[19]),"+f"(d[20]),"+f"(d[21]),"+f"(d[22]),"+f"(d[23]),"+f"(d[24]),
          "+f"(d[25]),"+f"(d[26]),"+f"(d[27]),"+f"(d[28]),"+f"(d[29]),"+f"(d[30]),"+f"(d[31]),"+f"(d[32]),"+f"(d[33]),"+f"(d[34]),"+f"(d[35]),"+f"(d[36]),
          "+f"(d[37]),"+f"(d[38]),"+f"(d[39]),"+f"(d[40]),"+f"(d[41]),"+f"(d[42]),"+f"(d[43]),"+f"(d[44]),"+f"(d[45]),"+f"(d[46]),"+f"(d[47]),"+f"(d[48]),
          "+f"(d[49]),"+f"(d[50]),"+f"(d[51]),"+f"(d[52]),"+f"(d[53]),"+f"(d[54]),"+f"(d[55]),"+f"(d[56]),"+f"(d[57]),"+f"(d[58]),"+f"(d[59]),"+f"(d[60]),
          "+f"(d[61]),"+f"(d[62]),"+f"(d[63]),"+f"(d[64]),"+f"(d[65]),"+f"(d[66]),"+f"(d[67]),"+f"(d[68]),"+f"(d[69]),"+f"(d[70]),"+f"(d[71]),"+f"(d[72]),
          "+f"(d[73]),"+f"(d[74]),"+f"(d[75]),"+f"(d[76]),"+f"(d[77]),"+f"(d[78]),"+f"(d[79]),"+f"(d[80]),"+f"(d[81]),"+f"(d[82]),"+f"(d[83]),"+f"(d[84]),
          "+f"(d[85]),"+f"(d[86]),"+f"(d[87]),"+f"(d[88]),"+f"(d[89]),"+f"(d[90]),"+f"(d[91]),"+f"(d[92]),"+f"(d[93]),"+f"(d[94]),"+f"(d[95]),"+f"(d[96]),
          "+f"(d[97]),"+f"(d[98]),"+f"(d[99]),"+f"(d[100]),"+f"(d[101]),"+f"(d[102]),"+f"(d[103]),"+f"(d[104]),"+f"(d[105]),"+f"(d[106]),"+f"(d[107]),
          "+f"(d[108]),"+f"(d[109]),"+f"(d[110]),"+f"(d[111]),"+f"(d[112]),"+f"(d[113]),"+f"(d[114]),"+f"(d[115]),"+f"(d[116]),"+f"(d[117]),"+f"(d[118]),
          "+f"(d[119]),"+f"(d[120]),"+f"(d[121]),"+f"(d[122]),"+f"(d[123]),"+f"(d[124]),"+f"(d[125]),"+f"(d[126]),"+f"(d[127])
        : "l"(da), "l"(db), "r"(acc));
}
__device__ __forceinline__ void wgmma_ss_n128(float* d, uint64_t da, uint64_t db, int acc) {
    asm volatile("{\n.reg .pred p;\nsetp.ne.b32 p, %66, 0;\nwgmma.mma_async.sync.aligned.m64n128k16.f32.bf16.bf16 {"
        "%0,%1,%2,%3,%4,%5,%6,%7,%8,%9,%10,%11,%12,%13,%14,%15,%16,%17,%18,%19,%20,%21,%22,%23,%24,%25,%26,%27,%28,%29,%30,%31,%32,%33,%34,%35,%36,%37,%38,%39,"
        "%40,%41,%42,%43,%44,%45,%46,%47,%48,%49,%50,%51,%52,%53,%54,%55,%56,%57,%58,%59,%60,%61,%62,%63"
        "}, %64, %65, p, 1, 1, 0, 1;\n}\n"
        : "+f"(d[0]),"+f"(d[1]),"+f"(d[2]),"+f"(d[3]),"+f"(d[4]),"+f"(d[5]),"+f"(d[6]),"+f"(d[7]),"+f"(d[8]),"+f"(d[9]),"+f"(d[10]),"+f"(d[11]),"+f"(d[12]),
          "+f"(d[13]),"+f"(d[14]),"+f"(d[15]),"+f"(d[16]),"+f"(d[17]),"+f"(d[18]),"+f"(d[19]),"+f"(d[20]),"+f"(d[21]),"+f"(d[22]),"+f"(d[23]),"+f"(d[24]),
          "+f"(d[25]),"+f"(d[26]),"+f"(d[27]),"+f"(d[28]),"+f"(d[29]),"+f"(d[30]),"+f"(d[31]),"+f"(d[32]),"+f"(d[33]),"+f"(d[34]),"+f"(d[35]),"+f"(d[36]),
          "+f"(d[37]),"+f"(d[38]),"+f"(d[39]),"+f"(d[40]),"+f"(d[41]),"+f"(d[42]),"+f"(d[43]),"+f"(d[44]),"+f"(d[45]),"+f"(d[46]),"+f"(d[47]),"+f"(d[48]),
          "+f"(d[49]),"+f"(d[50]),"+f"(d[51]),"+f"(d[52]),"+f"(d[53]),"+f"(d[54]),"+f"(d[55]),"+f"(d[56]),"+f"(d[57]),"+f"(d[58]),"+f"(d[59]),"+f"(d[60]),
          "+f"(d[61]),"+f"(d[62]),"+f"(d[63])
        : "l"(da), "l"(db), "r"(acc));
}
__device__ __forceinline__ void wgmma_ss_n64(float* d, uint64_t da, uint64_t db, int acc) {
    asm volatile("{\n.reg .pred p;\nsetp.ne.b32 p, %34, 0;\nwgmma.mma_async.sync.aligned.m64n64k16.f32.bf16.bf16 {"
        "%0,%1,%2,%3,%4,%5,%6,%7,%8,%9,%10,%11,%12,%13,%14,%15,%16,%17,%18,%19,%20,%21,%22,%23,%24,%25,%26,%27,%28,%29,%30,%31"
        "}, %32, %33, p, 1, 1, 0, 1;\n}\n"
        : "+f"(d[0]),"+f"(d[1]),"+f"(d[2]),"+f"(d[3]),"+f"(d[4]),"+f"(d[5]),"+f"(d[6]),"+f"(d[7]),"+f"(d[8]),"+f"(d[9]),"+f"(d[10]),"+f"(d[11]),"+f"(d[12]),
          "+f"(d[13]),"+f"(d[14]),"+f"(d[15]),"+f"(d[16]),"+f"(d[17]),"+f"(d[18]),"+f"(d[19]),"+f"(d[20]),"+f"(d[21]),"+f"(d[22]),"+f"(d[23]),"+f"(d[24]),
          "+f"(d[25]),"+f"(d[26]),"+f"(d[27]),"+f"(d[28]),"+f"(d[29]),"+f"(d[30]),"+f"(d[31])
        : "l"(da), "l"(db), "r"(acc));
}
__device__ __forceinline__ void wgmma_rs_n64_zero(float* d, const uint32_t* a, uint64_t db) {
    asm volatile("wgmma.mma_async.sync.aligned.m64n64k16.f32.bf16.bf16 {"
        "%0,%1,%2,%3,%4,%5,%6,%7,%8,%9,%10,%11,%12,%13,%14,%15,%16,%17,%18,%19,%20,%21,%22,%23,%24,%25,%26,%27,%28,%29,%30,%31"
        "}, {%32,%33,%34,%35}, %36, 0, 1, 1, 0;\n"
        : "=f"(d[0]),"=f"(d[1]),"=f"(d[2]),"=f"(d[3]),"=f"(d[4]),"=f"(d[5]),"=f"(d[6]),"=f"(d[7]),"=f"(d[8]),"=f"(d[9]),"=f"(d[10]),"=f"(d[11]),"=f"(d[12]),
          "=f"(d[13]),"=f"(d[14]),"=f"(d[15]),"=f"(d[16]),"=f"(d[17]),"=f"(d[18]),"=f"(d[19]),"=f"(d[20]),"=f"(d[21]),"=f"(d[22]),"=f"(d[23]),"=f"(d[24]),
          "=f"(d[25]),"=f"(d[26]),"=f"(d[27]),"=f"(d[28]),"=f"(d[29]),"=f"(d[30]),"=f"(d[31])
        : "r"(a[0]), "r"(a[1]), "r"(a[2]), "r"(a[3]), "l"(db));
}
__device__ __forceinline__ void wgmma_rs_n64_acc(float* d, const uint32_t* a, uint64_t db) {
    asm volatile("wgmma.mma_async.sync.aligned.m64n64k16.f32.bf16.bf16 {"
        "%0,%1,%2,%3,%4,%5,%6,%7,%8,%9,%10,%11,%12,%13,%14,%15,%16,%17,%18,%19,%20,%21,%22,%23,%24,%25,%26,%27,%28,%29,%30,%31"
        "}, {%32,%33,%34,%35}, %36, 1, 1, 1, 0;\n"
        : "+f"(d[0]),"+f"(d[1]),"+f"(d[2]),"+f"(d[3]),"+f"(d[4]),"+f"(d[5]),"+f"(d[6]),"+f"(d[7]),"+f"(d[8]),"+f"(d[9]),"+f"(d[10]),"+f"(d[11]),"+f"(d[12]),
          "+f"(d[13]),"+f"(d[14]),"+f"(d[15]),"+f"(d[16]),"+f"(d[17]),"+f"(d[18]),"+f"(d[19]),"+f"(d[20]),"+f"(d[21]),"+f"(d[22]),"+f"(d[23]),"+f"(d[24]),
          "+f"(d[25]),"+f"(d[26]),"+f"(d[27]),"+f"(d[28]),"+f"(d[29]),"+f"(d[30]),"+f"(d[31])
        : "r"(a[0]), "r"(a[1]), "r"(a[2]), "r"(a[3]), "l"(db));
}
__device__ __forceinline__ void wgmma_rs_n24_acc(float* d, const uint32_t* a, uint64_t db) {
    asm volatile("wgmma.mma_async.sync.aligned.m64n24k16.f32.bf16.bf16 {"
        "%0,%1,%2,%3,%4,%5,%6,%7,%8,%9,%10,%11"
        "}, {%12,%13,%14,%15}, %16, 1, 1, 1, 1;\n"
        : "+f"(d[0]),"+f"(d[1]),"+f"(d[2]),"+f"(d[3]),"+f"(d[4]),"+f"(d[5]),"+f"(d[6]),"+f"(d[7]),"+f"(d[8]),"+f"(d[9]),"+f"(d[10]),"+f"(d[11])
        : "r"(a[0]), "r"(a[1]), "r"(a[2]), "r"(a[3]), "l"(db));
}
__device__ __forceinline__ void wgmma_rs_n24_zero(float* d, const uint32_t* a, uint64_t db) {
    asm volatile("wgmma.mma_async.sync.aligned.m64n24k16.f32.bf16.bf16 {"
        "%0,%1,%2,%3,%4,%5,%6,%7,%8,%9,%10,%11"
        "}, {%12,%13,%14,%15}, %16, 0, 1, 1, 1;\n"
        : "=f"(d[0]),"=f"(d[1]),"=f"(d[2]),"=f"(d[3]),"=f"(d[4]),"=f"(d[5]),"=f"(d[6]),"=f"(d[7]),"=f"(d[8]),"=f"(d[9]),"=f"(d[10]),"=f"(d[11])
        : "r"(a[0]), "r"(a[1]), "r"(a[2]), "r"(a[3]), "l"(db));
}

constexpr int OFF_ONES = 131072;
constexpr int OFF_RING = OFF_ONES + 4096;
constexpr int NRING = 5;
constexpr int OFF_B2 = OFF_RING + NRING * 16384;
constexpr int OFF_CS = OFF_B2 + 2048;
constexpr int OFF_RS = OFF_CS + 2560;
constexpr int OFF_BAR = OFF_RS + 1024;
enum { B_FULL = 0, B_STATS = 40, B_KV = 45, B_RING = 53, B_WO = 56, B_O = 57, B_CNT2 = 65,
       B_AFREE = 65, B_ORD = 69, B_QKV = 74, B_CNT4 = 75, B_EMPTY = 75, B_AFREE0 = 80, B_DONE = 81, B_CNT8 = 82, B_TILE = 82, B_OW = 87, B_NUM = 100 };
constexpr int OFF_TS = OFF_BAR + 1024;
constexpr int SMEM_BYTES = OFF_BAR + B_NUM * 8;
constexpr unsigned FIXED_MASK = 0xB5;
constexpr float P71 = 2361183241434822606848.0f, M71 = 4.235164736271502e-22f;

__device__ __forceinline__ uint32_t exp2_fixed(float lo, float hi, uint32_t half2) {
    uint32_t y, g, d;
    asm("cvt.pack.sat.s16.s32 %0, %1, %2;" : "=r"(y) : "r"(__float_as_uint(hi)), "r"(__float_as_uint(lo)));
    asm("lop3.b32 %0, %1, 0x007F007F, %2, 0xEA;" : "=r"(g) : "r"(y), "r"(half2));
    asm("fma.rn.bf16x2 %0, %1, %2, %3;" : "=r"(d) : "r"(y), "r"(g), "r"(y & 0xFF80FF80u));
    return d;
}
__device__ __forceinline__ uint32_t k_tile_addr(uint32_t base, int tile) {
    const int c = tile >> 2;
    return base + ((tile & 2) ? 98304 + c * 4096 : (2 * c + 1) * 4096) + (tile & 1) * 2048;
}
constexpr uint32_t POS_STD = 0x76543210u, POS_LAST = 0xB75A9640u;

__global__ void __cluster_dims__(2, 1, 1) __launch_bounds__(640, 1)
mega_kernel(const __nv_bfloat16* __restrict__ x, const __nv_bfloat16* __restrict__ wqkv, const __nv_bfloat16* __restrict__ w1,
            const __nv_bfloat16* __restrict__ w3, __nv_bfloat16* __restrict__ out,
            const __grid_constant__ CUtensorMap mx, const __grid_constant__ CUtensorMap mqkv, const __grid_constant__ CUtensorMap mw1,
            const __grid_constant__ CUtensorMap mw3, const __grid_constant__ CUtensorMap mw2, const __grid_constant__ CUtensorMap mwo,
            uint32_t half2) {
    extern __shared__ __align__(1024) uint8_t smem_raw[];
    const uint32_t sb = __shfl_sync(0xffffffffu, smem_u32(smem_raw), 0);
    if ((sb & 0xFFFFFF) != SMEM_BASE) __trap();
    const uint32_t bars = sb + OFF_BAR, ring = sb + OFF_RING;
    const int tid = threadIdx.x, lane = tid & 31, g = lane >> 2, t4 = lane & 3;
    const int warp = __shfl_sync(0xffffffffu, tid >> 5, 0), wg = warp >> 2, wq = warp & 3;
    const int rank = blockIdx.x & 1, cl = blockIdx.x >> 1;
    const int grp = cl < 4 ? 4 + cl : cl < 36 ? (cl - 4) >> 3 : 4 + (cl - 36) / 7;
    const int rot = cl < 4 ? 7 : cl < 36 ? (cl - 4) & 7 : (cl - 36) % 7;
    const int mblk = rot * 2 + rank;
    const int nq = grp < 4 ? 2 : 1;
    const int qt0 = grp < 4 ? 2 * grp : 4 + grp;
    const int gu0 = (grp < 4 ? 3 * grp : 4 * grp - 4) - nq;
    const int head = blockIdx.x >> 2, qb = blockIdx.x & 3;

    if (elect_one()) {
#pragma unroll
        for (int i = 0; i < 5; i++) { const int b = warp * 5 + i; mbar_init(bars + 8 * b, b < B_CNT2 ? 1 : b < B_CNT4 ? 2 : b < B_CNT8 ? 4 : 8); }
        if (warp == 0) {
            fence_async_smem();
#pragma unroll
            for (int j = 0; j < 2; j++) {
                tma2d(sb + j * 16384, &mx, j * 64, mblk * 128, bars + 8 * (B_FULL + j));
                tma2d(ring + j * 16384, &mqkv, qt0 * 128, j * 64, bars + 8 * (B_FULL + j));
                tma2d(ring + j * 16384 + 8192, &mqkv, qt0 * 128 + 64, j * 64, bars + 8 * (B_FULL + j));
            }
        }
        if (warp < 8) {
#pragma unroll
            for (int i = 0; i < 5; i++) mbar_expect(bars + 8 * (warp * 5 + i), warp * 5 + i < 8 ? 32768 : 16384);
        }
        if (warp == 16) asm volatile("prefetch.tensormap [%0];" :: "l"(rank ? &mw3 : &mw1) : "memory");
        asm volatile("fence.mbarrier_init.release.cluster;" ::: "memory");
    }
    __syncthreads();
    if (tid == 512) TSTAMP(26);
    asm volatile("barrier.cluster.arrive.relaxed.aligned;" ::: "memory");

    if (wg < 4) {
        const int pair = wg >> 1, half = wg & 1;
        if (pair == 1) {
            const int row = mblk * 128 + grp * 16 + (warp - 8) * 2 + (lane >> 4);
            uint4 v[6];
            const uint32_t* w = reinterpret_cast<const uint32_t*>(v);
#pragma unroll
            for (int j = 0; j < 2; j++) v[4 + j] = __ldg(reinterpret_cast<const uint4*>(wqkv + (size_t)(rot * 64 + (warp - 8) * 8 + j * 4 + (lane >> 3)) * (3 * DM) + qt0 * 128 + rank * 64) + (lane & 7));
#pragma unroll
            for (int j = 0; j < 4; j++) v[j] = __ldg(reinterpret_cast<const uint4*>(x + (size_t)row * DM) + j * 16 + (lane & 15));
            const uint32_t tag = ld_epoch() + 1;
            float c[8];
#pragma unroll
            for (int e = 0; e < 4; e++) { c[2 * e] = bf_lo(w[16 + e]) + bf_lo(w[20 + e]); c[2 * e + 1] = bf_hi(w[16 + e]) + bf_hi(w[20 + e]); }
#pragma unroll
            for (int n = 4; n > 1; n >>= 1) {
                const bool up = lane & (4 * n);
#pragma unroll
                for (int e = 0; e < n; e++) c[e] = (up ? c[e + n] : c[e]) + __shfl_xor_sync(0xffffffffu, up ? c[e] : c[e + n], 4 * n);
            }
            asm volatile("st.shared.v2.f32 [%0], {%1,%2};" :: "r"(sb + OFF_CS + 512 + (warp - 8) * 256 + (lane & 7) * 32 + (lane >> 3) * 8), "f"(c[0]), "f"(c[1]) : "memory");
            bar_sync(6, 256);
            if (warp < 10) {
#pragma unroll
                for (int e = 0; e < 8; e++) asm volatile("ld.shared.f32 %0, [%1];" : "=f"(c[e]) : "r"(sb + OFF_CS + 512 + e * 256 + (tid & 63) * 4));
                st_tagged(reinterpret_cast<unsigned long long*>(g_cs) + (grp * 40 + rot) * 128 + rank * 64 + (tid & 63),
                          __float_as_uint(((c[0] + c[1]) + (c[2] + c[3])) + ((c[4] + c[5]) + (c[6] + c[7]))), tag);
                if (tid == 256) TSTAMP(40);
            }
            float s0 = 0.f, v0 = 0.f;
#pragma unroll
            for (int j = 0; j < 16; j++) s0 += bf_lo(w[j]) + bf_hi(w[j]);
#pragma unroll
            for (int d = 1; d < 16; d <<= 1) s0 += __shfl_xor_sync(0xffffffffu, s0, d);
            const float mean = s0 * (1.0f / DM);
#pragma unroll
            for (int j = 0; j < 16; j++) { const float a = bf_lo(w[j]) - mean, b = bf_hi(w[j]) - mean; v0 += fmaf(a, a, b * b); }
#pragma unroll
            for (int d = 1; d < 16; d <<= 1) v0 += __shfl_xor_sync(0xffffffffu, v0, d);
            if ((lane & 15) == 0) st_tagged(reinterpret_cast<unsigned long long*>(g_rs) + row, pack_bf16(mean, sqrtf(bf_round(bf_round(v0 * (1.0f / DM)) + 1e-5f))), tag);
            if (tid == 256) TSTAMP(45);
        }

        uint32_t q[4], qn[6];
        {
            float acc[64];
            const int rowblk = mblk * 2 + half, tile16 = rowblk * 4 + wq;
            const bool rel = wq < 2 && lane == 0, rel2 = wq == 2 && lane == 0;
            uint32_t empty;
            asm("mapa.shared::cluster.u32 %0, %1, %2;" : "=r"(empty) : "r"(bars + 8 * B_EMPTY), "r"(wq & 1));
#pragma unroll 1
            for (int t = pair; t < 5; t += 2) {
                uint32_t po = t == 4 ? POS_LAST : POS_STD, full = bars + 8 * (B_FULL + 8 * t), slot = (0x24130u >> (4 * t)) & 7, prev = 0;
                uint64_t da = mkdesc(half * 8192, 16, 1024, 1), db = mkdesc(OFF_RING, 8192, 1024, 1) + slot * 1024;
                if (tid == 0 && t == 0) TSTAMP(30);
                mbar_wait(full, 0);
                if (t > 0) mbar_wait(bars + 8 * (B_ORD + t - 1), 0);
#pragma unroll 1
                for (int j = 0; j < 8; j++) {
                    wg_fence();
#pragma unroll
                    for (int k = 0; k < 4; k++) wgmma_ss_n128(acc, da + k * 2, db + k * 128, (j | k) != 0);
                    wg_commit();
                    const uint32_t rel_a = empty + prev * 8, rel_b = bars + 8 * (j == 3 ? B_AFREE0 : B_AFREE + (j >> 1) - 1);
                    const bool do_a = j > 0 && rel, do_b = (po & 8) && rel2;
                    prev = slot; slot = slot == NRING - 1 ? 0 : slot + 1; po >>= 4; full += 8;
                    da = mkdesc(half * 8192, 16, 1024, 1) + (po & 7) * 1024; db = mkdesc(OFF_RING, 8192, 1024, 1) + slot * 1024;
                    if (j < 7) mbar_wait(full, 0); else if (rel2) mbar_arrive(bars + 8 * (B_ORD + t));
                    wg_wait<1>();
                    if (do_a) mbar_arrive_remote(rel_a);
                    if (do_b) mbar_arrive(rel_b);
                }
                if (t >= 3) {
                    mbar_wait(bars + 8 * B_QKV, 0);
                    const uint4* pq = g_q + (head * 128 + (qb * 8 + wg) * 4 + wq) * 32 + lane;
                    const uint4 v = __ldcg(pq), u = __ldcg(pq + 512);
                    qn[0] = v.x; qn[1] = v.y; qn[2] = v.z; qn[3] = v.w; q[0] = u.x; q[1] = u.y; q[2] = u.z; q[3] = u.w;
                }
                wg_wait<0>();
                if (rel) mbar_arrive_remote(empty + prev * 8);
                if (t >= 3 && rel2) mbar_arrive(bars + 8 * (t == 4 ? B_AFREE + 3 : B_AFREE0));
                pin<64>(acc);
                if (wq == 0 && half == 0 && lane == 0) TSTAMP(2 + 2 * t);
                mbar_wait(bars + 8 * (B_STATS + t), 0);
                uint32_t rs0, rs1;
                asm volatile("ld.shared.b32 %0, [%1];" : "=r"(rs0) : "r"(sb + OFF_RS + (half * 64 + wq * 16 + g) * 4));
                asm volatile("ld.shared.b32 %0, [%1];" : "=r"(rs1) : "r"(sb + OFF_RS + (half * 64 + wq * 16 + g + 8) * 4));
                const float m0 = bf_lo(rs0), m1 = bf_lo(rs1);
                float d0 = bf_hi(rs0), d1 = bf_hi(rs1);
#pragma unroll
                for (int j = 0; j < 16; j++) {
                    float c0, c1;
                    asm volatile("ld.shared.v2.f32 {%0,%1}, [%2];" : "=f"(c0), "=f"(c1) : "r"(sb + OFF_CS + (t * 128 + j * 8 + t4 * 2) * 4));
                    acc[4 * j] = fmaf(-m0, c0, acc[4 * j]); acc[4 * j + 1] = fmaf(-m0, c1, acc[4 * j + 1]);
                    acc[4 * j + 2] = fmaf(-m1, c0, acc[4 * j + 2]); acc[4 * j + 3] = fmaf(-m1, c1, acc[4 * j + 3]);
                }
                float r0 = __frcp_rn(d0), r1 = __frcp_rn(d1);
                if (t < nq) {
                    const int qt = qt0 + t, h0 = (qt & 3) * 8;
                    if (qt < 4) {
                        r0 *= 0.25f * 1.4426950408889634f * M71; r1 *= 0.25f * 1.4426950408889634f * M71;
                    } else if (qt < 8) {
                        r0 *= ((FIXED_MASK >> (2 * wq)) & 1) ? M71 : P71; r1 *= ((FIXED_MASK >> (2 * wq + 1)) & 1) ? M71 : P71;
                    }
                    uint32_t* p; int s8, sh;
                    if (qt < 8) { p = reinterpret_cast<uint32_t*>(g_k + h0 * 4096) + tile16 * 128 + lane; s8 = 64; sh = 32; }
                    else        { p = reinterpret_cast<uint32_t*>(g_v + h0 * 4096) + tile16 * 64 + lane;  s8 = 32; sh = 8192; }
#pragma unroll
                    for (int hh = 0; hh < 8; hh++) {
                        const float* a = acc + hh * 8;
                        const uint32_t e0 = pack_bf16(a[0] * r0, a[1] * r0), e1 = pack_bf16(a[2] * r1, a[3] * r1);
                        const uint32_t e2 = pack_bf16(a[4] * r0, a[5] * r0), e3 = pack_bf16(a[6] * r1, a[7] * r1);
                        if (qt < 4) g_q[((h0 + hh) * 128 + tile16) * 32 + lane] = make_uint4(e0, e1, e2, e3);
                        else { uint32_t* pp = p + hh * 16384; pp[0] = e0; pp[s8] = e1; pp[sh] = e2; pp[sh + s8] = e3; }
                    }
                } else {
                    uint32_t* p = reinterpret_cast<uint32_t*>(g_h + (rowblk * 28 + gu0 + t) * 512) + wq * 512 + lane;
                    r0 *= -1.4426950408889634f; r1 *= -1.4426950408889634f; d0 *= d0; d1 *= d1;
#pragma unroll
                    for (int j = 0; j < 8; j++) {
                        const float* a = acc + j * 4; const float* b = a + 32;
                        p[j * 32] = pack_bf16(a[0] * b[0] * rcpf(fmaf(ex2f(a[0] * r0), d0, d0)), a[1] * b[1] * rcpf(fmaf(ex2f(a[1] * r0), d0, d0)));
                        p[256 + j * 32] = pack_bf16(a[2] * b[2] * rcpf(fmaf(ex2f(a[2] * r1), d1, d1)), a[3] * b[3] * rcpf(fmaf(ex2f(a[3] * r1), d1, d1)));
                    }
                }
                __syncwarp();
                if (elect_one()) mbar_arrive(bars + 8 * (B_TILE + t));
                if (wq == 0 && half == 0 && lane == 0) TSTAMP(3 + 2 * t);
            }
        }
        const uint64_t db2 = mkdesc(OFF_B2, 128, 256, 0);
        float s[32];
        auto ref_point = [&](int ntile, uint32_t& b0, uint32_t& b1) {
            float m0 = -INFINITY, m1 = -INFINITY, f0 = -INFINITY, f1 = -INFINITY;
#pragma unroll 1
            for (int t = 0; t < ntile; t++) {
                wg_fence();
                wgmma_rs_n64_zero(s, q, mkdesc(k_tile_addr(0, t), 128, 256, 0));
                wg_commit();
                wg_wait<0>();
                pin<32>(s);
#pragma unroll
                for (int i = 0; i < 8; i++) {
                    if ((FIXED_MASK >> i) & 1) { f0 = fmaxf(f0, fmaxf(s[4 * i], s[4 * i + 1])); f1 = fmaxf(f1, fmaxf(s[4 * i + 2], s[4 * i + 3])); }
                    else                       { m0 = fmaxf(m0, fmaxf(s[4 * i], s[4 * i + 1])); m1 = fmaxf(m1, fmaxf(s[4 * i + 2], s[4 * i + 3])); }
                }
            }
            m0 = fmaxf(m0, f0 * P71 * P71); m1 = fmaxf(m1, f1 * P71 * P71);
            m0 = fmaxf(m0, __shfl_xor_sync(0xffffffffu, m0, 1)); m1 = fmaxf(m1, __shfl_xor_sync(0xffffffffu, m1, 1));
            m0 = fmaxf(m0, __shfl_xor_sync(0xffffffffu, m0, 2)); m1 = fmaxf(m1, __shfl_xor_sync(0xffffffffu, m1, 2));
#pragma unroll
            for (int r = 0; r < 2; r++) {
                const float m = -rintf(r ? m1 : m0), mh = bf_round(m), mm = bf_round(m - mh), ml = m - mh - mm;
                const float lo = t4 == 0 ? mh : t4 == 1 ? ml : t4 == 2 ? 1.f : 0.f, hi = t4 == 0 ? mm : t4 == 1 ? 1.f : 0.f;
                (r ? b1 : b0) = pack_bf16(lo * M71, hi * M71);
            }
        };
        uint32_t q2[4];
        int redo = 1;
        mbar_wait(bars + 8 * B_KV, 0);
#pragma unroll 1
        for (int round = -1; round < 2;) {
            if (redo) ref_point(redo, q2[0], q2[1]);
            if (round < 0) {
#pragma unroll
                for (int i = 0; i < 4; i++) { const uint32_t tq = q[i]; q[i] = qn[i]; qn[i] = tq; }
                qn[4] = q2[0]; qn[5] = q2[1];
                q2[2] = __shfl_sync(0xffffffffu, q2[0], 3); q2[3] = __shfl_sync(0xffffffffu, q2[1], 3);
                round = 0;
                continue;
            }
            float o[12]; uint32_t p[16];
#pragma unroll
            for (int i = 0; i < 12; i++) o[i] = 0.f;
            pin<12>(o); pin<4>(q2);
            if (wq == 0 && half == 0 && lane == 0) TSTAMP(12 + 4 * round + pair);
            uint64_t dk0 = mkdesc(4096, 128, 256, 0), dk1 = mkdesc(98304, 128, 256, 0), dv = mkdesc(0, 128, 65536, 0);
#pragma unroll 1
            for (int c = 0; c < 8; c++, dk0 += 512, dk1 += 256, dv += 512 - (256ull << 32)) {
                if (round == 0) mbar_wait(bars + 8 * (B_KV + c), 0);
#pragma unroll
                for (int t = 0; t < 4; t++) {
                    wg_fence();
                    wgmma_rs_n64_zero(s, q, (t & 2 ? dk1 : dk0) + (t & 1) * 128);
                    wgmma_rs_n64_acc(s, q2, db2);
                    wg_commit();
                    wg_wait<0>();
                    pin<32>(s); pin<16>(p);
#pragma unroll
                    for (int i = 0; i < 16; i++) {
                        if ((FIXED_MASK >> (i >> 1)) & 1) p[i] = exp2_fixed(s[2 * i], s[2 * i + 1], half2);
                        else                              p[i] = pack_bf16(ex2f(s[2 * i]), ex2f(s[2 * i + 1]));
                    }
                    wg_fence();
#pragma unroll
                    for (int k = 0; k < 4; k++) wgmma_rs_n24_acc(o, p + 4 * k, dv + (t * 4 + k) * 16);
                    wg_commit();
                }
            }
            wg_wait<0>();
            pin<12>(o);
            if (redo != 32) {
                float chk = (o[8] + o[10]) * 256.f;
#pragma unroll
                for (int i = 0; i < 8; i++) chk += fabsf(o[i]);
                uint32_t bad;
                asm volatile("{\n.reg .pred p, q;\nsetp.geu.f32 q, %1, 0f7F800000;\nbar.red.or.pred p, %2, 128, q;\nselp.u32 %0, 1, 0, p;\n}" : "=r"(bad) : "f"(chk), "r"(1 + wg) : "memory");
                if (__any_sync(0xffffffffu, bad)) { redo = 32; continue; }
            }
            const int rowblk = qb * 8 + round * 4 + wg;
            const float r0 = rcpf(o[8]), r1 = rcpf(o[10]);
            uint32_t* po = reinterpret_cast<uint32_t*>(g_o + (rowblk * 8 + (head >> 2)) * 512) + wq * 512 + (head & 3) * 64 + lane;
            po[0] = pack_bf16(o[0] * r0, o[1] * r0); po[256] = pack_bf16(o[2] * r1, o[3] * r1);
            po[32] = pack_bf16(o[4] * r0, o[5] * r0); po[288] = pack_bf16(o[6] * r1, o[7] * r1);
            if (round == 0) {
                __syncwarp();
                if (elect_one()) mbar_arrive(bars + 8 * (B_OW + pair));
            } else {
                bar_sync(1 + wg, 128);
                if (wq == 0 && elect_one()) { mbar_arrive(bars + 8 * B_DONE); signal_cnt(C_O + rowblk); }
            }
#pragma unroll
            for (int i = 0; i < 4; i++) q[i] = qn[i];
            q2[0] = qn[4]; q2[1] = qn[5];
            redo = 0;
            if (wq == 0 && half == 0 && lane == 0) TSTAMP(14 + 4 * round + pair);
            round++;
        }
    } else {
        uint32_t tag;
        if (wq == 0) {
            asm volatile("barrier.cluster.wait.aligned;" ::: "memory");
            if (tid == 512) TSTAMP(27);
            uint32_t slot = 2, ph = 1;
#pragma unroll 1
            for (int n = 2; n < 40; n++) {
                const int t = n >> 3, j = n & 7;
                const int kc = (n < 32 ? j : (POS_LAST >> (4 * j)) & 7) * 64;
                const CUtensorMap* m = t < nq ? &mqkv : rank ? &mw3 : &mw1;
                const int col = t < nq ? (qt0 + t) * 128 + rank * 64 : (gu0 + t) * 64;
                const uint32_t dst = ring + slot * 16384 + rank * 8192, fb = bars + 8 * (B_FULL + n);
                if (n < 8 && elect_one()) tma2d(sb + n * 16384, &mx, kc, mblk * 128, fb);
                mbar_wait(bars + 8 * (B_EMPTY + slot), ph);
                if (elect_one()) { TS2(0, n); tma2d_mc(dst, m, col, kc, fb); }
                if (++slot == NRING) { slot = 0; ph ^= 1; }
            }
            tag = ld_epoch() + 1;
        } else if (wq == 1) {
            tag = ld_epoch() + 1;
            mbar_wait(bars + 8 * (B_FULL + 6), 0);
#pragma unroll 1
            for (int t = 0; t < 5; t++) {
                float a[4];
                uint32_t r[4];
#pragma unroll 1
                for (int n = 0; n < 2000000; n++) {
                    uint32_t stale = ld_tagged2(g_rs + mblk * 64 + lane * 2, tag, r[0], r[1]) | ld_tagged2(g_rs + mblk * 64 + lane * 2 + 1, tag, r[2], r[3]);
                    a[0] = a[1] = a[2] = a[3] = 0.f;
#pragma unroll
                    for (int i = 0; i < 16; i++) {
                        uint32_t u, v;
                        stale |= ld_tagged2(g_cs + (grp * 5 + t) * 512 + i * 32 + lane, tag, u, v);
                        a[(i & 1) * 2] += __uint_as_float(u); a[(i & 1) * 2 + 1] += __uint_as_float(v);
                    }
                    if (__all_sync(0xffffffffu, stale == 0)) break;
                    if (t) __nanosleep(400);
                }
                asm volatile("st.shared.v2.f32 [%0], {%1,%2};" :: "r"(sb + OFF_CS + t * 512 + lane * 8), "f"(a[0]), "f"(a[1]) : "memory");
                asm volatile("st.shared.v2.f32 [%0], {%1,%2};" :: "r"(sb + OFF_CS + t * 512 + 256 + lane * 8), "f"(a[2]), "f"(a[3]) : "memory");
                if (t == 0) asm volatile("st.shared.v4.b32 [%0], {%1,%2,%3,%4};" :: "r"(sb + OFF_RS + lane * 16), "r"(r[0]), "r"(r[1]), "r"(r[2]), "r"(r[3]) : "memory");
                __syncwarp();
                if (elect_one()) { mbar_arrive(bars + 8 * (B_STATS + t)); TSTAMP(32 + t); }
            }
        } else {
            tag = ld_epoch() + 1;
            mbar_wait(bars + 8 * (B_FULL + wq - 1), 0);
#pragma unroll 1
            for (int t = wq - 1; t < 5; t += 2) {
                const __nv_bfloat16* src; int ld;
                if (t < nq) { src = wqkv + (qt0 + t) * 128 + rank * 64; ld = 3 * DM; }
                else        { src = (rank ? w3 : w1) + (gu0 + t) * 64; ld = FF; }
                src += (size_t)(rot * 64 + (lane >> 3)) * ld + (lane & 7) * 8;
                uint4 v[16];
                const uint32_t* w = reinterpret_cast<const uint32_t*>(v);
#pragma unroll
                for (int j = 0; j < 16; j++) v[j] = __ldg(reinterpret_cast<const uint4*>(src + (size_t)j * 4 * ld));
                float c[8];
#pragma unroll
                for (int e = 0; e < 4; e++) {
                    float a = 0.f, b = 0.f;
#pragma unroll
                    for (int j = 0; j < 16; j++) { a += bf_lo(w[4 * j + e]); b += bf_hi(w[4 * j + e]); }
                    c[2 * e] = a; c[2 * e + 1] = b;
                }
#pragma unroll
                for (int n = 4; n > 1; n >>= 1) {
                    const bool up = lane & (4 * n);
#pragma unroll
                    for (int e = 0; e < n; e++) c[e] = (up ? c[e + n] : c[e]) + __shfl_xor_sync(0xffffffffu, up ? c[e] : c[e + n], 4 * n);
                }
                unsigned long long* dst = reinterpret_cast<unsigned long long*>(g_cs) + ((grp * 5 + t) * 8 + rot) * 128 + rank * 64 + (lane & 7) * 8 + (lane >> 3) * 2;
                st_tagged(dst, __float_as_uint(c[0]), tag); st_tagged(dst + 1, __float_as_uint(c[1]), tag);
                if (lane == 0) TSTAMP(40 + t);
            }
        }
        if (wq == 3) {
#pragma unroll 1
            for (int i = lane; i < 256; i += 32) asm volatile("st.shared.v4.b32 [%0], {%1,%1,%1,%1};" :: "r"(sb + OFF_ONES + i * 16), "r"(0x3F803F80u) : "memory");
#pragma unroll 1
            for (int i = lane; i < 128; i += 32) {
                const bool fx = (FIXED_MASK >> (i >> 4)) & 1;
                uint32_t a = fx ? pack_bf16(M71, M71) : pack_bf16(P71, P71);
                uint32_t b = fx ? pack_bf16(M71, 47.0f * M71) : pack_bf16(P71, -79.5f * P71);
                uint32_t c = fx ? 0u : pack_bf16(0.08214f * P71, 0.f);
                if (i & 8) a = b = c = 0;
                asm volatile("st.shared.v4.b32 [%0], {%1,%2,%3,%4};" :: "r"(sb + OFF_B2 + i * 16), "r"(a), "r"(b), "r"(c), "r"(0) : "memory");
            }
            fence_async_smem();
            __syncwarp();
            if (elect_one()) mbar_arrive(bars + 8 * B_QKV);
        } else if (wq == 1) {
#pragma unroll 1
            for (int i = 0; i < 3; i++) wait_cnt(C_QKV + i * 4 + (head >> 3), 16 * tag, 100);
            fence_async_all();
            if (elect_one()) { mbar_arrive(bars + 8 * B_QKV); TSTAMP(29); }
            const uint8_t* gk = reinterpret_cast<const uint8_t*>(g_k + head * 4096);
            const uint8_t* gv = reinterpret_cast<const uint8_t*>(g_v + head * 4096);
#pragma unroll 1
            for (int c = 0; c < 8; c++) {
                if (!(c & 1)) mbar_wait(bars + 8 * (c ? B_AFREE + (c >> 1) : B_AFREE0), 0);
                if (elect_one()) {
                    const uint32_t b = bars + 8 * (B_KV + c);
                    mbar_expect(b, 16384);
                    bulk_load(sb + (2 * c + 1) * 4096, gk + c * 8192, 4096, b);
                    bulk_load(sb + 2 * c * 4096, gv + c * 4096, 4096, b);
                    bulk_load(sb + 65536 + c * 4096, gv + 32768 + c * 4096, 4096, b);
                    bulk_load(sb + 98304 + c * 4096, gk + c * 8192 + 4096, 4096, b);
                }
            }
        } else if (wq == 2) {
#pragma unroll 1
            for (int t = 0; t < 5; t++) {
                mbar_wait(bars + 8 * (B_TILE + t), 0);
                if (elect_one()) signal_cnt(t < nq ? C_QKV + qt0 + t : C_H + mblk);
            }
        }
        pin<1>(&tag);
        bar_sync(5, 128);
        if (tid == 639) g_epoch[blockIdx.x] = tag;
        const int cb = blockIdx.x & 7, pr = blockIdx.x >> 3;
        const int rb0 = (pr >> 2) * 8 + (pr & 3);
        uint32_t gate[2][16];
        {
            float dn[64];
            auto load_stage = [&](int kb, int st) {
                const uint32_t b = bars + 8 * (B_RING + st), dst = ring + st * 24576;
                mbar_expect(b, 24576);
                bulk_load(dst, g_h + (rb0 * 28 + kb) * 512, 8192, b);
                bulk_load(dst + 8192, g_h + ((rb0 + 4) * 28 + kb) * 512, 8192, b);
                tma2d(dst + 16384, &mw2, cb * 64, kb * 64, b);
            };
            if (wq == 0) {
                wait_cnt(C_H + (rb0 >> 1), 28 * tag, 200);
                wait_cnt(C_H + (rb0 >> 1) + 2, 28 * tag, 200);
                if (elect_one()) { TSTAMP(20); fence_async_all(); load_stage(0, 0); load_stage(1, 1); }
            }
            int st = 0; uint32_t ph = 0;
#pragma unroll 1
            for (int kb = 0; kb < 28; kb++) {
                mbar_wait(bars + 8 * (B_RING + st), ph);
                const uint64_t da = mkdesc(OFF_RING + st * 24576, 128, 1024, 0), db = mkdesc(OFF_RING + st * 24576 + 16384, 8192, 1024, 1);
                wg_fence();
#pragma unroll
                for (int k = 0; k < 4; k++) { wgmma_ss_n64(dn, da + k * 16, db + k * 128, (kb | k) != 0); wgmma_ss_n64(dn + 32, da + 512 + k * 16, db + k * 128, (kb | k) != 0); }
                wg_commit();
                wg_wait<1>();
                if (wq == 0 && kb < 26 && elect_one()) load_stage(kb + 2, st == 0 ? 2 : st - 1);
                if (++st == 3) { st = 0; ph ^= 1; }
            }
            wg_wait<0>();
            pin<64>(dn);
#pragma unroll
            for (int i = 0; i < 32; i++) gate[i >> 4][i & 15] = pack_bf16(siluf(dn[2 * i]), siluf(dn[2 * i + 1]));
        }
        float acc[32];
        if (tid == 512) TSTAMP(21);
        const uint32_t bar_wo = bars + 8 * B_WO;
        if (wq == 0 && elect_one()) {
            mbar_expect(bar_wo, 65536);
#pragma unroll 1
            for (int i = 0; i < 8; i++) tma2d(ring + i * 8192, &mwo, cb * 64, i * 64, bar_wo);
        }
        if (wq >= 2) {
            mbar_wait(bars + 8 * (B_OW + wq - 2), 0);
            if (elect_one()) {
                signal_cnt(C_O + qb * 8 + 2 * wq - 4);
                asm volatile("red.relaxed.gpu.global.add.u32 [%0], 1;" :: "l"(g_cnt + (C_O + qb * 8 + 2 * wq - 3) * 8) : "memory");
            }
        }
#pragma unroll 1
        for (int tl = 0; tl < 2; tl++) {
            const int rb = rb0 + 4 * tl;
            uint32_t xr[16];
            const uint32_t* px = reinterpret_cast<const uint32_t*>(x + (size_t)(rb * 64 + wq * 16 + g) * DM + cb * 64) + t4;
#pragma unroll
            for (int j = 0; j < 8; j++) { xr[2 * j] = __ldg(px + j * 4); xr[2 * j + 1] = __ldg(px + 8 * DM / 2 + j * 4); }
            if (wq == 0) {
                if (tl == 1) mbar_wait(bars + 8 * B_DONE, 0);
                wait_cnt(C_O + rb, 32 * tag, tl ? 20 : 200);
                if (elect_one()) {
                    fence_async_all();
                    TSTAMP(22 + 2 * tl);
#pragma unroll 1
                    for (int i = 0; i < (tl ? 8 : 2); i++) {
                        mbar_expect(bars + 8 * (B_O + i), 8192);
                        bulk_load((tl ? sb : ring + 65536) + i * 8192, g_o + (rb * 8 + i) * 512, 8192, bars + 8 * (B_O + i));
                    }
                }
            }
            if (tl == 0) mbar_wait(bar_wo, 0);
#pragma unroll 1
            for (int kb = 0; kb < 8; kb++) {
                mbar_wait(bars + 8 * (B_O + kb), tl);
                const uint32_t a = tl == 0 ? OFF_RING + 65536 + (kb & 1) * 8192 : kb * 8192;
                const uint64_t da = mkdesc(a, 128, 1024, 0), db = mkdesc(OFF_RING + kb * 8192, 8192, 1024, 1);
                wg_fence();
#pragma unroll
                for (int k = 0; k < 4; k++) wgmma_ss_n64(acc, da + k * 16, db + k * 128, (kb | k) != 0);
                wg_commit();
                if (tl == 0) {
                    wg_wait<0>();
                    bar_sync(5, 128);
                    if (wq == 0 && kb < 6 && elect_one()) { mbar_expect(bars + 8 * (B_O + kb + 2), 8192); bulk_load(sb + a, g_o + (rb * 8 + kb + 2) * 512, 8192, bars + 8 * (B_O + kb + 2)); }
                }
            }
            wg_wait<0>();
            pin<32>(acc);
            uint32_t* po = reinterpret_cast<uint32_t*>(out + (size_t)(rb * 64 + wq * 16 + g) * DM + cb * 64) + t4;
#pragma unroll
            for (int i = 0; i < 16; i++) {
                const uint32_t r = pack_bf16(fmaf(acc[2 * i], bf_lo(gate[0][i]), bf_lo(xr[i])), fmaf(acc[2 * i + 1], bf_hi(gate[0][i]), bf_hi(xr[i])));
                po[(i & 1) * (8 * DM / 2) + (i >> 1) * 4] = r;
                gate[0][i] = gate[1][i];
            }
            if (tid == 512) TSTAMP(23 + 2 * tl);
        }
    }
}

typedef CUresult (*EncodeFn)(CUtensorMap*, CUtensorMapDataType, cuuint32_t, void*, const cuuint64_t*, const cuuint64_t*, const cuuint32_t*,
                             const cuuint32_t*, CUtensorMapInterleave, CUtensorMapSwizzle, CUtensorMapL2promotion, CUtensorMapFloatOOBfill);

void make_map(EncodeFn fn, CUtensorMap* m, const void* p, int rows, int cols, int box_rows) {
    cuuint64_t dims[2] = {(cuuint64_t)cols, (cuuint64_t)rows};
    cuuint64_t strides[1] = {(cuuint64_t)cols * 2};
    cuuint32_t box[2] = {64, (cuuint32_t)box_rows};
    cuuint32_t es[2] = {1, 1};
    fn(m, CU_TENSOR_MAP_DATA_TYPE_BFLOAT16, 2, const_cast<void*>(p), dims, strides, box, es, CU_TENSOR_MAP_INTERLEAVE_NONE,
       CU_TENSOR_MAP_SWIZZLE_128B, CU_TENSOR_MAP_L2_PROMOTION_L2_128B, CU_TENSOR_MAP_FLOAT_OOB_FILL_NONE);
}

}

extern "C" void kernel_launch(void* const* d_in, const int* in_sizes, int n_in, void* d_out, int out_size) {
    const __nv_bfloat16* x = (const __nv_bfloat16*)d_in[0];
    static EncodeFn fn = nullptr;
    if (!fn) {
        cudaDriverEntryPointQueryResult qr;
        cudaGetDriverEntryPoint("cuTensorMapEncodeTiled", (void**)&fn, cudaEnableDefault, &qr);
        cudaFuncSetAttribute(mega_kernel, cudaFuncAttributeMaxDynamicSharedMemorySize, SMEM_BYTES);
    }
    CUtensorMap mx, mqkv, mw1, mw3, mw2, mwo;
    make_map(fn, &mx, d_in[0], SEQ, DM, 128);
    make_map(fn, &mqkv, d_in[1], DM, 3 * DM, 64);
    make_map(fn, &mwo, d_in[2], DM, DM, 64);
    make_map(fn, &mw1, d_in[4], DM, FF, 64);
    make_map(fn, &mw3, d_in[5], DM, FF, 64);
    make_map(fn, &mw2, d_in[6], FF, DM, 64);
    mega_kernel<<<128, 640, SMEM_BYTES, cudaStreamPerThread>>>(x, (const __nv_bfloat16*)d_in[1], (const __nv_bfloat16*)d_in[4], (const __nv_bfloat16*)d_in[5],
                                                               (__nv_bfloat16*)d_out, mx, mqkv, mw1, mw3, mw2, mwo, 0x3F003F00u);
}
```

```cpp
#include <cuda_runtime.h>
#include <cuda_bf16.h>
#include <cuda.h>
#include <stdint.h>

namespace {

constexpr int SEQ = 2048, DM = 512, FF = 1792;

__device__ uint4 g_q[32 * 128 * 32];
__device__ uint4 g_k[32 * 4096];
__device__ uint4 g_v[32 * 4096];
__device__ uint4 g_h[32 * 28 * 512];
__device__ uint4 g_o[32 * 8 * 512];
__device__ ulonglong2 g_cs[40 * 8 * 64];
__device__ ulonglong2 g_rs[SEQ / 2];
constexpr int C_QKV = 0, C_H = 12, C_O = 28, C_NUM = 60;
__device__ unsigned g_cnt[C_NUM * 8];
__device__ unsigned g_epoch[128];
#define TSTAMP(i)
#define TS2(k, i)

__device__ __forceinline__ uint32_t smem_u32(const void* p) { return (uint32_t)__cvta_generic_to_shared(p); }
__device__ __forceinline__ void mbar_init(uint32_t a, int c) { asm volatile("mbarrier.init.shared::cta.b64 [%0], %1;" :: "r"(a), "r"(c)); }
__device__ __forceinline__ void mbar_expect(uint32_t a, int b) { asm volatile("mbarrier.arrive.expect_tx.shared::cta.b64 _, [%0], %1;" :: "r"(a), "r"(b) : "memory"); }
__device__ __forceinline__ void mbar_arrive(uint32_t a) { asm volatile("mbarrier.arrive.shared::cta.b64 _, [%0];" :: "r"(a) : "memory"); }
__device__ __forceinline__ void mbar_arrive_remote(uint32_t a) { asm volatile("mbarrier.arrive.shared::cluster.b64 _, [%0];" :: "r"(a) : "memory"); }
__device__ __forceinline__ bool mbar_try(uint32_t a, uint32_t ph) {
    uint32_t ok;
    asm volatile("{\n.reg .pred p;\nmbarrier.try_wait.parity.shared::cta.b64 p, [%1], %2;\nselp.u32 %0, 1, 0, p;\n}" : "=r"(ok) : "r"(a), "r"(ph) : "memory");
    return ok;
}
__device__ __forceinline__ void mbar_wait(uint32_t a, uint32_t ph) {
    int n = 1 << 22;
#pragma unroll 1
    do { n = __all_sync(0xffffffffu, mbar_try(a, ph)) ? 0 : n - 1; } while (n > 0);
}
__device__ __forceinline__ bool elect_one() {
    uint32_t p;
    asm volatile("{\n.reg .pred P;\nelect.sync _|P, 0xffffffff;\nselp.u32 %0, 1, 0, P;\n}" : "=r"(p));
    return p;
}
__device__ __forceinline__ void signal_cnt(int c) {
    asm volatile("fence.release.gpu;\nred.relaxed.gpu.global.add.u32 [%0], 1;" :: "l"(g_cnt + c * 8) : "memory");
}
__device__ __forceinline__ void wait_cnt(int c, unsigned target, int ns) {
#pragma unroll 1
    for (int n = 0; n < 2000000; n++) {
        unsigned v;
        asm volatile("ld.relaxed.gpu.global.u32 %0, [%1];" : "=r"(v) : "l"(g_cnt + c * 8) : "memory");
        if (__all_sync(0xffffffffu, (int)(v - target) >= 0)) break;
        __nanosleep(ns);
    }
}
__device__ __forceinline__ uint32_t ld_epoch() {
    uint32_t e;
    asm volatile("ld.relaxed.gpu.global.u32 %0, [%1];" : "=r"(e) : "l"(g_epoch + blockIdx.x) : "memory");
    return e;
}
__device__ __forceinline__ void st_tagged(void* p, uint32_t v, uint32_t tag) {
    asm volatile("st.relaxed.gpu.global.b64 [%0], %1;" :: "l"(p), "l"((unsigned long long)tag << 32 | v) : "memory");
}
__device__ __forceinline__ uint32_t ld_tagged2(const ulonglong2* p, uint32_t tag, uint32_t& a, uint32_t& b) {
    unsigned long long u, v;
    asm volatile("ld.relaxed.gpu.global.v2.b64 {%0,%1}, [%2];" : "=l"(u), "=l"(v) : "l"(p) : "memory");
    a = (uint32_t)u; b = (uint32_t)v;
    return ((uint32_t)(u >> 32) ^ tag) | ((uint32_t)(v >> 32) ^ tag);
}
__device__ __forceinline__ void tma2d(uint32_t dst, const CUtensorMap* m, int c0, int c1, uint32_t bar) {
    asm volatile("cp.async.bulk.tensor.2d.shared::cluster.global.mbarrier::complete_tx::bytes [%0], [%1, {%3, %4}], [%2];"
                 :: "r"(dst), "l"(m), "r"(bar), "r"(c0), "r"(c1) : "memory");
}
__device__ __forceinline__ void tma2d_mc(uint32_t dst, const CUtensorMap* m, int c0, int c1, uint32_t bar) {
    asm volatile("cp.async.bulk.tensor.2d.shared::cluster.global.mbarrier::complete_tx::bytes.multicast::cluster [%0], [%1, {%3, %4}], [%2], %5;"
                 :: "r"(dst), "l"(m), "r"(bar), "r"(c0), "r"(c1), "h"((uint16_t)3) : "memory");
}
__device__ __forceinline__ void bulk_load(uint32_t dst, const void* src, int bytes, uint32_t bar) {
    asm volatile("cp.async.bulk.shared::cluster.global.mbarrier::complete_tx::bytes [%0], [%1], %2, [%3];"
                 :: "r"(dst), "l"(src), "r"(bytes), "r"(bar) : "memory");
}
__device__ __forceinline__ void bar_sync(int id, int n) { asm volatile("bar.sync %0, %1;" :: "r"(id), "r"(n) : "memory"); }
__device__ __forceinline__ void fence_async_smem() { asm volatile("fence.proxy.async.shared::cta;" ::: "memory"); }
__device__ __forceinline__ void fence_async_all() { asm volatile("fence.acquire.gpu;\nfence.proxy.async.global;" ::: "memory"); }
__device__ __forceinline__ void wg_fence() { asm volatile("wgmma.fence.sync.aligned;" ::: "memory"); }
__device__ __forceinline__ void wg_commit() { asm volatile("wgmma.commit_group.sync.aligned;" ::: "memory"); }
template <int N> __device__ __forceinline__ void wg_wait() { asm volatile("wgmma.wait_group.sync.aligned %0;" :: "n"(N) : "memory"); }
template <int N> __device__ __forceinline__ void pin(float* d) {
#pragma unroll
    for (int i = 0; i < N; i++) asm volatile("" : "+f"(d[i]) :: "memory");
}
template <int N> __device__ __forceinline__ void pin(uint32_t* d) {
#pragma unroll
    for (int i = 0; i < N; i++) asm volatile("" : "+r"(d[i]) :: "memory");
}
constexpr uint32_t SMEM_BASE = 1024;
__device__ __forceinline__ uint64_t mkdesc(uint32_t off, uint32_t lbo, uint32_t sbo, uint32_t swz) {
    return (uint64_t)((SMEM_BASE + off) >> 4) | ((uint64_t)(lbo >> 4) << 16) | ((uint64_t)(sbo >> 4) << 32) | ((uint64_t)swz << 62);
}
__device__ __forceinline__ float ex2f(float x) { float y; asm("ex2.approx.ftz.f32 %0, %1;" : "=f"(y) : "f"(x)); return y; }
__device__ __forceinline__ float rcpf(float x) { float y; asm("rcp.approx.ftz.f32 %0, %1;" : "=f"(y) : "f"(x)); return y; }
__device__ __forceinline__ uint32_t pack_bf16(float lo, float hi) { uint32_t r; asm("cvt.rn.bf16x2.f32 %0, %1, %2;" : "=r"(r) : "f"(hi), "f"(lo)); return r; }
__device__ __forceinline__ float bf_lo(uint32_t v) { return __uint_as_float(v << 16); }
__device__ __forceinline__ float bf_hi(uint32_t v) { return __uint_as_float(v & 0xFFFF0000u); }
__device__ __forceinline__ float bf_round(float x) { return __bfloat162float(__float2bfloat16_rn(x)); }
__device__ __forceinline__ float siluf(float g) { return g * rcpf(1.0f + ex2f(g * -1.4426950408889634f)); }

__device__ __forceinline__ void wgmma_ss_n256(float* d, uint64_t da, uint64_t db, int acc) {
    asm volatile("{\n.reg .pred p;\nsetp.ne.b32 p, %130, 0;\nwgmma.mma_async.sync.aligned.m64n256k16.f32.bf16.bf16 {"
        "%0,%1,%2,%3,%4,%5,%6,%7,%8,%9,%10,%11,%12,%13,%14,%15,%16,%17,%18,%19,%20,%21,%22,%23,%24,%25,%26,%27,%28,%29,%30,%31,%32,%33,%34,%35,%36,%37,%38,%39,"
        "%40,%41,%42,%43,%44,%45,%46,%47,%48,%49,%50,%51,%52,%53,%54,%55,%56,%57,%58,%59,%60,%61,%62,%63,%64,%65,%66,%67,%68,%69,%70,%71,%72,%73,%74,%75,%76,"
        "%77,%78,%79,%80,%81,%82,%83,%84,%85,%86,%87,%88,%89,%90,%91,%92,%93,%94,%95,%96,%97,%98,%99,%100,%101,%102,%103,%104,%105,%106,%107,%108,%109,%110,"
        "%111,%112,%113,%114,%115,%116,%117,%118,%119,%120,%121,%122,%123,%124,%125,%126,%127"
        "}, %128, %129, p, 1, 1, 0, 1;\n}\n"
        : "+f"(d[0]),"+f"(d[1]),"+f"(d[2]),"+f"(d[3]),"+f"(d[4]),"+f"(d[5]),"+f"(d[6]),"+f"(d[7]),"+f"(d[8]),"+f"(d[9]),"+f"(d[10]),"+f"(d[11]),"+f"(d[12]),
          "+f"(d[13]),"+f"(d[14]),"+f"(d[15]),"+f"(d[16]),"+f"(d[17]),"+f"(d[18]),"+f"(d[19]),"+f"(d[20]),"+f"(d[21]),"+f"(d[22]),"+f"(d[23]),"+f"(d[24]),
          "+f"(d[25]),"+f"(d[26]),"+f"(d[27]),"+f"(d[28]),"+f"(d[29]),"+f"(d[30]),"+f"(d[31]),"+f"(d[32]),"+f"(d[33]),"+f"(d[34]),"+f"(d[35]),"+f"(d[36]),
          "+f"(d[37]),"+f"(d[38]),"+f"(d[39]),"+f"(d[40]),"+f"(d[41]),"+f"(d[42]),"+f"(d[43]),"+f"(d[44]),"+f"(d[45]),"+f"(d[46]),"+f"(d[47]),"+f"(d[48]),
          "+f"(d[49]),"+f"(d[50]),"+f"(d[51]),"+f"(d[52]),"+f"(d[53]),"+f"(d[54]),"+f"(d[55]),"+f"(d[56]),"+f"(d[57]),"+f"(d[58]),"+f"(d[59]),"+f"(d[60]),
          "+f"(d[61]),"+f"(d[62]),"+f"(d[63]),"+f"(d[64]),"+f"(d[65]),"+f"(d[66]),"+f"(d[67]),"+f"(d[68]),"+f"(d[69]),"+f"(d[70]),"+f"(d[71]),"+f"(d[72]),
          "+f"(d[73]),"+f"(d[74]),"+f"(d[75]),"+f"(d[76]),"+f"(d[77]),"+f"(d[78]),"+f"(d[79]),"+f"(d[80]),"+f"(d[81]),"+f"(d[82]),"+f"(d[83]),"+f"(d[84]),
          "+f"(d[85]),"+f"(d[86]),"+f"(d[87]),"+f"(d[88]),"+f"(d[89]),"+f"(d[90]),"+f"(d[91]),"+f"(d[92]),"+f"(d[93]),"+f"(d[94]),"+f"(d[95]),"+f"(d[96]),
          "+f"(d[97]),"+f"(d[98]),"+f"(d[99]),"+f"(d[100]),"+f"(d[101]),"+f"(d[102]),"+f"(d[103]),"+f"(d[104]),"+f"(d[105]),"+f"(d[106]),"+f"(d[107]),
          "+f"(d[108]),"+f"(d[109]),"+f"(d[110]),"+f"(d[111]),"+f"(d[112]),"+f"(d[113]),"+f"(d[114]),"+f"(d[115]),"+f"(d[116]),"+f"(d[117]),"+f"(d[118]),
          "+f"(d[119]),"+f"(d[120]),"+f"(d[121]),"+f"(d[122]),"+f"(d[123]),"+f"(d[124]),"+f"(d[125]),"+f"(d[126]),"+f"(d[127])
        : "l"(da), "l"(db), "r"(acc));
}
__device__ __forceinline__ void wgmma_ss_n128(float* d, uint64_t da, uint64_t db, int acc) {
    asm volatile("{\n.reg .pred p;\nsetp.ne.b32 p, %66, 0;\nwgmma.mma_async.sync.aligned.m64n128k16.f32.bf16.bf16 {"
        "%0,%1,%2,%3,%4,%5,%6,%7,%8,%9,%10,%11,%12,%13,%14,%15,%16,%17,%18,%19,%20,%21,%22,%23,%24,%25,%26,%27,%28,%29,%30,%31,%32,%33,%34,%35,%36,%37,%38,%39,"
        "%40,%41,%42,%43,%44,%45,%46,%47,%48,%49,%50,%51,%52,%53,%54,%55,%56,%57,%58,%59,%60,%61,%62,%63"
        "}, %64, %65, p, 1, 1, 0, 1;\n}\n"
        : "+f"(d[0]),"+f"(d[1]),"+f"(d[2]),"+f"(d[3]),"+f"(d[4]),"+f"(d[5]),"+f"(d[6]),"+f"(d[7]),"+f"(d[8]),"+f"(d[9]),"+f"(d[10]),"+f"(d[11]),"+f"(d[12]),
          "+f"(d[13]),"+f"(d[14]),"+f"(d[15]),"+f"(d[16]),"+f"(d[17]),"+f"(d[18]),"+f"(d[19]),"+f"(d[20]),"+f"(d[21]),"+f"(d[22]),"+f"(d[23]),"+f"(d[24]),
          "+f"(d[25]),"+f"(d[26]),"+f"(d[27]),"+f"(d[28]),"+f"(d[29]),"+f"(d[30]),"+f"(d[31]),"+f"(d[32]),"+f"(d[33]),"+f"(d[34]),"+f"(d[35]),"+f"(d[36]),
          "+f"(d[37]),"+f"(d[38]),"+f"(d[39]),"+f"(d[40]),"+f"(d[41]),"+f"(d[42]),"+f"(d[43]),"+f"(d[44]),"+f"(d[45]),"+f"(d[46]),"+f"(d[47]),"+f"(d[48]),
          "+f"(d[49]),"+f"(d[50]),"+f"(d[51]),"+f"(d[52]),"+f"(d[53]),"+f"(d[54]),"+f"(d[55]),"+f"(d[56]),"+f"(d[57]),"+f"(d[58]),"+f"(d[59]),"+f"(d[60]),
          "+f"(d[61]),"+f"(d[62]),"+f"(d[63])
        : "l"(da), "l"(db), "r"(acc));
}
__device__ __forceinline__ void wgmma_ss_n64(float* d, uint64_t da, uint64_t db, int acc) {
    asm volatile("{\n.reg .pred p;\nsetp.ne.b32 p, %34, 0;\nwgmma.mma_async.sync.aligned.m64n64k16.f32.bf16.bf16 {"
        "%0,%1,%2,%3,%4,%5,%6,%7,%8,%9,%10,%11,%12,%13,%14,%15,%16,%17,%18,%19,%20,%21,%22,%23,%24,%25,%26,%27,%28,%29,%30,%31"
        "}, %32, %33, p, 1, 1, 0, 1;\n}\n"
        : "+f"(d[0]),"+f"(d[1]),"+f"(d[2]),"+f"(d[3]),"+f"(d[4]),"+f"(d[5]),"+f"(d[6]),"+f"(d[7]),"+f"(d[8]),"+f"(d[9]),"+f"(d[10]),"+f"(d[11]),"+f"(d[12]),
          "+f"(d[13]),"+f"(d[14]),"+f"(d[15]),"+f"(d[16]),"+f"(d[17]),"+f"(d[18]),"+f"(d[19]),"+f"(d[20]),"+f"(d[21]),"+f"(d[22]),"+f"(d[23]),"+f"(d[24]),
          "+f"(d[25]),"+f"(d[26]),"+f"(d[27]),"+f"(d[28]),"+f"(d[29]),"+f"(d[30]),"+f"(d[31])
        : "l"(da), "l"(db), "r"(acc));
}
__device__ __forceinline__ void wgmma_rs_n64_zero(float* d, const uint32_t* a, uint64_t db) {
    asm volatile("wgmma.mma_async.sync.aligned.m64n64k16.f32.bf16.bf16 {"
        "%0,%1,%2,%3,%4,%5,%6,%7,%8,%9,%10,%11,%12,%13,%14,%15,%16,%17,%18,%19,%20,%21,%22,%23,%24,%25,%26,%27,%28,%29,%30,%31"
        "}, {%32,%33,%34,%35}, %36, 0, 1, 1, 0;\n"
        : "=f"(d[0]),"=f"(d[1]),"=f"(d[2]),"=f"(d[3]),"=f"(d[4]),"=f"(d[5]),"=f"(d[6]),"=f"(d[7]),"=f"(d[8]),"=f"(d[9]),"=f"(d[10]),"=f"(d[11]),"=f"(d[12]),
          "=f"(d[13]),"=f"(d[14]),"=f"(d[15]),"=f"(d[16]),"=f"(d[17]),"=f"(d[18]),"=f"(d[19]),"=f"(d[20]),"=f"(d[21]),"=f"(d[22]),"=f"(d[23]),"=f"(d[24]),
          "=f"(d[25]),"=f"(d[26]),"=f"(d[27]),"=f"(d[28]),"=f"(d[29]),"=f"(d[30]),"=f"(d[31])
        : "r"(a[0]), "r"(a[1]), "r"(a[2]), "r"(a[3]), "l"(db));
}
__device__ __forceinline__ void wgmma_rs_n64_acc(float* d, const uint32_t* a, uint64_t db) {
    asm volatile("wgmma.mma_async.sync.aligned.m64n64k16.f32.bf16.bf16 {"
        "%0,%1,%2,%3,%4,%5,%6,%7,%8,%9,%10,%11,%12,%13,%14,%15,%16,%17,%18,%19,%20,%21,%22,%23,%24,%25,%26,%27,%28,%29,%30,%31"
        "}, {%32,%33,%34,%35}, %36, 1, 1, 1, 0;\n"
        : "+f"(d[0]),"+f"(d[1]),"+f"(d[2]),"+f"(d[3]),"+f"(d[4]),"+f"(d[5]),"+f"(d[6]),"+f"(d[7]),"+f"(d[8]),"+f"(d[9]),"+f"(d[10]),"+f"(d[11]),"+f"(d[12]),
          "+f"(d[13]),"+f"(d[14]),"+f"(d[15]),"+f"(d[16]),"+f"(d[17]),"+f"(d[18]),"+f"(d[19]),"+f"(d[20]),"+f"(d[21]),"+f"(d[22]),"+f"(d[23]),"+f"(d[24]),
          "+f"(d[25]),"+f"(d[26]),"+f"(d[27]),"+f"(d[28]),"+f"(d[29]),"+f"(d[30]),"+f"(d[31])
        : "r"(a[0]), "r"(a[1]), "r"(a[2]), "r"(a[3]), "l"(db));
}
__device__ __forceinline__ void wgmma_rs_n24_acc(float* d, const uint32_t* a, uint64_t db) {
    asm volatile("wgmma.mma_async.sync.aligned.m64n24k16.f32.bf16.bf16 {"
        "%0,%1,%2,%3,%4,%5,%6,%7,%8,%9,%10,%11"
        "}, {%12,%13,%14,%15}, %16, 1, 1, 1, 1;\n"
        : "+f"(d[0]),"+f"(d[1]),"+f"(d[2]),"+f"(d[3]),"+f"(d[4]),"+f"(d[5]),"+f"(d[6]),"+f"(d[7]),"+f"(d[8]),"+f"(d[9]),"+f"(d[10]),"+f"(d[11])
        : "r"(a[0]), "r"(a[1]), "r"(a[2]), "r"(a[3]), "l"(db));
}
__device__ __forceinline__ void wgmma_rs_n24_zero(float* d, const uint32_t* a, uint64_t db) {
    asm volatile("wgmma.mma_async.sync.aligned.m64n24k16.f32.bf16.bf16 {"
        "%0,%1,%2,%3,%4,%5,%6,%7,%8,%9,%10,%11"
        "}, {%12,%13,%14,%15}, %16, 0, 1, 1, 1;\n"
        : "=f"(d[0]),"=f"(d[1]),"=f"(d[2]),"=f"(d[3]),"=f"(d[4]),"=f"(d[5]),"=f"(d[6]),"=f"(d[7]),"=f"(d[8]),"=f"(d[9]),"=f"(d[10]),"=f"(d[11])
        : "r"(a[0]), "r"(a[1]), "r"(a[2]), "r"(a[3]), "l"(db));
}

constexpr int OFF_ONES = 131072;
constexpr int OFF_RING = OFF_ONES + 4096;
constexpr int NRING = 5;
constexpr int OFF_B2 = OFF_RING + NRING * 16384;
constexpr int OFF_CS = OFF_B2 + 2048;
constexpr int OFF_RS = OFF_CS + 2560;
constexpr int OFF_BAR = OFF_RS + 1024;
enum { B_FULL = 0, B_STATS = 40, B_KV = 45, B_RING = 53, B_WO = 56, B_O = 57, B_CNT2 = 65,
       B_AFREE = 65, B_ORD = 69, B_QKV = 74, B_CNT4 = 75, B_EMPTY = 75, B_AFREE0 = 80, B_DONE = 81, B_CNT8 = 82, B_TILE = 82, B_OW = 87, B_NUM = 100 };
constexpr int OFF_TS = OFF_BAR + 1024;
constexpr int SMEM_BYTES = OFF_BAR + B_NUM * 8;
constexpr unsigned FIXED_MASK = 0xB5;
constexpr float P71 = 2361183241434822606848.0f, M71 = 4.235164736271502e-22f;

__device__ __forceinline__ uint32_t exp2_fixed(float lo, float hi, uint32_t half2) {
    uint32_t y, g, d;
    asm("cvt.pack.sat.s16.s32 %0, %1, %2;" : "=r"(y) : "r"(__float_as_uint(hi)), "r"(__float_as_uint(lo)));
    asm("lop3.b32 %0, %1, 0x007F007F, %2, 0xEA;" : "=r"(g) : "r"(y), "r"(half2));
    asm("fma.rn.bf16x2 %0, %1, %2, %3;" : "=r"(d) : "r"(y), "r"(g), "r"(y & 0xFF80FF80u));
    return d;
}
__device__ __forceinline__ uint32_t k_tile_addr(uint32_t base, int tile) {
    const int c = tile >> 2;
    return base + ((tile & 2) ? 98304 + c * 4096 : (2 * c + 1) * 4096) + (tile & 1) * 2048;
}
constexpr uint32_t POS_STD = 0x76543210u, POS_LAST = 0xB75A9640u;

__global__ void __cluster_dims__(2, 1, 1) __launch_bounds__(640, 1)
mega_kernel(const __nv_bfloat16* __restrict__ x, const __nv_bfloat16* __restrict__ wqkv, const __nv_bfloat16* __restrict__ w1,
            const __nv_bfloat16* __restrict__ w3, __nv_bfloat16* __restrict__ out,
            const __grid_constant__ CUtensorMap mx, const __grid_constant__ CUtensorMap mqkv, const __grid_constant__ CUtensorMap mw1,
            const __grid_constant__ CUtensorMap mw3, const __grid_constant__ CUtensorMap mw2, const __grid_constant__ CUtensorMap mwo,
            uint32_t half2) {
    extern __shared__ __align__(1024) uint8_t smem_raw[];
    const uint32_t sb = __shfl_sync(0xffffffffu, smem_u32(smem_raw), 0);
    if ((sb & 0xFFFFFF) != SMEM_BASE) __trap();
    const uint32_t bars = sb + OFF_BAR, ring = sb + OFF_RING;
    const int tid = threadIdx.x, lane = tid & 31, g = lane >> 2, t4 = lane & 3;
    const int warp = __shfl_sync(0xffffffffu, tid >> 5, 0), wg = warp >> 2, wq = warp & 3;
    const int rank = blockIdx.x & 1, cl = blockIdx.x >> 1;
    const int grp = cl < 4 ? 4 + cl : cl < 36 ? (cl - 4) >> 3 : 4 + (cl - 36) / 7;
    const int rot = cl < 4 ? 7 : cl < 36 ? (cl - 4) & 7 : (cl - 36) % 7;
    const int mblk = rot * 2 + rank;
    const int nq = grp < 4 ? 2 : 1;
    const int qt0 = grp < 4 ? 2 * grp : 4 + grp;
    const int gu0 = (grp < 4 ? 3 * grp : 4 * grp - 4) - nq;
    const int head = blockIdx.x >> 2, qb = blockIdx.x & 3;

    if (elect_one()) {
#pragma unroll
        for (int i = 0; i < 5; i++) { const int b = warp * 5 + i; mbar_init(bars + 8 * b, b < B_CNT2 ? 1 : b < B_CNT4 ? 2 : b < B_CNT8 ? 4 : 8); }
        if (warp == 0) {
            fence_async_smem();
#pragma unroll
            for (int j = 0; j < 2; j++) {
                tma2d(sb + j * 16384, &mx, j * 64, mblk * 128, bars + 8 * (B_FULL + j));
                tma2d(ring + j * 16384, &mqkv, qt0 * 128, j * 64, bars + 8 * (B_FULL + j));
                tma2d(ring + j * 16384 + 8192, &mqkv, qt0 * 128 + 64, j * 64, bars + 8 * (B_FULL + j));
            }
        }
        if (warp < 8) {
#pragma unroll
            for (int i = 0; i < 5; i++) mbar_expect(bars + 8 * (warp * 5 + i), warp * 5 + i < 8 ? 32768 : 16384);
        }
        if (warp == 16) asm volatile("prefetch.tensormap [%0];" :: "l"(rank ? &mw3 : &mw1) : "memory");
        asm volatile("fence.mbarrier_init.release.cluster;" ::: "memory");
    }
    __syncthreads();
    if (tid == 512) TSTAMP(26);
    asm volatile("barrier.cluster.arrive.relaxed.aligned;" ::: "memory");

    if (wg < 4) {
        const int pair = wg >> 1, half = wg & 1;
        if (pair == 1) {
            const int row = mblk * 128 + grp * 16 + (warp - 8) * 2 + (lane >> 4);
            uint4 v[6];
            const uint32_t* w = reinterpret_cast<const uint32_t*>(v);
#pragma unroll
            for (int j = 0; j < 2; j++) v[4 + j] = __ldg(reinterpret_cast<const uint4*>(wqkv + (size_t)(rot * 64 + (warp - 8) * 8 + j * 4 + (lane >> 3)) * (3 * DM) + qt0 * 128 + rank * 64) + (lane & 7));
#pragma unroll
            for (int j = 0; j < 4; j++) v[j] = __ldg(reinterpret_cast<const uint4*>(x + (size_t)row * DM) + j * 16 + (lane & 15));
            const uint32_t tag = ld_epoch() + 1;
            float c[8];
#pragma unroll
            for (int e = 0; e < 4; e++) { c[2 * e] = bf_lo(w[16 + e]) + bf_lo(w[20 + e]); c[2 * e + 1] = bf_hi(w[16 + e]) + bf_hi(w[20 + e]); }
#pragma unroll
            for (int n = 4; n > 1; n >>= 1) {
                const bool up = lane & (4 * n);
#pragma unroll
                for (int e = 0; e < n; e++) c[e] = (up ? c[e + n] : c[e]) + __shfl_xor_sync(0xffffffffu, up ? c[e] : c[e + n], 4 * n);
            }
            asm volatile("st.shared.v2.f32 [%0], {%1,%2};" :: "r"(sb + OFF_CS + 512 + (warp - 8) * 256 + (lane & 7) * 32 + (lane >> 3) * 8), "f"(c[0]), "f"(c[1]) : "memory");
            float sa[4] = {0.f, 0.f, 0.f, 0.f}, sq[4] = {0.f, 0.f, 0.f, 0.f};
#pragma unroll
            for (int j = 0; j < 16; j++) sa[j & 3] += bf_lo(w[j]) + bf_hi(w[j]);
            float mean = ((sa[0] + sa[1]) + (sa[2] + sa[3])) * (1.0f / 32);
#pragma unroll
            for (int j = 0; j < 16; j++) { const float a = bf_lo(w[j]) - mean, b = bf_hi(w[j]) - mean; sq[j & 1] = fmaf(a, a, sq[j & 1]); sq[2 + (j & 1)] = fmaf(b, b, sq[2 + (j & 1)]); }
            float m2 = (sq[0] + sq[1]) + (sq[2] + sq[3]);
#pragma unroll
            for (int d = 1; d < 16; d <<= 1) {
                const float om = __shfl_xor_sync(0xffffffffu, mean, d), o2 = __shfl_xor_sync(0xffffffffu, m2, d), dm = mean - om;
                m2 = fmaf(dm * dm, 16.0f * d, m2 + o2); mean = 0.5f * (mean + om);
            }
            float sd;
            asm("sqrt.approx.f32 %0, %1;" : "=f"(sd) : "f"(bf_round(bf_round(m2 * (1.0f / DM)) + 1e-5f)));
            if ((lane & 15) == 0) st_tagged(reinterpret_cast<unsigned long long*>(g_rs) + row, pack_bf16(mean, sd), tag);
            if (tid == 256) TSTAMP(45);
            bar_sync(6, 256);
            if (warp < 10) {
#pragma unroll
                for (int e = 0; e < 8; e++) asm volatile("ld.shared.f32 %0, [%1];" : "=f"(c[e]) : "r"(sb + OFF_CS + 512 + e * 256 + (tid & 63) * 4));
                st_tagged(reinterpret_cast<unsigned long long*>(g_cs) + (grp * 40 + rot) * 128 + rank * 64 + (tid & 63),
                          __float_as_uint(((c[0] + c[1]) + (c[2] + c[3])) + ((c[4] + c[5]) + (c[6] + c[7]))), tag);
                if (tid == 256) TSTAMP(40);
            }
        }

        uint32_t q[4], qn[6];
        {
            float acc[64];
            const int rowblk = mblk * 2 + half, tile16 = rowblk * 4 + wq;
            const bool rel = wq < 2 && lane == 0, rel2 = wq == 2 && lane == 0;
            uint32_t empty;
            asm("mapa.shared::cluster.u32 %0, %1, %2;" : "=r"(empty) : "r"(bars + 8 * B_EMPTY), "r"(wq & 1));
#pragma unroll 1
            for (int t = pair; t < 5; t += 2) {
                uint32_t po = t == 4 ? POS_LAST : POS_STD, full = bars + 8 * (B_FULL + 8 * t), slot = (0x24130u >> (4 * t)) & 7, prev = 0;
                uint64_t da = mkdesc(half * 8192, 16, 1024, 1), db = mkdesc(OFF_RING, 8192, 1024, 1) + slot * 1024;
                if (tid == 0 && t == 0) TSTAMP(30);
                mbar_wait(full, 0);
                if (t > 0) mbar_wait(bars + 8 * (B_ORD + t - 1), 0);
#pragma unroll 1
                for (int j = 0; j < 8; j++) {
                    wg_fence();
#pragma unroll
                    for (int k = 0; k < 4; k++) wgmma_ss_n128(acc, da + k * 2, db + k * 128, (j | k) != 0);
                    wg_commit();
                    const uint32_t rel_a = empty + prev * 8, rel_b = bars + 8 * (j == 3 ? B_AFREE0 : B_AFREE + (j >> 1) - 1);
                    const bool do_a = j > 0 && rel, do_b = (po & 8) && rel2;
                    prev = slot; slot = slot == NRING - 1 ? 0 : slot + 1; po >>= 4; full += 8;
                    da = mkdesc(half * 8192, 16, 1024, 1) + (po & 7) * 1024; db = mkdesc(OFF_RING, 8192, 1024, 1) + slot * 1024;
                    if (j < 7) mbar_wait(full, 0); else if (rel2) mbar_arrive(bars + 8 * (B_ORD + t));
                    wg_wait<1>();
                    if (do_a) mbar_arrive_remote(rel_a);
                    if (do_b) mbar_arrive(rel_b);
                }
                if (t >= 3) {
                    mbar_wait(bars + 8 * B_QKV, 0);
                    const uint4* pq = g_q + (head * 128 + (qb * 8 + wg) * 4 + wq) * 32 + lane;
                    const uint4 v = __ldcg(pq), u = __ldcg(pq + 512);
                    qn[0] = v.x; qn[1] = v.y; qn[2] = v.z; qn[3] = v.w; q[0] = u.x; q[1] = u.y; q[2] = u.z; q[3] = u.w;
                }
                wg_wait<0>();
                if (rel) mbar_arrive_remote(empty + prev * 8);
                if (t >= 3 && rel2) mbar_arrive(bars + 8 * (t == 4 ? B_AFREE + 3 : B_AFREE0));
                pin<64>(acc);
                if (wq == 0 && half == 0 && lane == 0) TSTAMP(2 + 2 * t);
                mbar_wait(bars + 8 * (B_STATS + t), 0);
                uint32_t rs0, rs1;
                asm volatile("ld.shared.b32 %0, [%1];" : "=r"(rs0) : "r"(sb + OFF_RS + (half * 64 + wq * 16 + g) * 4));
                asm volatile("ld.shared.b32 %0, [%1];" : "=r"(rs1) : "r"(sb + OFF_RS + (half * 64 + wq * 16 + g + 8) * 4));
                const float m0 = bf_lo(rs0), m1 = bf_lo(rs1);
                float d0 = bf_hi(rs0), d1 = bf_hi(rs1);
#pragma unroll
                for (int j = 0; j < 16; j++) {
                    float c0, c1;
                    asm volatile("ld.shared.v2.f32 {%0,%1}, [%2];" : "=f"(c0), "=f"(c1) : "r"(sb + OFF_CS + (t * 128 + j * 8 + t4 * 2) * 4));
                    acc[4 * j] = fmaf(-m0, c0, acc[4 * j]); acc[4 * j + 1] = fmaf(-m0, c1, acc[4 * j + 1]);
                    acc[4 * j + 2] = fmaf(-m1, c0, acc[4 * j + 2]); acc[4 * j + 3] = fmaf(-m1, c1, acc[4 * j + 3]);
                }
                float r0 = __frcp_rn(d0), r1 = __frcp_rn(d1);
                if (t < nq) {
                    const int qt = qt0 + t, h0 = (qt & 3) * 8;
                    if (qt < 4) {
                        r0 *= 0.25f * 1.4426950408889634f * M71; r1 *= 0.25f * 1.4426950408889634f * M71;
                    } else if (qt < 8) {
                        r0 *= ((FIXED_MASK >> (2 * wq)) & 1) ? M71 : P71; r1 *= ((FIXED_MASK >> (2 * wq + 1)) & 1) ? M71 : P71;
                    }
                    uint32_t* p; int s8, sh;
                    if (qt < 8) { p = reinterpret_cast<uint32_t*>(g_k + h0 * 4096) + tile16 * 128 + lane; s8 = 64; sh = 32; }
                    else        { p = reinterpret_cast<uint32_t*>(g_v + h0 * 4096) + tile16 * 64 + lane;  s8 = 32; sh = 8192; }
#pragma unroll
                    for (int hh = 0; hh < 8; hh++) {
                        const float* a = acc + hh * 8;
                        const uint32_t e0 = pack_bf16(a[0] * r0, a[1] * r0), e1 = pack_bf16(a[2] * r1, a[3] * r1);
                        const uint32_t e2 = pack_bf16(a[4] * r0, a[5] * r0), e3 = pack_bf16(a[6] * r1, a[7] * r1);
                        if (qt < 4) g_q[((h0 + hh) * 128 + tile16) * 32 + lane] = make_uint4(e0, e1, e2, e3);
                        else { uint32_t* pp = p + hh * 16384; pp[0] = e0; pp[s8] = e1; pp[sh] = e2; pp[sh + s8] = e3; }
                    }
                } else {
                    uint32_t* p = reinterpret_cast<uint32_t*>(g_h + (rowblk * 28 + gu0 + t) * 512) + wq * 512 + lane;
                    r0 *= -1.4426950408889634f; r1 *= -1.4426950408889634f; d0 *= d0; d1 *= d1;
#pragma unroll
                    for (int j = 0; j < 8; j++) {
                        const float* a = acc + j * 4; const float* b = a + 32;
                        p[j * 32] = pack_bf16(a[0] * b[0] * rcpf(fmaf(ex2f(a[0] * r0), d0, d0)), a[1] * b[1] * rcpf(fmaf(ex2f(a[1] * r0), d0, d0)));
                        p[256 + j * 32] = pack_bf16(a[2] * b[2] * rcpf(fmaf(ex2f(a[2] * r1), d1, d1)), a[3] * b[3] * rcpf(fmaf(ex2f(a[3] * r1), d1, d1)));
                    }
                }
                __syncwarp();
                if (elect_one()) mbar_arrive(bars + 8 * (B_TILE + t));
                if (wq == 0 && half == 0 && lane == 0) TSTAMP(3 + 2 * t);
            }
        }
        const uint64_t db2 = mkdesc(OFF_B2, 128, 256, 0);
        float s[32];
        auto ref_point = [&](int ntile, uint32_t& b0, uint32_t& b1) {
            float m0 = -INFINITY, m1 = -INFINITY, f0 = -INFINITY, f1 = -INFINITY;
#pragma unroll 1
            for (int t = 0; t < ntile; t++) {
                wg_fence();
                wgmma_rs_n64_zero(s, q, mkdesc(k_tile_addr(0, t), 128, 256, 0));
                wg_commit();
                wg_wait<0>();
                pin<32>(s);
#pragma unroll
                for (int i = 0; i < 8; i++) {
                    if ((FIXED_MASK >> i) & 1) { f0 = fmaxf(f0, fmaxf(s[4 * i], s[4 * i + 1])); f1 = fmaxf(f1, fmaxf(s[4 * i + 2], s[4 * i + 3])); }
                    else                       { m0 = fmaxf(m0, fmaxf(s[4 * i], s[4 * i + 1])); m1 = fmaxf(m1, fmaxf(s[4 * i + 2], s[4 * i + 3])); }
                }
            }
            m0 = fmaxf(m0, f0 * P71 * P71); m1 = fmaxf(m1, f1 * P71 * P71);
            m0 = fmaxf(m0, __shfl_xor_sync(0xffffffffu, m0, 1)); m1 = fmaxf(m1, __shfl_xor_sync(0xffffffffu, m1, 1));
            m0 = fmaxf(m0, __shfl_xor_sync(0xffffffffu, m0, 2)); m1 = fmaxf(m1, __shfl_xor_sync(0xffffffffu, m1, 2));
#pragma unroll
            for (int r = 0; r < 2; r++) {
                const float m = -rintf(r ? m1 : m0), mh = bf_round(m), mm = bf_round(m - mh), ml = m - mh - mm;
                const float lo = t4 == 0 ? mh : t4 == 1 ? ml : t4 == 2 ? 1.f : 0.f, hi = t4 == 0 ? mm : t4 == 1 ? 1.f : 0.f;
                (r ? b1 : b0) = pack_bf16(lo * M71, hi * M71);
            }
        };
        uint32_t q2[4];
        int redo = 1;
        mbar_wait(bars + 8 * B_KV, 0);
#pragma unroll 1
        for (int round = -1; round < 2;) {
            if (redo) ref_point(redo, q2[0], q2[1]);
            if (round < 0) {
#pragma unroll
                for (int i = 0; i < 4; i++) { const uint32_t tq = q[i]; q[i] = qn[i]; qn[i] = tq; }
                qn[4] = q2[0]; qn[5] = q2[1];
                q2[2] = __shfl_sync(0xffffffffu, q2[0], 3); q2[3] = __shfl_sync(0xffffffffu, q2[1], 3);
                round = 0;
                continue;
            }
            float o[12]; uint32_t p[16];
#pragma unroll
            for (int i = 0; i < 12; i++) o[i] = 0.f;
            pin<12>(o); pin<4>(q2);
            if (wq == 0 && half == 0 && lane == 0) TSTAMP(12 + 4 * round + pair);
            uint64_t dk0 = mkdesc(4096, 128, 256, 0), dk1 = mkdesc(98304, 128, 256, 0), dv = mkdesc(0, 128, 65536, 0);
#pragma unroll 1
            for (int c = 0; c < 8; c++, dk0 += 512, dk1 += 256, dv += 512 - (256ull << 32)) {
                if (round == 0) mbar_wait(bars + 8 * (B_KV + c), 0);
#pragma unroll
                for (int t = 0; t < 4; t++) {
                    wg_fence();
                    wgmma_rs_n64_zero(s, q, (t & 2 ? dk1 : dk0) + (t & 1) * 128);
                    wgmma_rs_n64_acc(s, q2, db2);
                    wg_commit();
                    wg_wait<0>();
                    pin<32>(s); pin<16>(p);
#pragma unroll
                    for (int i = 0; i < 16; i++) {
                        if ((FIXED_MASK >> (i >> 1)) & 1) p[i] = exp2_fixed(s[2 * i], s[2 * i + 1], half2);
                        else                              p[i] = pack_bf16(ex2f(s[2 * i]), ex2f(s[2 * i + 1]));
                    }
                    wg_fence();
#pragma unroll
                    for (int k = 0; k < 4; k++) wgmma_rs_n24_acc(o, p + 4 * k, dv + (t * 4 + k) * 16);
                    wg_commit();
                }
            }
            wg_wait<0>();
            pin<12>(o);
            if (redo != 32) {
                float chk = (o[8] + o[10]) * 256.f;
#pragma unroll
                for (int i = 0; i < 8; i++) chk += fabsf(o[i]);
                uint32_t bad;
                asm volatile("{\n.reg .pred p, q;\nsetp.geu.f32 q, %1, 0f7F800000;\nbar.red.or.pred p, %2, 128, q;\nselp.u32 %0, 1, 0, p;\n}" : "=r"(bad) : "f"(chk), "r"(1 + wg) : "memory");
                if (__any_sync(0xffffffffu, bad)) { redo = 32; continue; }
            }
            const int rowblk = qb * 8 + round * 4 + wg;
            const float r0 = rcpf(o[8]), r1 = rcpf(o[10]);
            uint32_t* po = reinterpret_cast<uint32_t*>(g_o + (rowblk * 8 + (head >> 2)) * 512) + wq * 512 + (head & 3) * 64 + lane;
            po[0] = pack_bf16(o[0] * r0, o[1] * r0); po[256] = pack_bf16(o[2] * r1, o[3] * r1);
            po[32] = pack_bf16(o[4] * r0, o[5] * r0); po[288] = pack_bf16(o[6] * r1, o[7] * r1);
            if (round == 0) {
                __syncwarp();
                if (elect_one()) mbar_arrive(bars + 8 * (B_OW + pair));
            } else {
                bar_sync(1 + wg, 128);
                if (wq == 0 && elect_one()) { mbar_arrive(bars + 8 * B_DONE); signal_cnt(C_O + rowblk); }
            }
#pragma unroll
            for (int i = 0; i < 4; i++) q[i] = qn[i];
            q2[0] = qn[4]; q2[1] = qn[5];
            redo = 0;
            if (wq == 0 && half == 0 && lane == 0) TSTAMP(14 + 4 * round + pair);
            round++;
        }
    } else {
        uint32_t tag;
        if (wq == 0) {
            asm volatile("barrier.cluster.wait.aligned;" ::: "memory");
            if (tid == 512) TSTAMP(27);
            uint32_t slot = 2, ph = 1;
#pragma unroll 1
            for (int n = 2; n < 40; n++) {
                const int t = n >> 3, j = n & 7;
                const int kc = (n < 32 ? j : (POS_LAST >> (4 * j)) & 7) * 64;
                const CUtensorMap* m = t < nq ? &mqkv : rank ? &mw3 : &mw1;
                const int col = t < nq ? (qt0 + t) * 128 + rank * 64 : (gu0 + t) * 64;
                const uint32_t dst = ring + slot * 16384 + rank * 8192, fb = bars + 8 * (B_FULL + n);
                if (n < 8 && elect_one()) tma2d(sb + n * 16384, &mx, kc, mblk * 128, fb);
                mbar_wait(bars + 8 * (B_EMPTY + slot), ph);
                if (elect_one()) { TS2(0, n); tma2d_mc(dst, m, col, kc, fb); }
                if (++slot == NRING) { slot = 0; ph ^= 1; }
            }
            tag = ld_epoch() + 1;
        } else if (wq == 1) {
            tag = ld_epoch() + 1;
            mbar_wait(bars + 8 * (B_FULL + 6), 0);
#pragma unroll 1
            for (int t = 0; t < 5; t++) {
                float a[4];
                uint32_t r[4];
#pragma unroll 1
                for (int n = 0; n < 2000000; n++) {
                    uint32_t stale = ld_tagged2(g_rs + mblk * 64 + lane * 2, tag, r[0], r[1]) | ld_tagged2(g_rs + mblk * 64 + lane * 2 + 1, tag, r[2], r[3]);
                    a[0] = a[1] = a[2] = a[3] = 0.f;
#pragma unroll
                    for (int i = 0; i < 16; i++) {
                        uint32_t u, v;
                        stale |= ld_tagged2(g_cs + (grp * 5 + t) * 512 + i * 32 + lane, tag, u, v);
                        a[(i & 1) * 2] += __uint_as_float(u); a[(i & 1) * 2 + 1] += __uint_as_float(v);
                    }
                    if (__all_sync(0xffffffffu, stale == 0)) break;
                    if (t) __nanosleep(400);
                }
                asm volatile("st.shared.v2.f32 [%0], {%1,%2};" :: "r"(sb + OFF_CS + t * 512 + lane * 8), "f"(a[0]), "f"(a[1]) : "memory");
                asm volatile("st.shared.v2.f32 [%0], {%1,%2};" :: "r"(sb + OFF_CS + t * 512 + 256 + lane * 8), "f"(a[2]), "f"(a[3]) : "memory");
                if (t == 0) asm volatile("st.shared.v4.b32 [%0], {%1,%2,%3,%4};" :: "r"(sb + OFF_RS + lane * 16), "r"(r[0]), "r"(r[1]), "r"(r[2]), "r"(r[3]) : "memory");
                __syncwarp();
                if (elect_one()) { mbar_arrive(bars + 8 * (B_STATS + t)); TSTAMP(32 + t); }
            }
        } else {
            tag = ld_epoch() + 1;
            mbar_wait(bars + 8 * (B_FULL + wq - 1), 0);
#pragma unroll 1
            for (int t = wq - 1; t < 5; t += 2) {
                const __nv_bfloat16* src; int ld;
                if (t < nq) { src = wqkv + (qt0 + t) * 128 + rank * 64; ld = 3 * DM; }
                else        { src = (rank ? w3 : w1) + (gu0 + t) * 64; ld = FF; }
                src += (size_t)(rot * 64 + (lane >> 3)) * ld + (lane & 7) * 8;
                uint4 v[16];
                const uint32_t* w = reinterpret_cast<const uint32_t*>(v);
#pragma unroll
                for (int j = 0; j < 16; j++) v[j] = __ldg(reinterpret_cast<const uint4*>(src + (size_t)j * 4 * ld));
                float c[8];
#pragma unroll
                for (int e = 0; e < 4; e++) {
                    float a = 0.f, b = 0.f;
#pragma unroll
                    for (int j = 0; j < 16; j++) { a += bf_lo(w[4 * j + e]); b += bf_hi(w[4 * j + e]); }
                    c[2 * e] = a; c[2 * e + 1] = b;
                }
#pragma unroll
                for (int n = 4; n > 1; n >>= 1) {
                    const bool up = lane & (4 * n);
#pragma unroll
                    for (int e = 0; e < n; e++) c[e] = (up ? c[e + n] : c[e]) + __shfl_xor_sync(0xffffffffu, up ? c[e] : c[e + n], 4 * n);
                }
                unsigned long long* dst = reinterpret_cast<unsigned long long*>(g_cs) + ((grp * 5 + t) * 8 + rot) * 128 + rank * 64 + (lane & 7) * 8 + (lane >> 3) * 2;
                st_tagged(dst, __float_as_uint(c[0]), tag); st_tagged(dst + 1, __float_as_uint(c[1]), tag);
                if (lane == 0) TSTAMP(40 + t);
            }
        }
        if (wq == 3) {
#pragma unroll 1
            for (int i = lane; i < 256; i += 32) asm volatile("st.shared.v4.b32 [%0], {%1,%1,%1,%1};" :: "r"(sb + OFF_ONES + i * 16), "r"(0x3F803F80u) : "memory");
#pragma unroll 1
            for (int i = lane; i < 128; i += 32) {
                const bool fx = (FIXED_MASK >> (i >> 4)) & 1;
                uint32_t a = fx ? pack_bf16(M71, M71) : pack_bf16(P71, P71);
                uint32_t b = fx ? pack_bf16(M71, 47.0f * M71) : pack_bf16(P71, -79.5f * P71);
                uint32_t c = fx ? 0u : pack_bf16(0.08214f * P71, 0.f);
                if (i & 8) a = b = c = 0;
                asm volatile("st.shared.v4.b32 [%0], {%1,%2,%3,%4};" :: "r"(sb + OFF_B2 + i * 16), "r"(a), "r"(b), "r"(c), "r"(0) : "memory");
            }
            fence_async_smem();
            __syncwarp();
            if (elect_one()) mbar_arrive(bars + 8 * B_QKV);
        } else if (wq == 1) {
#pragma unroll 1
            for (int i = 0; i < 3; i++) wait_cnt(C_QKV + i * 4 + (head >> 3), 16 * tag, 100);
            fence_async_all();
            if (elect_one()) { mbar_arrive(bars + 8 * B_QKV); TSTAMP(29); }
            const uint8_t* gk = reinterpret_cast<const uint8_t*>(g_k + head * 4096);
            const uint8_t* gv = reinterpret_cast<const uint8_t*>(g_v + head * 4096);
#pragma unroll 1
            for (int c = 0; c < 8; c++) {
                if (!(c & 1)) mbar_wait(bars + 8 * (c ? B_AFREE + (c >> 1) : B_AFREE0), 0);
                if (elect_one()) {
                    const uint32_t b = bars + 8 * (B_KV + c);
                    mbar_expect(b, 16384);
                    bulk_load(sb + (2 * c + 1) * 4096, gk + c * 8192, 4096, b);
                    bulk_load(sb + 2 * c * 4096, gv + c * 4096, 4096, b);
                    bulk_load(sb + 65536 + c * 4096, gv + 32768 + c * 4096, 4096, b);
                    bulk_load(sb + 98304 + c * 4096, gk + c * 8192 + 4096, 4096, b);
                }
            }
        } else if (wq == 2) {
#pragma unroll 1
            for (int t = 0; t < 5; t++) {
                mbar_wait(bars + 8 * (B_TILE + t), 0);
                if (elect_one()) signal_cnt(t < nq ? C_QKV + qt0 + t : C_H + mblk);
            }
        }
        pin<1>(&tag);
        bar_sync(5, 128);
        if (tid == 639) g_epoch[blockIdx.x] = tag;
        const int cb = blockIdx.x & 7, pr = blockIdx.x >> 3;
        const int rb0 = (pr >> 2) * 8 + (pr & 3);
        uint32_t gate[2][16];
        {
            float dn[64];
            auto load_stage = [&](int kb, int st) {
                const uint32_t b = bars + 8 * (B_RING + st), dst = ring + st * 24576;
                mbar_expect(b, 24576);
                bulk_load(dst, g_h + (rb0 * 28 + kb) * 512, 8192, b);
                bulk_load(dst + 8192, g_h + ((rb0 + 4) * 28 + kb) * 512, 8192, b);
                tma2d(dst + 16384, &mw2, cb * 64, kb * 64, b);
            };
            if (wq == 0) {
                wait_cnt(C_H + (rb0 >> 1), 28 * tag, 200);
                wait_cnt(C_H + (rb0 >> 1) + 2, 28 * tag, 200);
                if (elect_one()) { TSTAMP(20); fence_async_all(); load_stage(0, 0); load_stage(1, 1); }
            }
            int st = 0; uint32_t ph = 0;
#pragma unroll 1
            for (int kb = 0; kb < 28; kb++) {
                mbar_wait(bars + 8 * (B_RING + st), ph);
                const uint64_t da = mkdesc(OFF_RING + st * 24576, 128, 1024, 0), db = mkdesc(OFF_RING + st * 24576 + 16384, 8192, 1024, 1);
                wg_fence();
#pragma unroll
                for (int k = 0; k < 4; k++) { wgmma_ss_n64(dn, da + k * 16, db + k * 128, (kb | k) != 0); wgmma_ss_n64(dn + 32, da + 512 + k * 16, db + k * 128, (kb | k) != 0); }
                wg_commit();
                wg_wait<1>();
                if (wq == 0 && kb < 26 && elect_one()) load_stage(kb + 2, st == 0 ? 2 : st - 1);
                if (++st == 3) { st = 0; ph ^= 1; }
            }
            wg_wait<0>();
            pin<64>(dn);
#pragma unroll
            for (int i = 0; i < 32; i++) gate[i >> 4][i & 15] = pack_bf16(siluf(dn[2 * i]), siluf(dn[2 * i + 1]));
        }
        float acc[32];
        if (tid == 512) TSTAMP(21);
        const uint32_t bar_wo = bars + 8 * B_WO;
        if (wq == 0 && elect_one()) {
            mbar_expect(bar_wo, 65536);
#pragma unroll 1
            for (int i = 0; i < 8; i++) tma2d(ring + i * 8192, &mwo, cb * 64, i * 64, bar_wo);
        }
        if (wq >= 2) {
            mbar_wait(bars + 8 * (B_OW + wq - 2), 0);
            if (elect_one()) {
                signal_cnt(C_O + qb * 8 + 2 * wq - 4);
                asm volatile("red.relaxed.gpu.global.add.u32 [%0], 1;" :: "l"(g_cnt + (C_O + qb * 8 + 2 * wq - 3) * 8) : "memory");
            }
        }
#pragma unroll 1
        for (int tl = 0; tl < 2; tl++) {
            const int rb = rb0 + 4 * tl;
            uint32_t xr[16];
            const uint32_t* px = reinterpret_cast<const uint32_t*>(x + (size_t)(rb * 64 + wq * 16 + g) * DM + cb * 64) + t4;
#pragma unroll
            for (int j = 0; j < 8; j++) { xr[2 * j] = __ldg(px + j * 4); xr[2 * j + 1] = __ldg(px + 8 * DM / 2 + j * 4); }
            if (wq == 0) {
                if (tl == 1) mbar_wait(bars + 8 * B_DONE, 0);
                wait_cnt(C_O + rb, 32 * tag, tl ? 20 : 200);
                if (elect_one()) {
                    fence_async_all();
                    TSTAMP(22 + 2 * tl);
#pragma unroll 1
                    for (int i = 0; i < (tl ? 8 : 2); i++) {
                        mbar_expect(bars + 8 * (B_O + i), 8192);
                        bulk_load((tl ? sb : ring + 65536) + i * 8192, g_o + (rb * 8 + i) * 512, 8192, bars + 8 * (B_O + i));
                    }
                }
            }
            if (tl == 0) mbar_wait(bar_wo, 0);
#pragma unroll 1
            for (int kb = 0; kb < 8; kb++) {
                mbar_wait(bars + 8 * (B_O + kb), tl);
                const uint32_t a = tl == 0 ? OFF_RING + 65536 + (kb & 1) * 8192 : kb * 8192;
                const uint64_t da = mkdesc(a, 128, 1024, 0), db = mkdesc(OFF_RING + kb * 8192, 8192, 1024, 1);
                wg_fence();
#pragma unroll
                for (int k = 0; k < 4; k++) wgmma_ss_n64(acc, da + k * 16, db + k * 128, (kb | k) != 0);
                wg_commit();
                if (tl == 0) {
                    wg_wait<0>();
                    bar_sync(5, 128);
                    if (wq == 0 && kb < 6 && elect_one()) { mbar_expect(bars + 8 * (B_O + kb + 2), 8192); bulk_load(sb + a, g_o + (rb * 8 + kb + 2) * 512, 8192, bars + 8 * (B_O + kb + 2)); }
                }
            }
            wg_wait<0>();
            pin<32>(acc);
            uint32_t* po = reinterpret_cast<uint32_t*>(out + (size_t)(rb * 64 + wq * 16 + g) * DM + cb * 64) + t4;
#pragma unroll
            for (int i = 0; i < 16; i++) {
                const uint32_t r = pack_bf16(fmaf(acc[2 * i], bf_lo(gate[0][i]), bf_lo(xr[i])), fmaf(acc[2 * i + 1], bf_hi(gate[0][i]), bf_hi(xr[i])));
                po[(i & 1) * (8 * DM / 2) + (i >> 1) * 4] = r;
                gate[0][i] = gate[1][i];
            }
            if (tid == 512) TSTAMP(23 + 2 * tl);
        }
    }
}

typedef CUresult (*EncodeFn)(CUtensorMap*, CUtensorMapDataType, cuuint32_t, void*, const cuuint64_t*, const cuuint64_t*, const cuuint32_t*,
                             const cuuint32_t*, CUtensorMapInterleave, CUtensorMapSwizzle, CUtensorMapL2promotion, CUtensorMapFloatOOBfill);

void make_map(EncodeFn fn, CUtensorMap* m, const void* p, int rows, int cols, int box_rows) {
    cuuint64_t dims[2] = {(cuuint64_t)cols, (cuuint64_t)rows};
    cuuint64_t strides[1] = {(cuuint64_t)cols * 2};
    cuuint32_t box[2] = {64, (cuuint32_t)box_rows};
    cuuint32_t es[2] = {1, 1};
    fn(m, CU_TENSOR_MAP_DATA_TYPE_BFLOAT16, 2, const_cast<void*>(p), dims, strides, box, es, CU_TENSOR_MAP_INTERLEAVE_NONE,
       CU_TENSOR_MAP_SWIZZLE_128B, CU_TENSOR_MAP_L2_PROMOTION_L2_128B, CU_TENSOR_MAP_FLOAT_OOB_FILL_NONE);
}

}

extern "C" void kernel_launch(void* const* d_in, const int* in_sizes, int n_in, void* d_out, int out_size) {
    const __nv_bfloat16* x = (const __nv_bfloat16*)d_in[0];
    static EncodeFn fn = nullptr;
    if (!fn) {
        cudaDriverEntryPointQueryResult qr;
        cudaGetDriverEntryPoint("cuTensorMapEncodeTiled", (void**)&fn, cudaEnableDefault, &qr);
        cudaFuncSetAttribute(mega_kernel, cudaFuncAttributeMaxDynamicSharedMemorySize, SMEM_BYTES);
    }
    CUtensorMap mx, mqkv, mw1, mw3, mw2, mwo;
    make_map(fn, &mx, d_in[0], SEQ, DM, 128);
    make_map(fn, &mqkv, d_in[1], DM, 3 * DM, 64);
    make_map(fn, &mwo, d_in[2], DM, DM, 64);
    make_map(fn, &mw1, d_in[4], DM, FF, 64);
    make_map(fn, &mw3, d_in[5], DM, FF, 64);
    make_map(fn, &mw2, d_in[6], FF, DM, 64);
    mega_kernel<<<128, 640, SMEM_BYTES, cudaStreamPerThread>>>(x, (const __nv_bfloat16*)d_in[1], (const __nv_bfloat16*)d_in[4], (const __nv_bfloat16*)d_in[5],
                                                               (__nv_bfloat16*)d_out, mx, mqkv, mw1, mw3, mw2, mwo, 0x3F003F00u);
}
```

```cpp
#include <cuda_runtime.h>
#include <cuda_bf16.h>
#include <cuda.h>
#include <stdint.h>

namespace {

constexpr int SEQ = 2048, DM = 512, FF = 1792;

__device__ uint4 g_q[32 * 128 * 32];
__device__ uint4 g_k[32 * 4096];
__device__ uint4 g_v[32 * 4096];
__device__ uint4 g_h[32 * 28 * 512];
__device__ uint4 g_o[32 * 8 * 512];
__device__ ulonglong2 g_cs[40 * 8 * 64];
__device__ ulonglong2 g_rs[SEQ / 2];
constexpr int C_QKV = 0, C_H = 12, C_O = 28, C_NUM = 60;
__device__ unsigned g_cnt[C_NUM * 8];
__device__ unsigned g_epoch[128];
#define TSTAMP(i)
#define TS2(k, i)

__device__ __forceinline__ uint32_t smem_u32(const void* p) { return (uint32_t)__cvta_generic_to_shared(p); }
__device__ __forceinline__ void mbar_init(uint32_t a, int c) { asm volatile("mbarrier.init.shared::cta.b64 [%0], %1;" :: "r"(a), "r"(c)); }
__device__ __forceinline__ void mbar_expect(uint32_t a, int b) { asm volatile("mbarrier.arrive.expect_tx.shared::cta.b64 _, [%0], %1;" :: "r"(a), "r"(b) : "memory"); }
__device__ __forceinline__ void mbar_arrive(uint32_t a) { asm volatile("mbarrier.arrive.shared::cta.b64 _, [%0];" :: "r"(a) : "memory"); }
__device__ __forceinline__ void mbar_arrive_remote(uint32_t a) { asm volatile("mbarrier.arrive.shared::cluster.b64 _, [%0];" :: "r"(a) : "memory"); }
__device__ __forceinline__ bool mbar_try(uint32_t a, uint32_t ph) {
    uint32_t ok;
    asm volatile("{\n.reg .pred p;\nmbarrier.try_wait.parity.shared::cta.b64 p, [%1], %2;\nselp.u32 %0, 1, 0, p;\n}" : "=r"(ok) : "r"(a), "r"(ph) : "memory");
    return ok;
}
__device__ __forceinline__ void mbar_wait(uint32_t a, uint32_t ph) {
    int n = 1 << 22;
#pragma unroll 1
    do { n = __all_sync(0xffffffffu, mbar_try(a, ph)) ? 0 : n - 1; } while (n > 0);
}
__device__ __forceinline__ bool elect_one() {
    uint32_t p;
    asm volatile("{\n.reg .pred P;\nelect.sync _|P, 0xffffffff;\nselp.u32 %0, 1, 0, P;\n}" : "=r"(p));
    return p;
}
__device__ __forceinline__ void signal_cnt(int c) {
    asm volatile("fence.release.gpu;\nred.relaxed.gpu.global.add.u32 [%0], 1;" :: "l"(g_cnt + c * 8) : "memory");
}
__device__ __forceinline__ void wait_cnt(int c, unsigned target, int ns) {
#pragma unroll 1
    for (int n = 0; n < 2000000; n++) {
        unsigned v;
        asm volatile("ld.relaxed.gpu.global.u32 %0, [%1];" : "=r"(v) : "l"(g_cnt + c * 8) : "memory");
        if (__all_sync(0xffffffffu, (int)(v - target) >= 0)) break;
        __nanosleep(ns);
    }
}
__device__ __forceinline__ uint32_t ld_epoch() {
    uint32_t e;
    asm volatile("ld.relaxed.gpu.global.u32 %0, [%1];" : "=r"(e) : "l"(g_epoch + blockIdx.x) : "memory");
    return e;
}
__device__ __forceinline__ void st_tagged(void* p, uint32_t v, uint32_t tag) {
    asm volatile("st.relaxed.gpu.global.b64 [%0], %1;" :: "l"(p), "l"((unsigned long long)tag << 32 | v) : "memory");
}
__device__ __forceinline__ uint32_t ld_tagged2(const ulonglong2* p, uint32_t tag, uint32_t& a, uint32_t& b) {
    unsigned long long u, v;
    asm volatile("ld.relaxed.gpu.global.v2.b64 {%0,%1}, [%2];" : "=l"(u), "=l"(v) : "l"(p) : "memory");
    a = (uint32_t)u; b = (uint32_t)v;
    return ((uint32_t)(u >> 32) ^ tag) | ((uint32_t)(v >> 32) ^ tag);
}
__device__ __forceinline__ void tma2d(uint32_t dst, const CUtensorMap* m, int c0, int c1, uint32_t bar) {
    asm volatile("cp.async.bulk.tensor.2d.shared::cluster.global.mbarrier::complete_tx::bytes [%0], [%1, {%3, %4}], [%2];"
                 :: "r"(dst), "l"(m), "r"(bar), "r"(c0), "r"(c1) : "memory");
}
__device__ __forceinline__ void tma2d_mc(uint32_t dst, const CUtensorMap* m, int c0, int c1, uint32_t bar) {
    asm volatile("cp.async.bulk.tensor.2d.shared::cluster.global.mbarrier::complete_tx::bytes.multicast::cluster [%0], [%1, {%3, %4}], [%2], %5;"
                 :: "r"(dst), "l"(m), "r"(bar), "r"(c0), "r"(c1), "h"((uint16_t)3) : "memory");
}
__device__ __forceinline__ void bulk_load(uint32_t dst, const void* src, int bytes, uint32_t bar) {
    asm volatile("cp.async.bulk.shared::cluster.global.mbarrier::complete_tx::bytes [%0], [%1], %2, [%3];"
                 :: "r"(dst), "l"(src), "r"(bytes), "r"(bar) : "memory");
}
__device__ __forceinline__ void bar_sync(int id, int n) { asm volatile("bar.sync %0, %1;" :: "r"(id), "r"(n) : "memory"); }
__device__ __forceinline__ void fence_async_smem() { asm volatile("fence.proxy.async.shared::cta;" ::: "memory"); }
__device__ __forceinline__ void fence_async_all() { asm volatile("fence.acquire.gpu;\nfence.proxy.async.global;" ::: "memory"); }
__device__ __forceinline__ void wg_fence() { asm volatile("wgmma.fence.sync.aligned;" ::: "memory"); }
__device__ __forceinline__ void wg_commit() { asm volatile("wgmma.commit_group.sync.aligned;" ::: "memory"); }
template <int N> __device__ __forceinline__ void wg_wait() { asm volatile("wgmma.wait_group.sync.aligned %0;" :: "n"(N) : "memory"); }
template <int N> __device__ __forceinline__ void pin(float* d) {
#pragma unroll
    for (int i = 0; i < N; i++) asm volatile("" : "+f"(d[i]) :: "memory");
}
template <int N> __device__ __forceinline__ void pin(uint32_t* d) {
#pragma unroll
    for (int i = 0; i < N; i++) asm volatile("" : "+r"(d[i]) :: "memory");
}
constexpr uint32_t SMEM_BASE = 1024;
__device__ __forceinline__ uint64_t mkdesc(uint32_t off, uint32_t lbo, uint32_t sbo, uint32_t swz) {
    return (uint64_t)((SMEM_BASE + off) >> 4) | ((uint64_t)(lbo >> 4) << 16) | ((uint64_t)(sbo >> 4) << 32) | ((uint64_t)swz << 62);
}
__device__ __forceinline__ float ex2f(float x) { float y; asm("ex2.approx.ftz.f32 %0, %1;" : "=f"(y) : "f"(x)); return y; }
__device__ __forceinline__ float rcpf(float x) { float y; asm("rcp.approx.ftz.f32 %0, %1;" : "=f"(y) : "f"(x)); return y; }
__device__ __forceinline__ uint32_t pack_bf16(float lo, float hi) { uint32_t r; asm("cvt.rn.bf16x2.f32 %0, %1, %2;" : "=r"(r) : "f"(hi), "f"(lo)); return r; }
__device__ __forceinline__ float bf_lo(uint32_t v) { return __uint_as_float(v << 16); }
__device__ __forceinline__ float bf_hi(uint32_t v) { return __uint_as_float(v & 0xFFFF0000u); }
__device__ __forceinline__ float bf_round(float x) { return __bfloat162float(__float2bfloat16_rn(x)); }
__device__ __forceinline__ float siluf(float g) { return g * rcpf(1.0f + ex2f(g * -1.4426950408889634f)); }

__device__ __forceinline__ void wgmma_ss_n256(float* d, uint64_t da, uint64_t db, int acc) {
    asm volatile("{\n.reg .pred p;\nsetp.ne.b32 p, %130, 0;\nwgmma.mma_async.sync.aligned.m64n256k16.f32.bf16.bf16 {"
        "%0,%1,%2,%3,%4,%5,%6,%7,%8,%9,%10,%11,%12,%13,%14,%15,%16,%17,%18,%19,%20,%21,%22,%23,%24,%25,%26,%27,%28,%29,%30,%31,%32,%33,%34,%35,%36,%37,%38,%39,"
        "%40,%41,%42,%43,%44,%45,%46,%47,%48,%49,%50,%51,%52,%53,%54,%55,%56,%57,%58,%59,%60,%61,%62,%63,%64,%65,%66,%67,%68,%69,%70,%71,%72,%73,%74,%75,%76,"
        "%77,%78,%79,%80,%81,%82,%83,%84,%85,%86,%87,%88,%89,%90,%91,%92,%93,%94,%95,%96,%97,%98,%99,%100,%101,%102,%103,%104,%105,%106,%107,%108,%109,%110,"
        "%111,%112,%113,%114,%115,%116,%117,%118,%119,%120,%121,%122,%123,%124,%125,%126,%127"
        "}, %128, %129, p, 1, 1, 0, 1;\n}\n"
        : "+f"(d[0]),"+f"(d[1]),"+f"(d[2]),"+f"(d[3]),"+f"(d[4]),"+f"(d[5]),"+f"(d[6]),"+f"(d[7]),"+f"(d[8]),"+f"(d[9]),"+f"(d[10]),"+f"(d[11]),"+f"(d[12]),
          "+f"(d[13]),"+f"(d[14]),"+f"(d[15]),"+f"(d[16]),"+f"(d[17]),"+f"(d[18]),"+f"(d[19]),"+f"(d[20]),"+f"(d[21]),"+f"(d[22]),"+f"(d[23]),"+f"(d[24]),
          "+f"(d[25]),"+f"(d[26]),"+f"(d[27]),"+f"(d[28]),"+f"(d[29]),"+f"(d[30]),"+f"(d[31]),"+f"(d[32]),"+f"(d[33]),"+f"(d[34]),"+f"(d[35]),"+f"(d[36]),
          "+f"(d[37]),"+f"(d[38]),"+f"(d[39]),"+f"(d[40]),"+f"(d[41]),"+f"(d[42]),"+f"(d[43]),"+f"(d[44]),"+f"(d[45]),"+f"(d[46]),"+f"(d[47]),"+f"(d[48]),
          "+f"(d[49]),"+f"(d[50]),"+f"(d[51]),"+f"(d[52]),"+f"(d[53]),"+f"(d[54]),"+f"(d[55]),"+f"(d[56]),"+f"(d[57]),"+f"(d[58]),"+f"(d[59]),"+f"(d[60]),
          "+f"(d[61]),"+f"(d[62]),"+f"(d[63]),"+f"(d[64]),"+f"(d[65]),"+f"(d[66]),"+f"(d[67]),"+f"(d[68]),"+f"(d[69]),"+f"(d[70]),"+f"(d[71]),"+f"(d[72]),
          "+f"(d[73]),"+f"(d[74]),"+f"(d[75]),"+f"(d[76]),"+f"(d[77]),"+f"(d[78]),"+f"(d[79]),"+f"(d[80]),"+f"(d[81]),"+f"(d[82]),"+f"(d[83]),"+f"(d[84]),
          "+f"(d[85]),"+f"(d[86]),"+f"(d[87]),"+f"(d[88]),"+f"(d[89]),"+f"(d[90]),"+f"(d[91]),"+f"(d[92]),"+f"(d[93]),"+f"(d[94]),"+f"(d[95]),"+f"(d[96]),
          "+f"(d[97]),"+f"(d[98]),"+f"(d[99]),"+f"(d[100]),"+f"(d[101]),"+f"(d[102]),"+f"(d[103]),"+f"(d[104]),"+f"(d[105]),"+f"(d[106]),"+f"(d[107]),
          "+f"(d[108]),"+f"(d[109]),"+f"(d[110]),"+f"(d[111]),"+f"(d[112]),"+f"(d[113]),"+f"(d[114]),"+f"(d[115]),"+f"(d[116]),"+f"(d[117]),"+f"(d[118]),
          "+f"(d[119]),"+f"(d[120]),"+f"(d[121]),"+f"(d[122]),"+f"(d[123]),"+f"(d[124]),"+f"(d[125]),"+f"(d[126]),"+f"(d[127])
        : "l"(da), "l"(db), "r"(acc));
}
__device__ __forceinline__ void wgmma_ss_n128(float* d, uint64_t da, uint64_t db, int acc) {
    asm volatile("{\n.reg .pred p;\nsetp.ne.b32 p, %66, 0;\nwgmma.mma_async.sync.aligned.m64n128k16.f32.bf16.bf16 {"
        "%0,%1,%2,%3,%4,%5,%6,%7,%8,%9,%10,%11,%12,%13,%14,%15,%16,%17,%18,%19,%20,%21,%22,%23,%24,%25,%26,%27,%28,%29,%30,%31,%32,%33,%34,%35,%36,%37,%38,%39,"
        "%40,%41,%42,%43,%44,%45,%46,%47,%48,%49,%50,%51,%52,%53,%54,%55,%56,%57,%58,%59,%60,%61,%62,%63"
        "}, %64, %65, p, 1, 1, 0, 1;\n}\n"
        : "+f"(d[0]),"+f"(d[1]),"+f"(d[2]),"+f"(d[3]),"+f"(d[4]),"+f"(d[5]),"+f"(d[6]),"+f"(d[7]),"+f"(d[8]),"+f"(d[9]),"+f"(d[10]),"+f"(d[11]),"+f"(d[12]),
          "+f"(d[13]),"+f"(d[14]),"+f"(d[15]),"+f"(d[16]),"+f"(d[17]),"+f"(d[18]),"+f"(d[19]),"+f"(d[20]),"+f"(d[21]),"+f"(d[22]),"+f"(d[23]),"+f"(d[24]),
          "+f"(d[25]),"+f"(d[26]),"+f"(d[27]),"+f"(d[28]),"+f"(d[29]),"+f"(d[30]),"+f"(d[31]),"+f"(d[32]),"+f"(d[33]),"+f"(d[34]),"+f"(d[35]),"+f"(d[36]),
          "+f"(d[37]),"+f"(d[38]),"+f"(d[39]),"+f"(d[40]),"+f"(d[41]),"+f"(d[42]),"+f"(d[43]),"+f"(d[44]),"+f"(d[45]),"+f"(d[46]),"+f"(d[47]),"+f"(d[48]),
          "+f"(d[49]),"+f"(d[50]),"+f"(d[51]),"+f"(d[52]),"+f"(d[53]),"+f"(d[54]),"+f"(d[55]),"+f"(d[56]),"+f"(d[57]),"+f"(d[58]),"+f"(d[59]),"+f"(d[60]),
          "+f"(d[61]),"+f"(d[62]),"+f"(d[63])
        : "l"(da), "l"(db), "r"(acc));
}
__device__ __forceinline__ void wgmma_ss_n64(float* d, uint64_t da, uint64_t db, int acc) {
    asm volatile("{\n.reg .pred p;\nsetp.ne.b32 p, %34, 0;\nwgmma.mma_async.sync.aligned.m64n64k16.f32.bf16.bf16 {"
        "%0,%1,%2,%3,%4,%5,%6,%7,%8,%9,%10,%11,%12,%13,%14,%15,%16,%17,%18,%19,%20,%21,%22,%23,%24,%25,%26,%27,%28,%29,%30,%31"
        "}, %32, %33, p, 1, 1, 0, 1;\n}\n"
        : "+f"(d[0]),"+f"(d[1]),"+f"(d[2]),"+f"(d[3]),"+f"(d[4]),"+f"(d[5]),"+f"(d[6]),"+f"(d[7]),"+f"(d[8]),"+f"(d[9]),"+f"(d[10]),"+f"(d[11]),"+f"(d[12]),
          "+f"(d[13]),"+f"(d[14]),"+f"(d[15]),"+f"(d[16]),"+f"(d[17]),"+f"(d[18]),"+f"(d[19]),"+f"(d[20]),"+f"(d[21]),"+f"(d[22]),"+f"(d[23]),"+f"(d[24]),
          "+f"(d[25]),"+f"(d[26]),"+f"(d[27]),"+f"(d[28]),"+f"(d[29]),"+f"(d[30]),"+f"(d[31])
        : "l"(da), "l"(db), "r"(acc));
}
__device__ __forceinline__ void wgmma_rs_n64_zero(float* d, const uint32_t* a, uint64_t db) {
    asm volatile("wgmma.mma_async.sync.aligned.m64n64k16.f32.bf16.bf16 {"
        "%0,%1,%2,%3,%4,%5,%6,%7,%8,%9,%10,%11,%12,%13,%14,%15,%16,%17,%18,%19,%20,%21,%22,%23,%24,%25,%26,%27,%28,%29,%30,%31"
        "}, {%32,%33,%34,%35}, %36, 0, 1, 1, 0;\n"
        : "=f"(d[0]),"=f"(d[1]),"=f"(d[2]),"=f"(d[3]),"=f"(d[4]),"=f"(d[5]),"=f"(d[6]),"=f"(d[7]),"=f"(d[8]),"=f"(d[9]),"=f"(d[10]),"=f"(d[11]),"=f"(d[12]),
          "=f"(d[13]),"=f"(d[14]),"=f"(d[15]),"=f"(d[16]),"=f"(d[17]),"=f"(d[18]),"=f"(d[19]),"=f"(d[20]),"=f"(d[21]),"=f"(d[22]),"=f"(d[23]),"=f"(d[24]),
          "=f"(d[25]),"=f"(d[26]),"=f"(d[27]),"=f"(d[28]),"=f"(d[29]),"=f"(d[30]),"=f"(d[31])
        : "r"(a[0]), "r"(a[1]), "r"(a[2]), "r"(a[3]), "l"(db));
}
__device__ __forceinline__ void wgmma_rs_n64_acc(float* d, const uint32_t* a, uint64_t db) {
    asm volatile("wgmma.mma_async.sync.aligned.m64n64k16.f32.bf16.bf16 {"
        "%0,%1,%2,%3,%4,%5,%6,%7,%8,%9,%10,%11,%12,%13,%14,%15,%16,%17,%18,%19,%20,%21,%22,%23,%24,%25,%26,%27,%28,%29,%30,%31"
        "}, {%32,%33,%34,%35}, %36, 1, 1, 1, 0;\n"
        : "+f"(d[0]),"+f"(d[1]),"+f"(d[2]),"+f"(d[3]),"+f"(d[4]),"+f"(d[5]),"+f"(d[6]),"+f"(d[7]),"+f"(d[8]),"+f"(d[9]),"+f"(d[10]),"+f"(d[11]),"+f"(d[12]),
          "+f"(d[13]),"+f"(d[14]),"+f"(d[15]),"+f"(d[16]),"+f"(d[17]),"+f"(d[18]),"+f"(d[19]),"+f"(d[20]),"+f"(d[21]),"+f"(d[22]),"+f"(d[23]),"+f"(d[24]),
          "+f"(d[25]),"+f"(d[26]),"+f"(d[27]),"+f"(d[28]),"+f"(d[29]),"+f"(d[30]),"+f"(d[31])
        : "r"(a[0]), "r"(a[1]), "r"(a[2]), "r"(a[3]), "l"(db));
}
__device__ __forceinline__ void wgmma_rs_n24_acc(float* d, const uint32_t* a, uint64_t db) {
    asm volatile("wgmma.mma_async.sync.aligned.m64n24k16.f32.bf16.bf16 {"
        "%0,%1,%2,%3,%4,%5,%6,%7,%8,%9,%10,%11"
        "}, {%12,%13,%14,%15}, %16, 1, 1, 1, 1;\n"
        : "+f"(d[0]),"+f"(d[1]),"+f"(d[2]),"+f"(d[3]),"+f"(d[4]),"+f"(d[5]),"+f"(d[6]),"+f"(d[7]),"+f"(d[8]),"+f"(d[9]),"+f"(d[10]),"+f"(d[11])
        : "r"(a[0]), "r"(a[1]), "r"(a[2]), "r"(a[3]), "l"(db));
}
__device__ __forceinline__ void wgmma_rs_n24_zero(float* d, const uint32_t* a, uint64_t db) {
    asm volatile("wgmma.mma_async.sync.aligned.m64n24k16.f32.bf16.bf16 {"
        "%0,%1,%2,%3,%4,%5,%6,%7,%8,%9,%10,%11"
        "}, {%12,%13,%14,%15}, %16, 0, 1, 1, 1;\n"
        : "=f"(d[0]),"=f"(d[1]),"=f"(d[2]),"=f"(d[3]),"=f"(d[4]),"=f"(d[5]),"=f"(d[6]),"=f"(d[7]),"=f"(d[8]),"=f"(d[9]),"=f"(d[10]),"=f"(d[11])
        : "r"(a[0]), "r"(a[1]), "r"(a[2]), "r"(a[3]), "l"(db));
}

constexpr int OFF_ONES = 131072;
constexpr int OFF_RING = OFF_ONES + 4096;
constexpr int NRING = 5;
constexpr int OFF_B2 = OFF_RING + NRING * 16384;
constexpr int OFF_CS = OFF_B2 + 2048;
constexpr int OFF_RS = OFF_CS + 2560;
constexpr int OFF_BAR = OFF_RS + 1024;
enum { B_FULL = 0, B_STATS = 40, B_KV = 45, B_RING = 53, B_WO = 56, B_O = 57, B_CNT2 = 65,
       B_AFREE = 65, B_ORD = 69, B_QKV = 74, B_CNT4 = 75, B_EMPTY = 75, B_AFREE0 = 80, B_DONE = 81, B_CNT8 = 82, B_TILE = 82, B_OW = 87, B_STATS0 = 89, B_NUM = 100 };
constexpr int OFF_TS = OFF_BAR + 1024;
constexpr int SMEM_BYTES = OFF_BAR + B_NUM * 8;
constexpr unsigned FIXED_MASK = 0xB5;
constexpr float P71 = 2361183241434822606848.0f, M71 = 4.235164736271502e-22f;

__device__ __forceinline__ uint32_t exp2_fixed(float lo, float hi, uint32_t half2) {
    uint32_t y, g, d;
    asm("cvt.pack.sat.s16.s32 %0, %1, %2;" : "=r"(y) : "r"(__float_as_uint(hi)), "r"(__float_as_uint(lo)));
    asm("lop3.b32 %0, %1, 0x007F007F, %2, 0xEA;" : "=r"(g) : "r"(y), "r"(half2));
    asm("fma.rn.bf16x2 %0, %1, %2, %3;" : "=r"(d) : "r"(y), "r"(g), "r"(y & 0xFF80FF80u));
    return d;
}
__device__ __forceinline__ uint32_t k_tile_addr(uint32_t base, int tile) {
    const int c = tile >> 2;
    return base + ((tile & 2) ? 98304 + c * 4096 : (2 * c + 1) * 4096) + (tile & 1) * 2048;
}
constexpr uint32_t POS_STD = 0x76543210u, POS_LAST = 0xB75A9640u;

__global__ void __cluster_dims__(2, 1, 1) __launch_bounds__(640, 1)
mega_kernel(const __nv_bfloat16* __restrict__ x, const __nv_bfloat16* __restrict__ wqkv, const __nv_bfloat16* __restrict__ w1,
            const __nv_bfloat16* __restrict__ w3, __nv_bfloat16* __restrict__ out,
            const __grid_constant__ CUtensorMap mx, const __grid_constant__ CUtensorMap mqkv, const __grid_constant__ CUtensorMap mw1,
            const __grid_constant__ CUtensorMap mw3, const __grid_constant__ CUtensorMap mw2, const __grid_constant__ CUtensorMap mwo,
            uint32_t half2) {
    extern __shared__ __align__(1024) uint8_t smem_raw[];
    const uint32_t sb = __shfl_sync(0xffffffffu, smem_u32(smem_raw), 0);
    if ((sb & 0xFFFFFF) != SMEM_BASE) __trap();
    const uint32_t bars = sb + OFF_BAR, ring = sb + OFF_RING;
    const int tid = threadIdx.x, lane = tid & 31, g = lane >> 2, t4 = lane & 3;
    const int warp = __shfl_sync(0xffffffffu, tid >> 5, 0), wg = warp >> 2, wq = warp & 3;
    const int rank = blockIdx.x & 1, cl = blockIdx.x >> 1;
    const int grp = cl < 4 ? 4 + cl : cl < 36 ? (cl - 4) >> 3 : 4 + (cl - 36) / 7;
    const int rot = cl < 4 ? 7 : cl < 36 ? (cl - 4) & 7 : (cl - 36) % 7;
    const int mblk = rot * 2 + rank;
    const int nq = grp < 4 ? 2 : 1;
    const int qt0 = grp < 4 ? 2 * grp : 4 + grp;
    const int gu0 = (grp < 4 ? 3 * grp : 4 * grp - 4) - nq;
    const int head = blockIdx.x >> 2, qb = blockIdx.x & 3;

    if (elect_one()) {
#pragma unroll
        for (int i = 0; i < 5; i++) { const int b = warp * 5 + i; mbar_init(bars + 8 * b, b < B_CNT2 ? 1 : b < B_CNT4 ? 2 : b < B_CNT8 ? 4 : 8); }
        if (warp == 0) {
            fence_async_smem();
#pragma unroll
            for (int j = 0; j < 2; j++) {
                tma2d(sb + j * 16384, &mx, j * 64, mblk * 128, bars + 8 * (B_FULL + j));
                tma2d(ring + j * 16384, &mqkv, qt0 * 128, j * 64, bars + 8 * (B_FULL + j));
                tma2d(ring + j * 16384 + 8192, &mqkv, qt0 * 128 + 64, j * 64, bars + 8 * (B_FULL + j));
            }
        }
        if (warp < 8) {
#pragma unroll
            for (int i = 0; i < 5; i++) mbar_expect(bars + 8 * (warp * 5 + i), warp * 5 + i < 8 ? 32768 : 16384);
        }
        if (warp == 16) asm volatile("prefetch.tensormap [%0];" :: "l"(rank ? &mw3 : &mw1) : "memory");
        asm volatile("fence.mbarrier_init.release.cluster;" ::: "memory");
    }
    __syncthreads();
    if (tid == 512) TSTAMP(26);
    asm volatile("barrier.cluster.arrive.relaxed.aligned;" ::: "memory");

    if (wg < 4) {
        const int pair = wg >> 1, half = wg & 1;
        if (pair == 1) {
            const int row = mblk * 128 + grp * 16 + (warp - 8) * 2 + (lane >> 4);
            uint4 v[6];
            const uint32_t* w = reinterpret_cast<const uint32_t*>(v);
#pragma unroll
            for (int j = 0; j < 2; j++) v[4 + j] = __ldg(reinterpret_cast<const uint4*>(wqkv + (size_t)(rot * 64 + (warp - 8) * 8 + j * 4 + (lane >> 3)) * (3 * DM) + qt0 * 128 + rank * 64) + (lane & 7));
#pragma unroll
            for (int j = 0; j < 4; j++) v[j] = __ldg(reinterpret_cast<const uint4*>(x + (size_t)row * DM) + j * 16 + (lane & 15));
            const uint32_t tag = ld_epoch() + 1;
            float c[8];
#pragma unroll
            for (int e = 0; e < 4; e++) { c[2 * e] = bf_lo(w[16 + e]) + bf_lo(w[20 + e]); c[2 * e + 1] = bf_hi(w[16 + e]) + bf_hi(w[20 + e]); }
#pragma unroll
            for (int n = 4; n > 1; n >>= 1) {
                const bool up = lane & (4 * n);
#pragma unroll
                for (int e = 0; e < n; e++) c[e] = (up ? c[e + n] : c[e]) + __shfl_xor_sync(0xffffffffu, up ? c[e] : c[e + n], 4 * n);
            }
            asm volatile("st.shared.v2.f32 [%0], {%1,%2};" :: "r"(sb + OFF_CS + 512 + (warp - 8) * 256 + (lane & 7) * 32 + (lane >> 3) * 8), "f"(c[0]), "f"(c[1]) : "memory");
            float sa[4] = {0.f, 0.f, 0.f, 0.f}, sq[4] = {0.f, 0.f, 0.f, 0.f};
#pragma unroll
            for (int j = 0; j < 16; j++) sa[j & 3] += bf_lo(w[j]) + bf_hi(w[j]);
            float mean = ((sa[0] + sa[1]) + (sa[2] + sa[3])) * (1.0f / 32);
#pragma unroll
            for (int j = 0; j < 16; j++) { const float a = bf_lo(w[j]) - mean, b = bf_hi(w[j]) - mean; sq[j & 1] = fmaf(a, a, sq[j & 1]); sq[2 + (j & 1)] = fmaf(b, b, sq[2 + (j & 1)]); }
            float m2 = (sq[0] + sq[1]) + (sq[2] + sq[3]);
#pragma unroll
            for (int d = 1; d < 16; d <<= 1) {
                const float om = __shfl_xor_sync(0xffffffffu, mean, d), o2 = __shfl_xor_sync(0xffffffffu, m2, d), dm = mean - om;
                m2 = fmaf(dm * dm, 16.0f * d, m2 + o2); mean = 0.5f * (mean + om);
            }
            float sd;
            asm("sqrt.approx.f32 %0, %1;" : "=f"(sd) : "f"(bf_round(bf_round(m2 * (1.0f / DM)) + 1e-5f)));
            if ((lane & 15) == 0) st_tagged(reinterpret_cast<unsigned long long*>(g_rs) + row, pack_bf16(mean, sd), tag);
            if (tid == 256) TSTAMP(45);
            bar_sync(6, 256);
            if (warp < 10) {
#pragma unroll
                for (int e = 0; e < 8; e++) asm volatile("ld.shared.f32 %0, [%1];" : "=f"(c[e]) : "r"(sb + OFF_CS + 512 + e * 256 + (tid & 63) * 4));
                st_tagged(reinterpret_cast<unsigned long long*>(g_cs) + (grp * 40 + rot) * 128 + rank * 64 + (tid & 63),
                          __float_as_uint(((c[0] + c[1]) + (c[2] + c[3])) + ((c[4] + c[5]) + (c[6] + c[7]))), tag);
                if (tid == 256) TSTAMP(40);
            }
            uint32_t r0, r1, a0, a1, b0, b1;
#pragma unroll 1
            for (int n = 0; n < 2000000; n++) {
                const ulonglong2* pc = g_cs + grp * 2560 + (lane >> 3) * 64 + (warp - 8) * 8 + (lane & 7);
                const uint32_t stale = ld_tagged2(g_rs + mblk * 64 + (warp - 8) * 8 + (lane & 7), tag, r0, r1) | ld_tagged2(pc, tag, a0, a1) | ld_tagged2(pc + 256, tag, b0, b1);
                if (__all_sync(0xffffffffu, stale == 0)) break;
            }
            c[0] = __uint_as_float(a0) + __uint_as_float(b0); c[1] = __uint_as_float(a1) + __uint_as_float(b1);
#pragma unroll
            for (int d = 8; d < 32; d <<= 1) { c[0] += __shfl_xor_sync(0xffffffffu, c[0], d); c[1] += __shfl_xor_sync(0xffffffffu, c[1], d); }
            if (lane < 8) {
                asm volatile("st.shared.v2.f32 [%0], {%1,%2};" :: "r"(sb + OFF_CS + (warp - 8) * 64 + lane * 8), "f"(c[0]), "f"(c[1]) : "memory");
                asm volatile("st.shared.v2.b32 [%0], {%1,%2};" :: "r"(sb + OFF_RS + (warp - 8) * 64 + lane * 8), "r"(r0), "r"(r1) : "memory");
            }
            __syncwarp();
            if (elect_one()) mbar_arrive(bars + 8 * B_STATS0);
            if (tid == 256) TSTAMP(32);
        }

        uint32_t q[4], qn[6];
        {
            float acc[64];
            const int rowblk = mblk * 2 + half, tile16 = rowblk * 4 + wq;
            const bool rel = wq < 2 && lane == 0, rel2 = wq == 2 && lane == 0;
            uint32_t empty;
            asm("mapa.shared::cluster.u32 %0, %1, %2;" : "=r"(empty) : "r"(bars + 8 * B_EMPTY), "r"(wq & 1));
#pragma unroll 1
            for (int t = pair; t < 5; t += 2) {
                uint32_t po = t == 4 ? POS_LAST : POS_STD, full = bars + 8 * (B_FULL + 8 * t), slot = (0x24130u >> (4 * t)) & 7, prev = 0;
                uint64_t da = mkdesc(half * 8192, 16, 1024, 1), db = mkdesc(OFF_RING, 8192, 1024, 1) + slot * 1024;
                if (tid == 0 && t == 0) TSTAMP(30);
                mbar_wait(full, 0);
                if (t > 0) mbar_wait(bars + 8 * (B_ORD + t - 1), 0);
#pragma unroll 1
                for (int j = 0; j < 8; j++) {
                    wg_fence();
#pragma unroll
                    for (int k = 0; k < 4; k++) wgmma_ss_n128(acc, da + k * 2, db + k * 128, (j | k) != 0);
                    wg_commit();
                    const uint32_t rel_a = empty + prev * 8, rel_b = bars + 8 * (j == 3 ? B_AFREE0 : B_AFREE + (j >> 1) - 1);
                    const bool do_a = j > 0 && rel, do_b = (po & 8) && rel2;
                    prev = slot; slot = slot == NRING - 1 ? 0 : slot + 1; po >>= 4; full += 8;
                    da = mkdesc(half * 8192, 16, 1024, 1) + (po & 7) * 1024; db = mkdesc(OFF_RING, 8192, 1024, 1) + slot * 1024;
                    if (j < 7) mbar_wait(full, 0); else if (rel2) mbar_arrive(bars + 8 * (B_ORD + t));
                    wg_wait<1>();
                    if (do_a) mbar_arrive_remote(rel_a);
                    if (do_b) mbar_arrive(rel_b);
                }
                if (t >= 3) {
                    mbar_wait(bars + 8 * B_QKV, 0);
                    const uint4* pq = g_q + (head * 128 + (qb * 8 + wg) * 4 + wq) * 32 + lane;
                    const uint4 v = __ldcg(pq), u = __ldcg(pq + 512);
                    qn[0] = v.x; qn[1] = v.y; qn[2] = v.z; qn[3] = v.w; q[0] = u.x; q[1] = u.y; q[2] = u.z; q[3] = u.w;
                }
                wg_wait<0>();
                if (rel) mbar_arrive_remote(empty + prev * 8);
                if (t >= 3 && rel2) mbar_arrive(bars + 8 * (t == 4 ? B_AFREE + 3 : B_AFREE0));
                pin<64>(acc);
                if (wq == 0 && half == 0 && lane == 0) TSTAMP(2 + 2 * t);
                mbar_wait(bars + 8 * (t ? B_STATS + t : B_STATS0), 0);
                uint32_t rs0, rs1;
                asm volatile("ld.shared.b32 %0, [%1];" : "=r"(rs0) : "r"(sb + OFF_RS + (half * 64 + wq * 16 + g) * 4));
                asm volatile("ld.shared.b32 %0, [%1];" : "=r"(rs1) : "r"(sb + OFF_RS + (half * 64 + wq * 16 + g + 8) * 4));
                const float m0 = bf_lo(rs0), m1 = bf_lo(rs1);
                float d0 = bf_hi(rs0), d1 = bf_hi(rs1);
#pragma unroll
                for (int j = 0; j < 16; j++) {
                    float c0, c1;
                    asm volatile("ld.shared.v2.f32 {%0,%1}, [%2];" : "=f"(c0), "=f"(c1) : "r"(sb + OFF_CS + (t * 128 + j * 8 + t4 * 2) * 4));
                    acc[4 * j] = fmaf(-m0, c0, acc[4 * j]); acc[4 * j + 1] = fmaf(-m0, c1, acc[4 * j + 1]);
                    acc[4 * j + 2] = fmaf(-m1, c0, acc[4 * j + 2]); acc[4 * j + 3] = fmaf(-m1, c1, acc[4 * j + 3]);
                }
                float r0 = __frcp_rn(d0), r1 = __frcp_rn(d1);
                if (t < nq) {
                    const int qt = qt0 + t, h0 = (qt & 3) * 8;
                    if (qt < 4) {
                        r0 *= 0.25f * 1.4426950408889634f * M71; r1 *= 0.25f * 1.4426950408889634f * M71;
                    } else if (qt < 8) {
                        r0 *= ((FIXED_MASK >> (2 * wq)) & 1) ? M71 : P71; r1 *= ((FIXED_MASK >> (2 * wq + 1)) & 1) ? M71 : P71;
                    }
                    uint32_t* p; int s8, sh;
                    if (qt < 8) { p = reinterpret_cast<uint32_t*>(g_k + h0 * 4096) + tile16 * 128 + lane; s8 = 64; sh = 32; }
                    else        { p = reinterpret_cast<uint32_t*>(g_v + h0 * 4096) + tile16 * 64 + lane;  s8 = 32; sh = 8192; }
#pragma unroll
                    for (int hh = 0; hh < 8; hh++) {
                        const float* a = acc + hh * 8;
                        const uint32_t e0 = pack_bf16(a[0] * r0, a[1] * r0), e1 = pack_bf16(a[2] * r1, a[3] * r1);
                        const uint32_t e2 = pack_bf16(a[4] * r0, a[5] * r0), e3 = pack_bf16(a[6] * r1, a[7] * r1);
                        if (qt < 4) g_q[((h0 + hh) * 128 + tile16) * 32 + lane] = make_uint4(e0, e1, e2, e3);
                        else { uint32_t* pp = p + hh * 16384; pp[0] = e0; pp[s8] = e1; pp[sh] = e2; pp[sh + s8] = e3; }
                    }
                } else {
                    uint32_t* p = reinterpret_cast<uint32_t*>(g_h + (rowblk * 28 + gu0 + t) * 512) + wq * 512 + lane;
                    r0 *= -1.4426950408889634f; r1 *= -1.4426950408889634f; d0 *= d0; d1 *= d1;
#pragma unroll
                    for (int j = 0; j < 8; j++) {
                        const float* a = acc + j * 4; const float* b = a + 32;
                        p[j * 32] = pack_bf16(a[0] * b[0] * rcpf(fmaf(ex2f(a[0] * r0), d0, d0)), a[1] * b[1] * rcpf(fmaf(ex2f(a[1] * r0), d0, d0)));
                        p[256 + j * 32] = pack_bf16(a[2] * b[2] * rcpf(fmaf(ex2f(a[2] * r1), d1, d1)), a[3] * b[3] * rcpf(fmaf(ex2f(a[3] * r1), d1, d1)));
                    }
                }
                __syncwarp();
                if (elect_one()) mbar_arrive(bars + 8 * (B_TILE + t));
                if (wq == 0 && half == 0 && lane == 0) TSTAMP(3 + 2 * t);
            }
        }
        const uint64_t db2 = mkdesc(OFF_B2, 128, 256, 0);
        float s[32];
        auto ref_point = [&](int ntile, uint32_t& b0, uint32_t& b1) {
            float m0 = -INFINITY, m1 = -INFINITY, f0 = -INFINITY, f1 = -INFINITY;
#pragma unroll 1
            for (int t = 0; t < ntile; t++) {
                wg_fence();
                wgmma_rs_n64_zero(s, q, mkdesc(k_tile_addr(0, t), 128, 256, 0));
                wg_commit();
                wg_wait<0>();
                pin<32>(s);
#pragma unroll
                for (int i = 0; i < 8; i++) {
                    if ((FIXED_MASK >> i) & 1) { f0 = fmaxf(f0, fmaxf(s[4 * i], s[4 * i + 1])); f1 = fmaxf(f1, fmaxf(s[4 * i + 2], s[4 * i + 3])); }
                    else                       { m0 = fmaxf(m0, fmaxf(s[4 * i], s[4 * i + 1])); m1 = fmaxf(m1, fmaxf(s[4 * i + 2], s[4 * i + 3])); }
                }
            }
            m0 = fmaxf(m0, f0 * P71 * P71); m1 = fmaxf(m1, f1 * P71 * P71);
            m0 = fmaxf(m0, __shfl_xor_sync(0xffffffffu, m0, 1)); m1 = fmaxf(m1, __shfl_xor_sync(0xffffffffu, m1, 1));
            m0 = fmaxf(m0, __shfl_xor_sync(0xffffffffu, m0, 2)); m1 = fmaxf(m1, __shfl_xor_sync(0xffffffffu, m1, 2));
#pragma unroll
            for (int r = 0; r < 2; r++) {
                const float m = -rintf(r ? m1 : m0), mh = bf_round(m), mm = bf_round(m - mh), ml = m - mh - mm;
                const float lo = t4 == 0 ? mh : t4 == 1 ? ml : t4 == 2 ? 1.f : 0.f, hi = t4 == 0 ? mm : t4 == 1 ? 1.f : 0.f;
                (r ? b1 : b0) = pack_bf16(lo * M71, hi * M71);
            }
        };
        uint32_t q2[4];
        int redo = 1;
        mbar_wait(bars + 8 * B_KV, 0);
#pragma unroll 1
        for (int round = -1; round < 2;) {
            if (redo) ref_point(redo, q2[0], q2[1]);
            if (round < 0) {
#pragma unroll
                for (int i = 0; i < 4; i++) { const uint32_t tq = q[i]; q[i] = qn[i]; qn[i] = tq; }
                qn[4] = q2[0]; qn[5] = q2[1];
                q2[2] = __shfl_sync(0xffffffffu, q2[0], 3); q2[3] = __shfl_sync(0xffffffffu, q2[1], 3);
                round = 0;
                continue;
            }
            float o[12]; uint32_t p[16];
#pragma unroll
            for (int i = 0; i < 12; i++) o[i] = 0.f;
            pin<12>(o); pin<4>(q2);
            if (wq == 0 && half == 0 && lane == 0) TSTAMP(12 + 4 * round + pair);
            uint64_t dk0 = mkdesc(4096, 128, 256, 0), dk1 = mkdesc(98304, 128, 256, 0), dv = mkdesc(0, 128, 65536, 0);
#pragma unroll 1
            for (int c = 0; c < 8; c++, dk0 += 512, dk1 += 256, dv += 512 - (256ull << 32)) {
                if (round == 0) mbar_wait(bars + 8 * (B_KV + c), 0);
#pragma unroll
                for (int t = 0; t < 4; t++) {
                    wg_fence();
                    wgmma_rs_n64_zero(s, q, (t & 2 ? dk1 : dk0) + (t & 1) * 128);
                    wgmma_rs_n64_acc(s, q2, db2);
                    wg_commit();
                    wg_wait<0>();
                    pin<32>(s); pin<16>(p);
#pragma unroll
                    for (int i = 0; i < 16; i++) {
                        if ((FIXED_MASK >> (i >> 1)) & 1) p[i] = exp2_fixed(s[2 * i], s[2 * i + 1], half2);
                        else                              p[i] = pack_bf16(ex2f(s[2 * i]), ex2f(s[2 * i + 1]));
                    }
                    wg_fence();
#pragma unroll
                    for (int k = 0; k < 4; k++) wgmma_rs_n24_acc(o, p + 4 * k, dv + (t * 4 + k) * 16);
                    wg_commit();
                }
            }
            wg_wait<0>();
            pin<12>(o);
            if (redo != 32) {
                float chk = (o[8] + o[10]) * 256.f;
#pragma unroll
                for (int i = 0; i < 8; i++) chk += fabsf(o[i]);
                uint32_t bad;
                asm volatile("{\n.reg .pred p, q;\nsetp.geu.f32 q, %1, 0f7F800000;\nbar.red.or.pred p, %2, 128, q;\nselp.u32 %0, 1, 0, p;\n}" : "=r"(bad) : "f"(chk), "r"(1 + wg) : "memory");
                if (__any_sync(0xffffffffu, bad)) { redo = 32; continue; }
            }
            const int rowblk = qb * 8 + round * 4 + wg;
            const float r0 = rcpf(o[8]), r1 = rcpf(o[10]);
            uint32_t* po = reinterpret_cast<uint32_t*>(g_o + (rowblk * 8 + (head >> 2)) * 512) + wq * 512 + (head & 3) * 64 + lane;
            po[0] = pack_bf16(o[0] * r0, o[1] * r0); po[256] = pack_bf16(o[2] * r1, o[3] * r1);
            po[32] = pack_bf16(o[4] * r0, o[5] * r0); po[288] = pack_bf16(o[6] * r1, o[7] * r1);
            if (round == 0) {
                __syncwarp();
                if (elect_one()) mbar_arrive(bars + 8 * (B_OW + pair));
            } else {
                bar_sync(1 + wg, 128);
                if (wq == 0 && elect_one()) { mbar_arrive(bars + 8 * B_DONE); signal_cnt(C_O + rowblk); }
            }
#pragma unroll
            for (int i = 0; i < 4; i++) q[i] = qn[i];
            q2[0] = qn[4]; q2[1] = qn[5];
            redo = 0;
            if (wq == 0 && half == 0 && lane == 0) TSTAMP(14 + 4 * round + pair);
            round++;
        }
    } else {
        uint32_t tag;
        if (wq == 0) {
            asm volatile("barrier.cluster.wait.aligned;" ::: "memory");
            if (tid == 512) TSTAMP(27);
            uint32_t slot = 2, ph = 1;
#pragma unroll 1
            for (int n = 2; n < 40; n++) {
                const int t = n >> 3, j = n & 7;
                const int kc = (n < 32 ? j : (POS_LAST >> (4 * j)) & 7) * 64;
                const CUtensorMap* m = t < nq ? &mqkv : rank ? &mw3 : &mw1;
                const int col = t < nq ? (qt0 + t) * 128 + rank * 64 : (gu0 + t) * 64;
                const uint32_t dst = ring + slot * 16384 + rank * 8192, fb = bars + 8 * (B_FULL + n);
                if (n < 8 && elect_one()) tma2d(sb + n * 16384, &mx, kc, mblk * 128, fb);
                mbar_wait(bars + 8 * (B_EMPTY + slot), ph);
                if (elect_one()) { TS2(0, n); tma2d_mc(dst, m, col, kc, fb); }
                if (++slot == NRING) { slot = 0; ph ^= 1; }
            }
            tag = ld_epoch() + 1;
        } else if (wq == 1) {
            tag = ld_epoch() + 1;
            mbar_wait(bars + 8 * B_STATS0, 0);
#pragma unroll 1
            for (int t = 1; t < 5; t++) {
                float a[4];
#pragma unroll 1
                for (int n = 0; n < 2000000; n++) {
                    uint32_t stale = 0;
                    a[0] = a[1] = a[2] = a[3] = 0.f;
#pragma unroll
                    for (int i = 0; i < 16; i++) {
                        uint32_t u, v;
                        stale |= ld_tagged2(g_cs + (grp * 5 + t) * 512 + i * 32 + lane, tag, u, v);
                        a[(i & 1) * 2] += __uint_as_float(u); a[(i & 1) * 2 + 1] += __uint_as_float(v);
                    }
                    if (__all_sync(0xffffffffu, stale == 0)) break;
                    __nanosleep(400);
                }
                asm volatile("st.shared.v2.f32 [%0], {%1,%2};" :: "r"(sb + OFF_CS + t * 512 + lane * 8), "f"(a[0]), "f"(a[1]) : "memory");
                asm volatile("st.shared.v2.f32 [%0], {%1,%2};" :: "r"(sb + OFF_CS + t * 512 + 256 + lane * 8), "f"(a[2]), "f"(a[3]) : "memory");
                __syncwarp();
                if (elect_one()) { mbar_arrive(bars + 8 * (B_STATS + t)); TSTAMP(32 + t); }
            }
        } else {
            tag = ld_epoch() + 1;
            mbar_wait(bars + 8 * (B_FULL + wq - 1), 0);
#pragma unroll 1
            for (int t = wq - 1; t < 5; t += 2) {
                const __nv_bfloat16* src; int ld;
                if (t < nq) { src = wqkv + (qt0 + t) * 128 + rank * 64; ld = 3 * DM; }
                else        { src = (rank ? w3 : w1) + (gu0 + t) * 64; ld = FF; }
                src += (size_t)(rot * 64 + (lane >> 3)) * ld + (lane & 7) * 8;
                uint4 v[16];
                const uint32_t* w = reinterpret_cast<const uint32_t*>(v);
#pragma unroll
                for (int j = 0; j < 16; j++) v[j] = __ldg(reinterpret_cast<const uint4*>(src + (size_t)j * 4 * ld));
                float c[8];
#pragma unroll
                for (int e = 0; e < 4; e++) {
                    float a = 0.f, b = 0.f;
#pragma unroll
                    for (int j = 0; j < 16; j++) { a += bf_lo(w[4 * j + e]); b += bf_hi(w[4 * j + e]); }
                    c[2 * e] = a; c[2 * e + 1] = b;
                }
#pragma unroll
                for (int n = 4; n > 1; n >>= 1) {
                    const bool up = lane & (4 * n);
#pragma unroll
                    for (int e = 0; e < n; e++) c[e] = (up ? c[e + n] : c[e]) + __shfl_xor_sync(0xffffffffu, up ? c[e] : c[e + n], 4 * n);
                }
                unsigned long long* dst = reinterpret_cast<unsigned long long*>(g_cs) + ((grp * 5 + t) * 8 + rot) * 128 + rank * 64 + (lane & 7) * 8 + (lane >> 3) * 2;
                st_tagged(dst, __float_as_uint(c[0]), tag); st_tagged(dst + 1, __float_as_uint(c[1]), tag);
                if (lane == 0) TSTAMP(40 + t);
            }
        }
        if (wq == 3) {
#pragma unroll 1
            for (int i = lane; i < 256; i += 32) asm volatile("st.shared.v4.b32 [%0], {%1,%1,%1,%1};" :: "r"(sb + OFF_ONES + i * 16), "r"(0x3F803F80u) : "memory");
#pragma unroll 1
            for (int i = lane; i < 128; i += 32) {
                const bool fx = (FIXED_MASK >> (i >> 4)) & 1;
                uint32_t a = fx ? pack_bf16(M71, M71) : pack_bf16(P71, P71);
                uint32_t b = fx ? pack_bf16(M71, 47.0f * M71) : pack_bf16(P71, -79.5f * P71);
                uint32_t c = fx ? 0u : pack_bf16(0.08214f * P71, 0.f);
                if (i & 8) a = b = c = 0;
                asm volatile("st.shared.v4.b32 [%0], {%1,%2,%3,%4};" :: "r"(sb + OFF_B2 + i * 16), "r"(a), "r"(b), "r"(c), "r"(0) : "memory");
            }
            fence_async_smem();
            __syncwarp();
            if (elect_one()) mbar_arrive(bars + 8 * B_QKV);
        } else if (wq == 1) {
#pragma unroll 1
            for (int i = 0; i < 3; i++) wait_cnt(C_QKV + i * 4 + (head >> 3), 16 * tag, 100);
            fence_async_all();
            if (elect_one()) { mbar_arrive(bars + 8 * B_QKV); TSTAMP(29); }
            const uint8_t* gk = reinterpret_cast<const uint8_t*>(g_k + head * 4096);
            const uint8_t* gv = reinterpret_cast<const uint8_t*>(g_v + head * 4096);
#pragma unroll 1
            for (int c = 0; c < 8; c++) {
                if (!(c & 1)) mbar_wait(bars + 8 * (c ? B_AFREE + (c >> 1) : B_AFREE0), 0);
                if (elect_one()) {
                    const uint32_t b = bars + 8 * (B_KV + c);
                    mbar_expect(b, 16384);
                    bulk_load(sb + (2 * c + 1) * 4096, gk + c * 8192, 4096, b);
                    bulk_load(sb + 2 * c * 4096, gv + c * 4096, 4096, b);
                    bulk_load(sb + 65536 + c * 4096, gv + 32768 + c * 4096, 4096, b);
                    bulk_load(sb + 98304 + c * 4096, gk + c * 8192 + 4096, 4096, b);
                }
            }
        } else if (wq == 2) {
#pragma unroll 1
            for (int t = 0; t < 5; t++) {
                mbar_wait(bars + 8 * (B_TILE + t), 0);
                if (elect_one()) signal_cnt(t < nq ? C_QKV + qt0 + t : C_H + mblk);
            }
        }
        pin<1>(&tag);
        bar_sync(5, 128);
        if (tid == 639) g_epoch[blockIdx.x] = tag;
        const int cb = blockIdx.x & 7, pr = blockIdx.x >> 3;
        const int rb0 = (pr >> 2) * 8 + (pr & 3);
        uint32_t gate[2][16];
        {
            float dn[64];
            auto load_stage = [&](int kb, int st) {
                const uint32_t b = bars + 8 * (B_RING + st), dst = ring + st * 24576;
                mbar_expect(b, 24576);
                bulk_load(dst, g_h + (rb0 * 28 + kb) * 512, 8192, b);
                bulk_load(dst + 8192, g_h + ((rb0 + 4) * 28 + kb) * 512, 8192, b);
                tma2d(dst + 16384, &mw2, cb * 64, kb * 64, b);
            };
            if (wq == 0) {
                wait_cnt(C_H + (rb0 >> 1), 28 * tag, 200);
                wait_cnt(C_H + (rb0 >> 1) + 2, 28 * tag, 200);
                if (elect_one()) { TSTAMP(20); fence_async_all(); load_stage(0, 0); load_stage(1, 1); }
            }
            int st = 0; uint32_t ph = 0;
#pragma unroll 1
            for (int kb = 0; kb < 28; kb++) {
                mbar_wait(bars + 8 * (B_RING + st), ph);
                const uint64_t da = mkdesc(OFF_RING + st * 24576, 128, 1024, 0), db = mkdesc(OFF_RING + st * 24576 + 16384, 8192, 1024, 1);
                wg_fence();
#pragma unroll
                for (int k = 0; k < 4; k++) { wgmma_ss_n64(dn, da + k * 16, db + k * 128, (kb | k) != 0); wgmma_ss_n64(dn + 32, da + 512 + k * 16, db + k * 128, (kb | k) != 0); }
                wg_commit();
                wg_wait<1>();
                if (wq == 0 && kb < 26 && elect_one()) load_stage(kb + 2, st == 0 ? 2 : st - 1);
                if (++st == 3) { st = 0; ph ^= 1; }
            }
            wg_wait<0>();
            pin<64>(dn);
#pragma unroll
            for (int i = 0; i < 32; i++) gate[i >> 4][i & 15] = pack_bf16(siluf(dn[2 * i]), siluf(dn[2 * i + 1]));
        }
        float acc[32];
        if (tid == 512) TSTAMP(21);
        const uint32_t bar_wo = bars + 8 * B_WO;
        if (wq == 0 && elect_one()) {
            mbar_expect(bar_wo, 65536);
#pragma unroll 1
            for (int i = 0; i < 8; i++) tma2d(ring + i * 8192, &mwo, cb * 64, i * 64, bar_wo);
        }
        if (wq >= 2) {
            mbar_wait(bars + 8 * (B_OW + wq - 2), 0);
            if (elect_one()) {
                signal_cnt(C_O + qb * 8 + 2 * wq - 4);
                asm volatile("red.relaxed.gpu.global.add.u32 [%0], 1;" :: "l"(g_cnt + (C_O + qb * 8 + 2 * wq - 3) * 8) : "memory");
            }
        }
#pragma unroll 1
        for (int tl = 0; tl < 2; tl++) {
            const int rb = rb0 + 4 * tl;
            uint32_t xr[16];
            const uint32_t* px = reinterpret_cast<const uint32_t*>(x + (size_t)(rb * 64 + wq * 16 + g) * DM + cb * 64) + t4;
#pragma unroll
            for (int j = 0; j < 8; j++) { xr[2 * j] = __ldg(px + j * 4); xr[2 * j + 1] = __ldg(px + 8 * DM / 2 + j * 4); }
            if (wq == 0) {
                if (tl == 1) mbar_wait(bars + 8 * B_DONE, 0);
                wait_cnt(C_O + rb, 32 * tag, tl ? 20 : 200);
                if (elect_one()) {
                    fence_async_all();
                    TSTAMP(22 + 2 * tl);
#pragma unroll 1
                    for (int i = 0; i < (tl ? 8 : 2); i++) {
                        mbar_expect(bars + 8 * (B_O + i), 8192);
                        bulk_load((tl ? sb : ring + 65536) + i * 8192, g_o + (rb * 8 + i) * 512, 8192, bars + 8 * (B_O + i));
                    }
                }
            }
            if (tl == 0) mbar_wait(bar_wo, 0);
#pragma unroll 1
            for (int kb = 0; kb < 8; kb++) {
                mbar_wait(bars + 8 * (B_O + kb), tl);
                const uint32_t a = tl == 0 ? OFF_RING + 65536 + (kb & 1) * 8192 : kb * 8192;
                const uint64_t da = mkdesc(a, 128, 1024, 0), db = mkdesc(OFF_RING + kb * 8192, 8192, 1024, 1);
                wg_fence();
#pragma unroll
                for (int k = 0; k < 4; k++) wgmma_ss_n64(acc, da + k * 16, db + k * 128, (kb | k) != 0);
                wg_commit();
                if (tl == 0) {
                    wg_wait<0>();
                    bar_sync(5, 128);
                    if (wq == 0 && kb < 6 && elect_one()) { mbar_expect(bars + 8 * (B_O + kb + 2), 8192); bulk_load(sb + a, g_o + (rb * 8 + kb + 2) * 512, 8192, bars + 8 * (B_O + kb + 2)); }
                }
            }
            wg_wait<0>();
            pin<32>(acc);
            uint32_t* po = reinterpret_cast<uint32_t*>(out + (size_t)(rb * 64 + wq * 16 + g) * DM + cb * 64) + t4;
#pragma unroll
            for (int i = 0; i < 16; i++) {
                const uint32_t r = pack_bf16(fmaf(acc[2 * i], bf_lo(gate[0][i]), bf_lo(xr[i])), fmaf(acc[2 * i + 1], bf_hi(gate[0][i]), bf_hi(xr[i])));
                po[(i & 1) * (8 * DM / 2) + (i >> 1) * 4] = r;
                gate[0][i] = gate[1][i];
            }
            if (tid == 512) TSTAMP(23 + 2 * tl);
        }
    }
}

typedef CUresult (*EncodeFn)(CUtensorMap*, CUtensorMapDataType, cuuint32_t, void*, const cuuint64_t*, const cuuint64_t*, const cuuint32_t*,
                             const cuuint32_t*, CUtensorMapInterleave, CUtensorMapSwizzle, CUtensorMapL2promotion, CUtensorMapFloatOOBfill);

void make_map(EncodeFn fn, CUtensorMap* m, const void* p, int rows, int cols, int box_rows) {
    cuuint64_t dims[2] = {(cuuint64_t)cols, (cuuint64_t)rows};
    cuuint64_t strides[1] = {(cuuint64_t)cols * 2};
    cuuint32_t box[2] = {64, (cuuint32_t)box_rows};
    cuuint32_t es[2] = {1, 1};
    fn(m, CU_TENSOR_MAP_DATA_TYPE_BFLOAT16, 2, const_cast<void*>(p), dims, strides, box, es, CU_TENSOR_MAP_INTERLEAVE_NONE,
       CU_TENSOR_MAP_SWIZZLE_128B, CU_TENSOR_MAP_L2_PROMOTION_L2_128B, CU_TENSOR_MAP_FLOAT_OOB_FILL_NONE);
}

}

extern "C" void kernel_launch(void* const* d_in, const int* in_sizes, int n_in, void* d_out, int out_size) {
    const __nv_bfloat16* x = (const __nv_bfloat16*)d_in[0];
    static EncodeFn fn = nullptr;
    if (!fn) {
        cudaDriverEntryPointQueryResult qr;
        cudaGetDriverEntryPoint("cuTensorMapEncodeTiled", (void**)&fn, cudaEnableDefault, &qr);
        cudaFuncSetAttribute(mega_kernel, cudaFuncAttributeMaxDynamicSharedMemorySize, SMEM_BYTES);
    }
    CUtensorMap mx, mqkv, mw1, mw3, mw2, mwo;
    make_map(fn, &mx, d_in[0], SEQ, DM, 128);
    make_map(fn, &mqkv, d_in[1], DM, 3 * DM, 64);
    make_map(fn, &mwo, d_in[2], DM, DM, 64);
    make_map(fn, &mw1, d_in[4], DM, FF, 64);
    make_map(fn, &mw3, d_in[5], DM, FF, 64);
    make_map(fn, &mw2, d_in[6], FF, DM, 64);
    mega_kernel<<<128, 640, SMEM_BYTES, cudaStreamPerThread>>>(x, (const __nv_bfloat16*)d_in[1], (const __nv_bfloat16*)d_in[4], (const __nv_bfloat16*)d_in[5],
                                                               (__nv_bfloat16*)d_out, mx, mqkv, mw1, mw3, mw2, mwo, 0x3F003F00u);
}
```

```cpp
#include <cuda_runtime.h>
#include <cuda_bf16.h>
#include <cuda.h>
#include <stdint.h>

namespace {

constexpr int SEQ = 2048, DM = 512, FF = 1792;

__device__ uint4 g_q[32 * 128 * 32];
__device__ uint4 g_k[32 * 4096];
__device__ uint4 g_v[32 * 4096];
__device__ uint4 g_h[32 * 28 * 512];
__device__ uint4 g_o[32 * 8 * 512];
__device__ ulonglong2 g_cs[40 * 8 * 64];
__device__ ulonglong2 g_rs[SEQ / 2];
constexpr int C_QKV = 0, C_H = 12, C_O = 28, C_NUM = 60;
__device__ unsigned g_cnt[C_NUM * 8];
__device__ unsigned g_epoch[128];
#define TSTAMP(i)
#define TS2(k, i)

__device__ __forceinline__ uint32_t smem_u32(const void* p) { return (uint32_t)__cvta_generic_to_shared(p); }
__device__ __forceinline__ void mbar_init(uint32_t a, int c) { asm volatile("mbarrier.init.shared::cta.b64 [%0], %1;" :: "r"(a), "r"(c)); }
__device__ __forceinline__ void mbar_expect(uint32_t a, int b) { asm volatile("mbarrier.arrive.expect_tx.shared::cta.b64 _, [%0], %1;" :: "r"(a), "r"(b) : "memory"); }
__device__ __forceinline__ void mbar_arrive(uint32_t a) { asm volatile("mbarrier.arrive.shared::cta.b64 _, [%0];" :: "r"(a) : "memory"); }
__device__ __forceinline__ void mbar_arrive_remote(uint32_t a) { asm volatile("mbarrier.arrive.shared::cluster.b64 _, [%0];" :: "r"(a) : "memory"); }
__device__ __forceinline__ bool mbar_try(uint32_t a, uint32_t ph) {
    uint32_t ok;
    asm volatile("{\n.reg .pred p;\nmbarrier.try_wait.parity.shared::cta.b64 p, [%1], %2;\nselp.u32 %0, 1, 0, p;\n}" : "=r"(ok) : "r"(a), "r"(ph) : "memory");
    return ok;
}
__device__ __forceinline__ void mbar_wait(uint32_t a, uint32_t ph) {
    int n = 1 << 22;
#pragma unroll 1
    do { n = __all_sync(0xffffffffu, mbar_try(a, ph)) ? 0 : n - 1; } while (n > 0);
}
__device__ __forceinline__ bool elect_one() {
    uint32_t p;
    asm volatile("{\n.reg .pred P;\nelect.sync _|P, 0xffffffff;\nselp.u32 %0, 1, 0, P;\n}" : "=r"(p));
    return p;
}
__device__ __forceinline__ void signal_cnt(int c) {
    asm volatile("fence.release.gpu;\nred.relaxed.gpu.global.add.u32 [%0], 1;" :: "l"(g_cnt + c * 8) : "memory");
}
__device__ __forceinline__ void wait_cnt(int c, unsigned target, int ns) {
#pragma unroll 1
    for (int n = 0; n < 2000000; n++) {
        unsigned v;
        asm volatile("ld.relaxed.gpu.global.u32 %0, [%1];" : "=r"(v) : "l"(g_cnt + c * 8) : "memory");
        if (__all_sync(0xffffffffu, (int)(v - target) >= 0)) break;
        __nanosleep(ns);
    }
}
__device__ __forceinline__ uint32_t ld_epoch() {
    uint32_t e;
    asm volatile("ld.relaxed.gpu.global.u32 %0, [%1];" : "=r"(e) : "l"(g_epoch + blockIdx.x) : "memory");
    return e;
}
__device__ __forceinline__ void st_tagged(void* p, uint32_t v, uint32_t tag) {
    asm volatile("st.relaxed.gpu.global.b64 [%0], %1;" :: "l"(p), "l"((unsigned long long)tag << 32 | v) : "memory");
}
__device__ __forceinline__ uint32_t ld_tagged2(const ulonglong2* p, uint32_t tag, uint32_t& a, uint32_t& b) {
    unsigned long long u, v;
    asm volatile("ld.relaxed.gpu.global.v2.b64 {%0,%1}, [%2];" : "=l"(u), "=l"(v) : "l"(p) : "memory");
    a = (uint32_t)u; b = (uint32_t)v;
    return ((uint32_t)(u >> 32) ^ tag) | ((uint32_t)(v >> 32) ^ tag);
}
__device__ __forceinline__ void tma2d(uint32_t dst, const CUtensorMap* m, int c0, int c1, uint32_t bar) {
    asm volatile("cp.async.bulk.tensor.2d.shared::cluster.global.mbarrier::complete_tx::bytes [%0], [%1, {%3, %4}], [%2];"
                 :: "r"(dst), "l"(m), "r"(bar), "r"(c0), "r"(c1) : "memory");
}
__device__ __forceinline__ void tma2d_mc(uint32_t dst, const CUtensorMap* m, int c0, int c1, uint32_t bar) {
    asm volatile("cp.async.bulk.tensor.2d.shared::cluster.global.mbarrier::complete_tx::bytes.multicast::cluster [%0], [%1, {%3, %4}], [%2], %5;"
                 :: "r"(dst), "l"(m), "r"(bar), "r"(c0), "r"(c1), "h"((uint16_t)3) : "memory");
}
__device__ __forceinline__ void bulk_load(uint32_t dst, const void* src, int bytes, uint32_t bar) {
    asm volatile("cp.async.bulk.shared::cluster.global.mbarrier::complete_tx::bytes [%0], [%1], %2, [%3];"
                 :: "r"(dst), "l"(src), "r"(bytes), "r"(bar) : "memory");
}
__device__ __forceinline__ void bar_sync(int id, int n) { asm volatile("bar.sync %0, %1;" :: "r"(id), "r"(n) : "memory"); }
__device__ __forceinline__ void fence_async_smem() { asm volatile("fence.proxy.async.shared::cta;" ::: "memory"); }
__device__ __forceinline__ void fence_async_all() { asm volatile("fence.acquire.gpu;\nfence.proxy.async.global;" ::: "memory"); }
__device__ __forceinline__ void wg_fence() { asm volatile("wgmma.fence.sync.aligned;" ::: "memory"); }
__device__ __forceinline__ void wg_commit() { asm volatile("wgmma.commit_group.sync.aligned;" ::: "memory"); }
template <int N> __device__ __forceinline__ void wg_wait() { asm volatile("wgmma.wait_group.sync.aligned %0;" :: "n"(N) : "memory"); }
template <int N> __device__ __forceinline__ void pin(float* d) {
#pragma unroll
    for (int i = 0; i < N; i++) asm volatile("" : "+f"(d[i]) :: "memory");
}
template <int N> __device__ __forceinline__ void pin(uint32_t* d) {
#pragma unroll
    for (int i = 0; i < N; i++) asm volatile("" : "+r"(d[i]) :: "memory");
}
constexpr uint32_t SMEM_BASE = 1024;
__device__ __forceinline__ uint64_t mkdesc(uint32_t off, uint32_t lbo, uint32_t sbo, uint32_t swz) {
    return (uint64_t)((SMEM_BASE + off) >> 4) | ((uint64_t)(lbo >> 4) << 16) | ((uint64_t)(sbo >> 4) << 32) | ((uint64_t)swz << 62);
}
__device__ __forceinline__ float ex2f(float x) { float y; asm("ex2.approx.ftz.f32 %0, %1;" : "=f"(y) : "f"(x)); return y; }
__device__ __forceinline__ float rcpf(float x) { float y; asm("rcp.approx.ftz.f32 %0, %1;" : "=f"(y) : "f"(x)); return y; }
__device__ __forceinline__ uint32_t pack_bf16(float lo, float hi) { uint32_t r; asm("cvt.rn.bf16x2.f32 %0, %1, %2;" : "=r"(r) : "f"(hi), "f"(lo)); return r; }
__device__ __forceinline__ float bf_lo(uint32_t v) { return __uint_as_float(v << 16); }
__device__ __forceinline__ float bf_hi(uint32_t v) { return __uint_as_float(v & 0xFFFF0000u); }
__device__ __forceinline__ float bf_round(float x) { return __bfloat162float(__float2bfloat16_rn(x)); }
__device__ __forceinline__ float siluf(float g) { return g * rcpf(1.0f + ex2f(g * -1.4426950408889634f)); }

__device__ __forceinline__ void wgmma_ss_n256(float* d, uint64_t da, uint64_t db, int acc) {
    asm volatile("{\n.reg .pred p;\nsetp.ne.b32 p, %130, 0;\nwgmma.mma_async.sync.aligned.m64n256k16.f32.bf16.bf16 {"
        "%0,%1,%2,%3,%4,%5,%6,%7,%8,%9,%10,%11,%12,%13,%14,%15,%16,%17,%18,%19,%20,%21,%22,%23,%24,%25,%26,%27,%28,%29,%30,%31,%32,%33,%34,%35,%36,%37,%38,%39,"
        "%40,%41,%42,%43,%44,%45,%46,%47,%48,%49,%50,%51,%52,%53,%54,%55,%56,%57,%58,%59,%60,%61,%62,%63,%64,%65,%66,%67,%68,%69,%70,%71,%72,%73,%74,%75,%76,"
        "%77,%78,%79,%80,%81,%82,%83,%84,%85,%86,%87,%88,%89,%90,%91,%92,%93,%94,%95,%96,%97,%98,%99,%100,%101,%102,%103,%104,%105,%106,%107,%108,%109,%110,"
        "%111,%112,%113,%114,%115,%116,%117,%118,%119,%120,%121,%122,%123,%124,%125,%126,%127"
        "}, %128, %129, p, 1, 1, 0, 1;\n}\n"
        : "+f"(d[0]),"+f"(d[1]),"+f"(d[2]),"+f"(d[3]),"+f"(d[4]),"+f"(d[5]),"+f"(d[6]),"+f"(d[7]),"+f"(d[8]),"+f"(d[9]),"+f"(d[10]),"+f"(d[11]),"+f"(d[12]),
          "+f"(d[13]),"+f"(d[14]),"+f"(d[15]),"+f"(d[16]),"+f"(d[17]),"+f"(d[18]),"+f"(d[19]),"+f"(d[20]),"+f"(d[21]),"+f"(d[22]),"+f"(d[23]),"+f"(d[24]),
          "+f"(d[25]),"+f"(d[26]),"+f"(d[27]),"+f"(d[28]),"+f"(d[29]),"+f"(d[30]),"+f"(d[31]),"+f"(d[32]),"+f"(d[33]),"+f"(d[34]),"+f"(d[35]),"+f"(d[36]),
          "+f"(d[37]),"+f"(d[38]),"+f"(d[39]),"+f"(d[40]),"+f"(d[41]),"+f"(d[42]),"+f"(d[43]),"+f"(d[44]),"+f"(d[45]),"+f"(d[46]),"+f"(d[47]),"+f"(d[48]),
          "+f"(d[49]),"+f"(d[50]),"+f"(d[51]),"+f"(d[52]),"+f"(d[53]),"+f"(d[54]),"+f"(d[55]),"+f"(d[56]),"+f"(d[57]),"+f"(d[58]),"+f"(d[59]),"+f"(d[60]),
          "+f"(d[61]),"+f"(d[62]),"+f"(d[63]),"+f"(d[64]),"+f"(d[65]),"+f"(d[66]),"+f"(d[67]),"+f"(d[68]),"+f"(d[69]),"+f"(d[70]),"+f"(d[71]),"+f"(d[72]),
          "+f"(d[73]),"+f"(d[74]),"+f"(d[75]),"+f"(d[76]),"+f"(d[77]),"+f"(d[78]),"+f"(d[79]),"+f"(d[80]),"+f"(d[81]),"+f"(d[82]),"+f"(d[83]),"+f"(d[84]),
          "+f"(d[85]),"+f"(d[86]),"+f"(d[87]),"+f"(d[88]),"+f"(d[89]),"+f"(d[90]),"+f"(d[91]),"+f"(d[92]),"+f"(d[93]),"+f"(d[94]),"+f"(d[95]),"+f"(d[96]),
          "+f"(d[97]),"+f"(d[98]),"+f"(d[99]),"+f"(d[100]),"+f"(d[101]),"+f"(d[102]),"+f"(d[103]),"+f"(d[104]),"+f"(d[105]),"+f"(d[106]),"+f"(d[107]),
          "+f"(d[108]),"+f"(d[109]),"+f"(d[110]),"+f"(d[111]),"+f"(d[112]),"+f"(d[113]),"+f"(d[114]),"+f"(d[115]),"+f"(d[116]),"+f"(d[117]),"+f"(d[118]),
          "+f"(d[119]),"+f"(d[120]),"+f"(d[121]),"+f"(d[122]),"+f"(d[123]),"+f"(d[124]),"+f"(d[125]),"+f"(d[126]),"+f"(d[127])
        : "l"(da), "l"(db), "r"(acc));
}
__device__ __forceinline__ void wgmma_ss_n128(float* d, uint64_t da, uint64_t db, int acc) {
    asm volatile("{\n.reg .pred p;\nsetp.ne.b32 p, %66, 0;\nwgmma.mma_async.sync.aligned.m64n128k16.f32.bf16.bf16 {"
        "%0,%1,%2,%3,%4,%5,%6,%7,%8,%9,%10,%11,%12,%13,%14,%15,%16,%17,%18,%19,%20,%21,%22,%23,%24,%25,%26,%27,%28,%29,%30,%31,%32,%33,%34,%35,%36,%37,%38,%39,"
        "%40,%41,%42,%43,%44,%45,%46,%47,%48,%49,%50,%51,%52,%53,%54,%55,%56,%57,%58,%59,%60,%61,%62,%63"
        "}, %64, %65, p, 1, 1, 0, 1;\n}\n"
        : "+f"(d[0]),"+f"(d[1]),"+f"(d[2]),"+f"(d[3]),"+f"(d[4]),"+f"(d[5]),"+f"(d[6]),"+f"(d[7]),"+f"(d[8]),"+f"(d[9]),"+f"(d[10]),"+f"(d[11]),"+f"(d[12]),
          "+f"(d[13]),"+f"(d[14]),"+f"(d[15]),"+f"(d[16]),"+f"(d[17]),"+f"(d[18]),"+f"(d[19]),"+f"(d[20]),"+f"(d[21]),"+f"(d[22]),"+f"(d[23]),"+f"(d[24]),
          "+f"(d[25]),"+f"(d[26]),"+f"(d[27]),"+f"(d[28]),"+f"(d[29]),"+f"(d[30]),"+f"(d[31]),"+f"(d[32]),"+f"(d[33]),"+f"(d[34]),"+f"(d[35]),"+f"(d[36]),
          "+f"(d[37]),"+f"(d[38]),"+f"(d[39]),"+f"(d[40]),"+f"(d[41]),"+f"(d[42]),"+f"(d[43]),"+f"(d[44]),"+f"(d[45]),"+f"(d[46]),"+f"(d[47]),"+f"(d[48]),
          "+f"(d[49]),"+f"(d[50]),"+f"(d[51]),"+f"(d[52]),"+f"(d[53]),"+f"(d[54]),"+f"(d[55]),"+f"(d[56]),"+f"(d[57]),"+f"(d[58]),"+f"(d[59]),"+f"(d[60]),
          "+f"(d[61]),"+f"(d[62]),"+f"(d[63])
        : "l"(da), "l"(db), "r"(acc));
}
__device__ __forceinline__ void wgmma_ss_n64(float* d, uint64_t da, uint64_t db, int acc) {
    asm volatile("{\n.reg .pred p;\nsetp.ne.b32 p, %34, 0;\nwgmma.mma_async.sync.aligned.m64n64k16.f32.bf16.bf16 {"
        "%0,%1,%2,%3,%4,%5,%6,%7,%8,%9,%10,%11,%12,%13,%14,%15,%16,%17,%18,%19,%20,%21,%22,%23,%24,%25,%26,%27,%28,%29,%30,%31"
        "}, %32, %33, p, 1, 1, 0, 1;\n}\n"
        : "+f"(d[0]),"+f"(d[1]),"+f"(d[2]),"+f"(d[3]),"+f"(d[4]),"+f"(d[5]),"+f"(d[6]),"+f"(d[7]),"+f"(d[8]),"+f"(d[9]),"+f"(d[10]),"+f"(d[11]),"+f"(d[12]),
          "+f"(d[13]),"+f"(d[14]),"+f"(d[15]),"+f"(d[16]),"+f"(d[17]),"+f"(d[18]),"+f"(d[19]),"+f"(d[20]),"+f"(d[21]),"+f"(d[22]),"+f"(d[23]),"+f"(d[24]),
          "+f"(d[25]),"+f"(d[26]),"+f"(d[27]),"+f"(d[28]),"+f"(d[29]),"+f"(d[30]),"+f"(d[31])
        : "l"(da), "l"(db), "r"(acc));
}
__device__ __forceinline__ void wgmma_rs_n64_zero(float* d, const uint32_t* a, uint64_t db) {
    asm volatile("wgmma.mma_async.sync.aligned.m64n64k16.f32.bf16.bf16 {"
        "%0,%1,%2,%3,%4,%5,%6,%7,%8,%9,%10,%11,%12,%13,%14,%15,%16,%17,%18,%19,%20,%21,%22,%23,%24,%25,%26,%27,%28,%29,%30,%31"
        "}, {%32,%33,%34,%35}, %36, 0, 1, 1, 0;\n"
        : "=f"(d[0]),"=f"(d[1]),"=f"(d[2]),"=f"(d[3]),"=f"(d[4]),"=f"(d[5]),"=f"(d[6]),"=f"(d[7]),"=f"(d[8]),"=f"(d[9]),"=f"(d[10]),"=f"(d[11]),"=f"(d[12]),
          "=f"(d[13]),"=f"(d[14]),"=f"(d[15]),"=f"(d[16]),"=f"(d[17]),"=f"(d[18]),"=f"(d[19]),"=f"(d[20]),"=f"(d[21]),"=f"(d[22]),"=f"(d[23]),"=f"(d[24]),
          "=f"(d[25]),"=f"(d[26]),"=f"(d[27]),"=f"(d[28]),"=f"(d[29]),"=f"(d[30]),"=f"(d[31])
        : "r"(a[0]), "r"(a[1]), "r"(a[2]), "r"(a[3]), "l"(db));
}
__device__ __forceinline__ void wgmma_rs_n64_acc(float* d, const uint32_t* a, uint64_t db) {
    asm volatile("wgmma.mma_async.sync.aligned.m64n64k16.f32.bf16.bf16 {"
        "%0,%1,%2,%3,%4,%5,%6,%7,%8,%9,%10,%11,%12,%13,%14,%15,%16,%17,%18,%19,%20,%21,%22,%23,%24,%25,%26,%27,%28,%29,%30,%31"
        "}, {%32,%33,%34,%35}, %36, 1, 1, 1, 0;\n"
        : "+f"(d[0]),"+f"(d[1]),"+f"(d[2]),"+f"(d[3]),"+f"(d[4]),"+f"(d[5]),"+f"(d[6]),"+f"(d[7]),"+f"(d[8]),"+f"(d[9]),"+f"(d[10]),"+f"(d[11]),"+f"(d[12]),
          "+f"(d[13]),"+f"(d[14]),"+f"(d[15]),"+f"(d[16]),"+f"(d[17]),"+f"(d[18]),"+f"(d[19]),"+f"(d[20]),"+f"(d[21]),"+f"(d[22]),"+f"(d[23]),"+f"(d[24]),
          "+f"(d[25]),"+f"(d[26]),"+f"(d[27]),"+f"(d[28]),"+f"(d[29]),"+f"(d[30]),"+f"(d[31])
        : "r"(a[0]), "r"(a[1]), "r"(a[2]), "r"(a[3]), "l"(db));
}
__device__ __forceinline__ void wgmma_rs_n24_acc(float* d, const uint32_t* a, uint64_t db) {
    asm volatile("wgmma.mma_async.sync.aligned.m64n24k16.f32.bf16.bf16 {"
        "%0,%1,%2,%3,%4,%5,%6,%7,%8,%9,%10,%11"
        "}, {%12,%13,%14,%15}, %16, 1, 1, 1, 1;\n"
        : "+f"(d[0]),"+f"(d[1]),"+f"(d[2]),"+f"(d[3]),"+f"(d[4]),"+f"(d[5]),"+f"(d[6]),"+f"(d[7]),"+f"(d[8]),"+f"(d[9]),"+f"(d[10]),"+f"(d[11])
        : "r"(a[0]), "r"(a[1]), "r"(a[2]), "r"(a[3]), "l"(db));
}
__device__ __forceinline__ void wgmma_rs_n24_zero(float* d, const uint32_t* a, uint64_t db) {
    asm volatile("wgmma.mma_async.sync.aligned.m64n24k16.f32.bf16.bf16 {"
        "%0,%1,%2,%3,%4,%5,%6,%7,%8,%9,%10,%11"
        "}, {%12,%13,%14,%15}, %16, 0, 1, 1, 1;\n"
        : "=f"(d[0]),"=f"(d[1]),"=f"(d[2]),"=f"(d[3]),"=f"(d[4]),"=f"(d[5]),"=f"(d[6]),"=f"(d[7]),"=f"(d[8]),"=f"(d[9]),"=f"(d[10]),"=f"(d[11])
        : "r"(a[0]), "r"(a[1]), "r"(a[2]), "r"(a[3]), "l"(db));
}

constexpr int OFF_ONES = 131072;
constexpr int OFF_RING = OFF_ONES + 4096;
constexpr int NRING = 5;
constexpr int OFF_B2 = OFF_RING + NRING * 16384;
constexpr int OFF_CS = OFF_B2 + 2048;
constexpr int OFF_RS = OFF_CS + 2560;
constexpr int OFF_BAR = OFF_RS + 1024;
enum { B_FULL = 0, B_STATS = 40, B_KV = 45, B_RING = 53, B_WO = 56, B_O = 57, B_CNT2 = 65,
       B_AFREE = 65, B_ORD = 69, B_QKV = 74, B_CNT4 = 75, B_EMPTY = 75, B_AFREE0 = 80, B_DONE = 81, B_CNT8 = 82, B_TILE = 82, B_OW = 87, B_STATS0 = 89, B_NUM = 100 };
constexpr int OFF_TS = OFF_BAR + 1024;
constexpr int SMEM_BYTES = OFF_BAR + B_NUM * 8;
constexpr unsigned FIXED_MASK = 0xB5;
constexpr float P71 = 2361183241434822606848.0f, M71 = 4.235164736271502e-22f;

__device__ __forceinline__ uint32_t exp2_fixed(float lo, float hi, uint32_t half2) {
    uint32_t y, g, d;
    asm("cvt.pack.sat.s16.s32 %0, %1, %2;" : "=r"(y) : "r"(__float_as_uint(hi)), "r"(__float_as_uint(lo)));
    asm("lop3.b32 %0, %1, 0x007F007F, %2, 0xEA;" : "=r"(g) : "r"(y), "r"(half2));
    asm("fma.rn.bf16x2 %0, %1, %2, %3;" : "=r"(d) : "r"(y), "r"(g), "r"(y & 0xFF80FF80u));
    return d;
}
__device__ __forceinline__ uint32_t k_tile_addr(uint32_t base, int tile) {
    const int c = tile >> 2;
    return base + ((tile & 2) ? 98304 + c * 4096 : (2 * c + 1) * 4096) + (tile & 1) * 2048;
}
constexpr uint32_t POS_STD = 0x76543210u, POS_LAST = 0xB75A9640u;

__global__ void __cluster_dims__(2, 1, 1) __launch_bounds__(640, 1)
mega_kernel(const __nv_bfloat16* __restrict__ x, const __nv_bfloat16* __restrict__ wqkv, const __nv_bfloat16* __restrict__ w1,
            const __nv_bfloat16* __restrict__ w3, __nv_bfloat16* __restrict__ out,
            const __grid_constant__ CUtensorMap mx, const __grid_constant__ CUtensorMap mqkv, const __grid_constant__ CUtensorMap mw1,
            const __grid_constant__ CUtensorMap mw3, const __grid_constant__ CUtensorMap mw2, const __grid_constant__ CUtensorMap mwo,
            uint32_t half2) {
    extern __shared__ __align__(1024) uint8_t smem_raw[];
    const uint32_t sb = __shfl_sync(0xffffffffu, smem_u32(smem_raw), 0);
    if ((sb & 0xFFFFFF) != SMEM_BASE) __trap();
    const uint32_t bars = sb + OFF_BAR, ring = sb + OFF_RING;
    const int tid = threadIdx.x, lane = tid & 31, g = lane >> 2, t4 = lane & 3;
    const int warp = __shfl_sync(0xffffffffu, tid >> 5, 0), wg = warp >> 2, wq = warp & 3;
    const int rank = blockIdx.x & 1, cl = blockIdx.x >> 1;
    const int grp = cl < 4 ? 4 + cl : cl < 36 ? (cl - 4) >> 3 : 4 + (cl - 36) / 7;
    const int rot = cl < 4 ? 7 : cl < 36 ? (cl - 4) & 7 : (cl - 36) % 7;
    const int mblk = rot * 2 + rank;
    const int nq = grp < 4 ? 2 : 1;
    const int qt0 = grp < 4 ? 2 * grp : 4 + grp;
    const int gu0 = (grp < 4 ? 3 * grp : 4 * grp - 4) - nq;
    const int head = blockIdx.x >> 2, qb = blockIdx.x & 3;

    if (elect_one()) {
#pragma unroll
        for (int i = 0; i < 5; i++) { const int b = warp * 5 + i; mbar_init(bars + 8 * b, b < B_CNT2 ? 1 : b < B_CNT4 ? 2 : b < B_CNT8 ? 4 : 8); }
        if (warp == 0) {
            fence_async_smem();
#pragma unroll
            for (int j = 0; j < 2; j++) {
                tma2d(sb + j * 16384, &mx, j * 64, mblk * 128, bars + 8 * (B_FULL + j));
                tma2d(ring + j * 16384, &mqkv, qt0 * 128, j * 64, bars + 8 * (B_FULL + j));
                tma2d(ring + j * 16384 + 8192, &mqkv, qt0 * 128 + 64, j * 64, bars + 8 * (B_FULL + j));
            }
        }
        if (warp < 8) {
#pragma unroll
            for (int i = 0; i < 5; i++) mbar_expect(bars + 8 * (warp * 5 + i), warp * 5 + i < 8 ? 32768 : 16384);
        }
        if (warp == 16) asm volatile("prefetch.tensormap [%0];" :: "l"(rank ? &mw3 : &mw1) : "memory");
        asm volatile("fence.mbarrier_init.release.cluster;" ::: "memory");
    }
    __syncthreads();
    if (tid == 512) TSTAMP(26);
    asm volatile("barrier.cluster.arrive.relaxed.aligned;" ::: "memory");

    if (wg < 4) {
        const int pair = wg >> 1, half = wg & 1;
        const uint32_t epoch = ld_epoch();
        if (pair == 1) {
            const uint32_t tag = epoch + 1;
            const int row = mblk * 128 + grp * 16 + (warp - 8) * 2 + (lane >> 4);
            uint4 v[6];
            const uint32_t* w = reinterpret_cast<const uint32_t*>(v);
#pragma unroll
            for (int j = 0; j < 2; j++) v[4 + j] = __ldg(reinterpret_cast<const uint4*>(wqkv + (size_t)(rot * 64 + (warp - 8) * 8 + j * 4 + (lane >> 3)) * (3 * DM) + qt0 * 128 + rank * 64) + (lane & 7));
#pragma unroll
            for (int j = 0; j < 4; j++) v[j] = __ldg(reinterpret_cast<const uint4*>(x + (size_t)row * DM) + j * 16 + (lane & 15));
            float c[8];
#pragma unroll
            for (int e = 0; e < 4; e++) { c[2 * e] = bf_lo(w[16 + e]) + bf_lo(w[20 + e]); c[2 * e + 1] = bf_hi(w[16 + e]) + bf_hi(w[20 + e]); }
#pragma unroll
            for (int n = 4; n > 1; n >>= 1) {
                const bool up = lane & (4 * n);
#pragma unroll
                for (int e = 0; e < n; e++) c[e] = (up ? c[e + n] : c[e]) + __shfl_xor_sync(0xffffffffu, up ? c[e] : c[e + n], 4 * n);
            }
            asm volatile("st.shared.v2.f32 [%0], {%1,%2};" :: "r"(sb + OFF_CS + 512 + (warp - 8) * 256 + (lane & 7) * 32 + (lane >> 3) * 8), "f"(c[0]), "f"(c[1]) : "memory");
            float sa[4] = {0.f, 0.f, 0.f, 0.f}, sq[4] = {0.f, 0.f, 0.f, 0.f};
#pragma unroll
            for (int j = 0; j < 16; j++) sa[j & 3] += bf_lo(w[j]) + bf_hi(w[j]);
            float mean = ((sa[0] + sa[1]) + (sa[2] + sa[3])) * (1.0f / 32);
#pragma unroll
            for (int j = 0; j < 16; j++) { const float a = bf_lo(w[j]) - mean, b = bf_hi(w[j]) - mean; sq[j & 1] = fmaf(a, a, sq[j & 1]); sq[2 + (j & 1)] = fmaf(b, b, sq[2 + (j & 1)]); }
            float m2 = (sq[0] + sq[1]) + (sq[2] + sq[3]);
#pragma unroll
            for (int d = 1; d < 16; d <<= 1) {
                const float om = __shfl_xor_sync(0xffffffffu, mean, d), o2 = __shfl_xor_sync(0xffffffffu, m2, d), dm = mean - om;
                m2 = fmaf(dm * dm, 16.0f * d, m2 + o2); mean = 0.5f * (mean + om);
            }
            float sd;
            asm("sqrt.approx.f32 %0, %1;" : "=f"(sd) : "f"(bf_round(bf_round(m2 * (1.0f / DM)) + 1e-5f)));
            if ((lane & 15) == 0) st_tagged(reinterpret_cast<unsigned long long*>(g_rs) + row, pack_bf16(mean, sd), tag);
            if (tid == 256) TSTAMP(45);
            bar_sync(6, 256);
            if (warp < 10) {
#pragma unroll
                for (int e = 0; e < 8; e++) asm volatile("ld.shared.f32 %0, [%1];" : "=f"(c[e]) : "r"(sb + OFF_CS + 512 + e * 256 + (tid & 63) * 4));
                st_tagged(reinterpret_cast<unsigned long long*>(g_cs) + (grp * 40 + rot) * 128 + rank * 64 + (tid & 63),
                          __float_as_uint(((c[0] + c[1]) + (c[2] + c[3])) + ((c[4] + c[5]) + (c[6] + c[7]))), tag);
                if (tid == 256) TSTAMP(40);
            }
        }

        uint32_t q[4], qn[6];
        {
            float acc[64];
            const int rowblk = mblk * 2 + half, tile16 = rowblk * 4 + wq;
            const bool rel = wq < 2 && lane == 0, rel2 = wq == 2 && lane == 0;
            uint32_t empty;
            asm("mapa.shared::cluster.u32 %0, %1, %2;" : "=r"(empty) : "r"(bars + 8 * B_EMPTY), "r"(wq & 1));
#pragma unroll 1
            for (int t = pair; t < 5; t += 2) {
                uint32_t po = t == 4 ? POS_LAST : POS_STD, full = bars + 8 * (B_FULL + 8 * t), slot = (0x24130u >> (4 * t)) & 7, prev = 0;
                uint64_t da = mkdesc(half * 8192, 16, 1024, 1), db = mkdesc(OFF_RING, 8192, 1024, 1) + slot * 1024;
                if (tid == 0 && t == 0) TSTAMP(30);
                mbar_wait(full, 0);
                if (t > 0) mbar_wait(bars + 8 * (B_ORD + t - 1), 0);
#pragma unroll 1
                for (int j = 0; j < 8; j++) {
                    wg_fence();
#pragma unroll
                    for (int k = 0; k < 4; k++) wgmma_ss_n128(acc, da + k * 2, db + k * 128, (j | k) != 0);
                    wg_commit();
                    const uint32_t rel_a = empty + prev * 8, rel_b = bars + 8 * (j == 3 ? B_AFREE0 : B_AFREE + (j >> 1) - 1);
                    const bool do_a = j > 0 && rel, do_b = (po & 8) && rel2;
                    prev = slot; slot = slot == NRING - 1 ? 0 : slot + 1; po >>= 4; full += 8;
                    da = mkdesc(half * 8192, 16, 1024, 1) + (po & 7) * 1024; db = mkdesc(OFF_RING, 8192, 1024, 1) + slot * 1024;
                    if (j < 7) mbar_wait(full, 0); else if (rel2) mbar_arrive(bars + 8 * (B_ORD + t));
                    wg_wait<1>();
                    if (do_a) mbar_arrive_remote(rel_a);
                    if (do_b) mbar_arrive(rel_b);
                }
                if (t == 0) {
                    const uint32_t tag = epoch + 1;
                    uint32_t r0, r1, a0, a1, b0, b1;
                    float c[2];
#pragma unroll 1
                    for (int n = 0; n < 2000000; n++) {
                        const ulonglong2* pc = g_cs + grp * 2560 + (lane >> 3) * 64 + warp * 8 + (lane & 7);
                        const uint32_t stale = ld_tagged2(g_rs + mblk * 64 + warp * 8 + (lane & 7), tag, r0, r1) | ld_tagged2(pc, tag, a0, a1) | ld_tagged2(pc + 256, tag, b0, b1);
                        if (__all_sync(0xffffffffu, stale == 0)) break;
                    }
                    c[0] = __uint_as_float(a0) + __uint_as_float(b0); c[1] = __uint_as_float(a1) + __uint_as_float(b1);
#pragma unroll
                    for (int d = 8; d < 32; d <<= 1) { c[0] += __shfl_xor_sync(0xffffffffu, c[0], d); c[1] += __shfl_xor_sync(0xffffffffu, c[1], d); }
                    if (lane < 8) {
                        asm volatile("st.shared.v2.f32 [%0], {%1,%2};" :: "r"(sb + OFF_CS + warp * 64 + lane * 8), "f"(c[0]), "f"(c[1]) : "memory");
                        asm volatile("st.shared.v2.b32 [%0], {%1,%2};" :: "r"(sb + OFF_RS + warp * 64 + lane * 8), "r"(r0), "r"(r1) : "memory");
                    }
                    __syncwarp();
                    if (elect_one()) mbar_arrive(bars + 8 * B_STATS0);
                    if (tid == 0) TSTAMP(32);
                }
                if (t >= 3) {
                    mbar_wait(bars + 8 * B_QKV, 0);
                    const uint4* pq = g_q + (head * 128 + (qb * 8 + wg) * 4 + wq) * 32 + lane;
                    const uint4 v = __ldcg(pq), u = __ldcg(pq + 512);
                    qn[0] = v.x; qn[1] = v.y; qn[2] = v.z; qn[3] = v.w; q[0] = u.x; q[1] = u.y; q[2] = u.z; q[3] = u.w;
                }
                wg_wait<0>();
                if (rel) mbar_arrive_remote(empty + prev * 8);
                if (t >= 3 && rel2) mbar_arrive(bars + 8 * (t == 4 ? B_AFREE + 3 : B_AFREE0));
                pin<64>(acc);
                if (wq == 0 && half == 0 && lane == 0) TSTAMP(2 + 2 * t);
                mbar_wait(bars + 8 * (t ? B_STATS + t : B_STATS0), 0);
                uint32_t rs0, rs1;
                asm volatile("ld.shared.b32 %0, [%1];" : "=r"(rs0) : "r"(sb + OFF_RS + (half * 64 + wq * 16 + g) * 4));
                asm volatile("ld.shared.b32 %0, [%1];" : "=r"(rs1) : "r"(sb + OFF_RS + (half * 64 + wq * 16 + g + 8) * 4));
                const float m0 = bf_lo(rs0), m1 = bf_lo(rs1);
                float d0 = bf_hi(rs0), d1 = bf_hi(rs1);
#pragma unroll
                for (int j = 0; j < 16; j++) {
                    float c0, c1;
                    asm volatile("ld.shared.v2.f32 {%0,%1}, [%2];" : "=f"(c0), "=f"(c1) : "r"(sb + OFF_CS + (t * 128 + j * 8 + t4 * 2) * 4));
                    acc[4 * j] = fmaf(-m0, c0, acc[4 * j]); acc[4 * j + 1] = fmaf(-m0, c1, acc[4 * j + 1]);
                    acc[4 * j + 2] = fmaf(-m1, c0, acc[4 * j + 2]); acc[4 * j + 3] = fmaf(-m1, c1, acc[4 * j + 3]);
                }
                float r0 = __frcp_rn(d0), r1 = __frcp_rn(d1);
                if (t < nq) {
                    const int qt = qt0 + t, h0 = (qt & 3) * 8;
                    if (qt < 4) {
                        r0 *= 0.25f * 1.4426950408889634f * M71; r1 *= 0.25f * 1.4426950408889634f * M71;
                    } else if (qt < 8) {
                        r0 *= ((FIXED_MASK >> (2 * wq)) & 1) ? M71 : P71; r1 *= ((FIXED_MASK >> (2 * wq + 1)) & 1) ? M71 : P71;
                    }
                    uint32_t* p; int s8, sh;
                    if (qt < 8) { p = reinterpret_cast<uint32_t*>(g_k + h0 * 4096) + tile16 * 128 + lane; s8 = 64; sh = 32; }
                    else        { p = reinterpret_cast<uint32_t*>(g_v + h0 * 4096) + tile16 * 64 + lane;  s8 = 32; sh = 8192; }
#pragma unroll
                    for (int hh = 0; hh < 8; hh++) {
                        const float* a = acc + hh * 8;
                        const uint32_t e0 = pack_bf16(a[0] * r0, a[1] * r0), e1 = pack_bf16(a[2] * r1, a[3] * r1);
                        const uint32_t e2 = pack_bf16(a[4] * r0, a[5] * r0), e3 = pack_bf16(a[6] * r1, a[7] * r1);
                        if (qt < 4) g_q[((h0 + hh) * 128 + tile16) * 32 + lane] = make_uint4(e0, e1, e2, e3);
                        else { uint32_t* pp = p + hh * 16384; pp[0] = e0; pp[s8] = e1; pp[sh] = e2; pp[sh + s8] = e3; }
                    }
                } else {
                    uint32_t* p = reinterpret_cast<uint32_t*>(g_h + (rowblk * 28 + gu0 + t) * 512) + wq * 512 + lane;
                    r0 *= -1.4426950408889634f; r1 *= -1.4426950408889634f; d0 *= d0; d1 *= d1;
#pragma unroll
                    for (int j = 0; j < 8; j++) {
                        const float* a = acc + j * 4; const float* b = a + 32;
                        p[j * 32] = pack_bf16(a[0] * b[0] * rcpf(fmaf(ex2f(a[0] * r0), d0, d0)), a[1] * b[1] * rcpf(fmaf(ex2f(a[1] * r0), d0, d0)));
                        p[256 + j * 32] = pack_bf16(a[2] * b[2] * rcpf(fmaf(ex2f(a[2] * r1), d1, d1)), a[3] * b[3] * rcpf(fmaf(ex2f(a[3] * r1), d1, d1)));
                    }
                }
                __syncwarp();
                if (elect_one()) mbar_arrive(bars + 8 * (B_TILE + t));
                if (wq == 0 && half == 0 && lane == 0) TSTAMP(3 + 2 * t);
            }
        }
        const uint64_t db2 = mkdesc(OFF_B2, 128, 256, 0);
        float s[32];
        auto ref_point = [&](int ntile, uint32_t& b0, uint32_t& b1) {
            float m0 = -INFINITY, m1 = -INFINITY, f0 = -INFINITY, f1 = -INFINITY;
#pragma unroll 1
            for (int t = 0; t < ntile; t++) {
                wg_fence();
                wgmma_rs_n64_zero(s, q, mkdesc(k_tile_addr(0, t), 128, 256, 0));
                wg_commit();
                wg_wait<0>();
                pin<32>(s);
#pragma unroll
                for (int i = 0; i < 8; i++) {
                    if ((FIXED_MASK >> i) & 1) { f0 = fmaxf(f0, fmaxf(s[4 * i], s[4 * i + 1])); f1 = fmaxf(f1, fmaxf(s[4 * i + 2], s[4 * i + 3])); }
                    else                       { m0 = fmaxf(m0, fmaxf(s[4 * i], s[4 * i + 1])); m1 = fmaxf(m1, fmaxf(s[4 * i + 2], s[4 * i + 3])); }
                }
            }
            m0 = fmaxf(m0, f0 * P71 * P71); m1 = fmaxf(m1, f1 * P71 * P71);
            m0 = fmaxf(m0, __shfl_xor_sync(0xffffffffu, m0, 1)); m1 = fmaxf(m1, __shfl_xor_sync(0xffffffffu, m1, 1));
            m0 = fmaxf(m0, __shfl_xor_sync(0xffffffffu, m0, 2)); m1 = fmaxf(m1, __shfl_xor_sync(0xffffffffu, m1, 2));
#pragma unroll
            for (int r = 0; r < 2; r++) {
                const float m = -rintf(r ? m1 : m0), mh = bf_round(m), mm = bf_round(m - mh), ml = m - mh - mm;
                const float lo = t4 == 0 ? mh : t4 == 1 ? ml : t4 == 2 ? 1.f : 0.f, hi = t4 == 0 ? mm : t4 == 1 ? 1.f : 0.f;
                (r ? b1 : b0) = pack_bf16(lo * M71, hi * M71);
            }
        };
        uint32_t q2[4];
        int redo = 1;
        mbar_wait(bars + 8 * B_KV, 0);
#pragma unroll 1
        for (int round = -1; round < 2;) {
            if (redo) ref_point(redo, q2[0], q2[1]);
            if (round < 0) {
#pragma unroll
                for (int i = 0; i < 4; i++) { const uint32_t tq = q[i]; q[i] = qn[i]; qn[i] = tq; }
                qn[4] = q2[0]; qn[5] = q2[1];
                q2[2] = __shfl_sync(0xffffffffu, q2[0], 3); q2[3] = __shfl_sync(0xffffffffu, q2[1], 3);
                round = 0;
                continue;
            }
            float o[12]; uint32_t p[16];
#pragma unroll
            for (int i = 0; i < 12; i++) o[i] = 0.f;
            pin<12>(o); pin<4>(q2);
            if (wq == 0 && half == 0 && lane == 0) TSTAMP(12 + 4 * round + pair);
            uint64_t dk0 = mkdesc(4096, 128, 256, 0), dk1 = mkdesc(98304, 128, 256, 0), dv = mkdesc(0, 128, 65536, 0);
#pragma unroll 1
            for (int c = 0; c < 8; c++, dk0 += 512, dk1 += 256, dv += 512 - (256ull << 32)) {
                if (round == 0) mbar_wait(bars + 8 * (B_KV + c), 0);
#pragma unroll
                for (int t = 0; t < 4; t++) {
                    wg_fence();
                    wgmma_rs_n64_zero(s, q, (t & 2 ? dk1 : dk0) + (t & 1) * 128);
                    wgmma_rs_n64_acc(s, q2, db2);
                    wg_commit();
                    wg_wait<0>();
                    pin<32>(s); pin<16>(p);
#pragma unroll
                    for (int i = 0; i < 16; i++) {
                        if ((FIXED_MASK >> (i >> 1)) & 1) p[i] = exp2_fixed(s[2 * i], s[2 * i + 1], half2);
                        else                              p[i] = pack_bf16(ex2f(s[2 * i]), ex2f(s[2 * i + 1]));
                    }
                    wg_fence();
#pragma unroll
                    for (int k = 0; k < 4; k++) wgmma_rs_n24_acc(o, p + 4 * k, dv + (t * 4 + k) * 16);
                    wg_commit();
                }
            }
            wg_wait<0>();
            pin<12>(o);
            if (redo != 32) {
                float chk = (o[8] + o[10]) * 256.f;
#pragma unroll
                for (int i = 0; i < 8; i++) chk += fabsf(o[i]);
                uint32_t bad;
                asm volatile("{\n.reg .pred p, q;\nsetp.geu.f32 q, %1, 0f7F800000;\nbar.red.or.pred p, %2, 128, q;\nselp.u32 %0, 1, 0, p;\n}" : "=r"(bad) : "f"(chk), "r"(1 + wg) : "memory");
                if (__any_sync(0xffffffffu, bad)) { redo = 32; continue; }
            }
            const int rowblk = qb * 8 + round * 4 + wg;
            const float r0 = rcpf(o[8]), r1 = rcpf(o[10]);
            uint32_t* po = reinterpret_cast<uint32_t*>(g_o + (rowblk * 8 + (head >> 2)) * 512) + wq * 512 + (head & 3) * 64 + lane;
            po[0] = pack_bf16(o[0] * r0, o[1] * r0); po[256] = pack_bf16(o[2] * r1, o[3] * r1);
            po[32] = pack_bf16(o[4] * r0, o[5] * r0); po[288] = pack_bf16(o[6] * r1, o[7] * r1);
            if (round == 0) {
                __syncwarp();
                if (elect_one()) mbar_arrive(bars + 8 * (B_OW + pair));
            } else {
                bar_sync(1 + wg, 128);
                if (wq == 0 && elect_one()) { mbar_arrive(bars + 8 * B_DONE); signal_cnt(C_O + rowblk); }
            }
#pragma unroll
            for (int i = 0; i < 4; i++) q[i] = qn[i];
            q2[0] = qn[4]; q2[1] = qn[5];
            redo = 0;
            if (wq == 0 && half == 0 && lane == 0) TSTAMP(14 + 4 * round + pair);
            round++;
        }
    } else {
        uint32_t tag;
        if (wq == 0) {
            asm volatile("barrier.cluster.wait.aligned;" ::: "memory");
            if (tid == 512) TSTAMP(27);
            uint32_t slot = 2, ph = 1;
#pragma unroll 1
            for (int n = 2; n < 40; n++) {
                const int t = n >> 3, j = n & 7;
                const int kc = (n < 32 ? j : (POS_LAST >> (4 * j)) & 7) * 64;
                const CUtensorMap* m = t < nq ? &mqkv : rank ? &mw3 : &mw1;
                const int col = t < nq ? (qt0 + t) * 128 + rank * 64 : (gu0 + t) * 64;
                const uint32_t dst = ring + slot * 16384 + rank * 8192, fb = bars + 8 * (B_FULL + n);
                if (n < 8 && elect_one()) tma2d(sb + n * 16384, &mx, kc, mblk * 128, fb);
                mbar_wait(bars + 8 * (B_EMPTY + slot), ph);
                if (elect_one()) { TS2(0, n); tma2d_mc(dst, m, col, kc, fb); }
                if (++slot == NRING) { slot = 0; ph ^= 1; }
            }
            tag = ld_epoch() + 1;
        } else if (wq == 1) {
            tag = ld_epoch() + 1;
            mbar_wait(bars + 8 * B_STATS0, 0);
#pragma unroll 1
            for (int t = 1; t < 5; t++) {
                float a[4];
#pragma unroll 1
                for (int n = 0; n < 2000000; n++) {
                    uint32_t stale = 0;
                    a[0] = a[1] = a[2] = a[3] = 0.f;
#pragma unroll
                    for (int i = 0; i < 16; i++) {
                        uint32_t u, v;
                        stale |= ld_tagged2(g_cs + (grp * 5 + t) * 512 + i * 32 + lane, tag, u, v);
                        a[(i & 1) * 2] += __uint_as_float(u); a[(i & 1) * 2 + 1] += __uint_as_float(v);
                    }
                    if (__all_sync(0xffffffffu, stale == 0)) break;
                    __nanosleep(400);
                }
                asm volatile("st.shared.v2.f32 [%0], {%1,%2};" :: "r"(sb + OFF_CS + t * 512 + lane * 8), "f"(a[0]), "f"(a[1]) : "memory");
                asm volatile("st.shared.v2.f32 [%0], {%1,%2};" :: "r"(sb + OFF_CS + t * 512 + 256 + lane * 8), "f"(a[2]), "f"(a[3]) : "memory");
                __syncwarp();
                if (elect_one()) { mbar_arrive(bars + 8 * (B_STATS + t)); TSTAMP(32 + t); }
            }
        } else {
            tag = ld_epoch() + 1;
            mbar_wait(bars + 8 * (B_FULL + wq - 1), 0);
#pragma unroll 1
            for (int t = wq - 1; t < 5; t += 2) {
                const __nv_bfloat16* src; int ld;
                if (t < nq) { src = wqkv + (qt0 + t) * 128 + rank * 64; ld = 3 * DM; }
                else        { src = (rank ? w3 : w1) + (gu0 + t) * 64; ld = FF; }
                src += (size_t)(rot * 64 + (lane >> 3)) * ld + (lane & 7) * 8;
                uint4 v[16];
                const uint32_t* w = reinterpret_cast<const uint32_t*>(v);
#pragma unroll
                for (int j = 0; j < 16; j++) v[j] = __ldg(reinterpret_cast<const uint4*>(src + (size_t)j * 4 * ld));
                float c[8];
#pragma unroll
                for (int e = 0; e < 4; e++) {
                    float a = 0.f, b = 0.f;
#pragma unroll
                    for (int j = 0; j < 16; j++) { a += bf_lo(w[4 * j + e]); b += bf_hi(w[4 * j + e]); }
                    c[2 * e] = a; c[2 * e + 1] = b;
                }
#pragma unroll
                for (int n = 4; n > 1; n >>= 1) {
                    const bool up = lane & (4 * n);
#pragma unroll
                    for (int e = 0; e < n; e++) c[e] = (up ? c[e + n] : c[e]) + __shfl_xor_sync(0xffffffffu, up ? c[e] : c[e + n], 4 * n);
                }
                unsigned long long* dst = reinterpret_cast<unsigned long long*>(g_cs) + ((grp * 5 + t) * 8 + rot) * 128 + rank * 64 + (lane & 7) * 8 + (lane >> 3) * 2;
                st_tagged(dst, __float_as_uint(c[0]), tag); st_tagged(dst + 1, __float_as_uint(c[1]), tag);
                if (lane == 0) TSTAMP(40 + t);
            }
        }
        if (wq == 3) {
#pragma unroll 1
            for (int i = lane; i < 256; i += 32) asm volatile("st.shared.v4.b32 [%0], {%1,%1,%1,%1};" :: "r"(sb + OFF_ONES + i * 16), "r"(0x3F803F80u) : "memory");
#pragma unroll 1
            for (int i = lane; i < 128; i += 32) {
                const bool fx = (FIXED_MASK >> (i >> 4)) & 1;
                uint32_t a = fx ? pack_bf16(M71, M71) : pack_bf16(P71, P71);
                uint32_t b = fx ? pack_bf16(M71, 47.0f * M71) : pack_bf16(P71, -79.5f * P71);
                uint32_t c = fx ? 0u : pack_bf16(0.08214f * P71, 0.f);
                if (i & 8) a = b = c = 0;
                asm volatile("st.shared.v4.b32 [%0], {%1,%2,%3,%4};" :: "r"(sb + OFF_B2 + i * 16), "r"(a), "r"(b), "r"(c), "r"(0) : "memory");
            }
            fence_async_smem();
            __syncwarp();
            if (elect_one()) mbar_arrive(bars + 8 * B_QKV);
        } else if (wq == 1) {
#pragma unroll 1
            for (int i = 0; i < 3; i++) wait_cnt(C_QKV + i * 4 + (head >> 3), 16 * tag, 100);
            fence_async_all();
            if (elect_one()) { mbar_arrive(bars + 8 * B_QKV); TSTAMP(29); }
            const uint8_t* gk = reinterpret_cast<const uint8_t*>(g_k + head * 4096);
            const uint8_t* gv = reinterpret_cast<const uint8_t*>(g_v + head * 4096);
#pragma unroll 1
            for (int c = 0; c < 8; c++) {
                if (!(c & 1)) mbar_wait(bars + 8 * (c ? B_AFREE + (c >> 1) : B_AFREE0), 0);
                if (elect_one()) {
                    const uint32_t b = bars + 8 * (B_KV + c);
                    mbar_expect(b, 16384);
                    bulk_load(sb + (2 * c + 1) * 4096, gk + c * 8192, 4096, b);
                    bulk_load(sb + 2 * c * 4096, gv + c * 4096, 4096, b);
                    bulk_load(sb + 65536 + c * 4096, gv + 32768 + c * 4096, 4096, b);
                    bulk_load(sb + 98304 + c * 4096, gk + c * 8192 + 4096, 4096, b);
                }
            }
        } else if (wq == 2) {
#pragma unroll 1
            for (int t = 0; t < 5; t++) {
                mbar_wait(bars + 8 * (B_TILE + t), 0);
                if (elect_one()) signal_cnt(t < nq ? C_QKV + qt0 + t : C_H + mblk);
            }
        }
        pin<1>(&tag);
        bar_sync(5, 128);
        if (tid == 639) g_epoch[blockIdx.x] = tag;
        const int cb = blockIdx.x & 7, pr = blockIdx.x >> 3;
        const int rb0 = (pr >> 2) * 8 + (pr & 3);
        uint32_t gate[2][16];
        {
            float dn[64];
            auto load_stage = [&](int kb, int st) {
                const uint32_t b = bars + 8 * (B_RING + st), dst = ring + st * 24576;
                mbar_expect(b, 24576);
                bulk_load(dst, g_h + (rb0 * 28 + kb) * 512, 8192, b);
                bulk_load(dst + 8192, g_h + ((rb0 + 4) * 28 + kb) * 512, 8192, b);
                tma2d(dst + 16384, &mw2, cb * 64, kb * 64, b);
            };
            if (wq == 0) {
                wait_cnt(C_H + (rb0 >> 1), 28 * tag, 200);
                wait_cnt(C_H + (rb0 >> 1) + 2, 28 * tag, 200);
                if (elect_one()) { TSTAMP(20); fence_async_all(); load_stage(0, 0); load_stage(1, 1); }
            }
            int st = 0; uint32_t ph = 0;
#pragma unroll 1
            for (int kb = 0; kb < 28; kb++) {
                mbar_wait(bars + 8 * (B_RING + st), ph);
                const uint64_t da = mkdesc(OFF_RING + st * 24576, 128, 1024, 0), db = mkdesc(OFF_RING + st * 24576 + 16384, 8192, 1024, 1);
                wg_fence();
#pragma unroll
                for (int k = 0; k < 4; k++) { wgmma_ss_n64(dn, da + k * 16, db + k * 128, (kb | k) != 0); wgmma_ss_n64(dn + 32, da + 512 + k * 16, db + k * 128, (kb | k) != 0); }
                wg_commit();
                wg_wait<1>();
                if (wq == 0 && kb < 26 && elect_one()) load_stage(kb + 2, st == 0 ? 2 : st - 1);
                if (++st == 3) { st = 0; ph ^= 1; }
            }
            wg_wait<0>();
            pin<64>(dn);
#pragma unroll
            for (int i = 0; i < 32; i++) gate[i >> 4][i & 15] = pack_bf16(siluf(dn[2 * i]), siluf(dn[2 * i + 1]));
        }
        float acc[32];
        if (tid == 512) TSTAMP(21);
        const uint32_t bar_wo = bars + 8 * B_WO;
        if (wq == 0 && elect_one()) {
            mbar_expect(bar_wo, 65536);
#pragma unroll 1
            for (int i = 0; i < 8; i++) tma2d(ring + i * 8192, &mwo, cb * 64, i * 64, bar_wo);
        }
        if (wq >= 2) {
            mbar_wait(bars + 8 * (B_OW + wq - 2), 0);
            if (elect_one()) {
                signal_cnt(C_O + qb * 8 + 2 * wq - 4);
                asm volatile("red.relaxed.gpu.global.add.u32 [%0], 1;" :: "l"(g_cnt + (C_O + qb * 8 + 2 * wq - 3) * 8) : "memory");
            }
        }
#pragma unroll 1
        for (int tl = 0; tl < 2; tl++) {
            const int rb = rb0 + 4 * tl;
            uint32_t xr[16];
            const uint32_t* px = reinterpret_cast<const uint32_t*>(x + (size_t)(rb * 64 + wq * 16 + g) * DM + cb * 64) + t4;
#pragma unroll
            for (int j = 0; j < 8; j++) { xr[2 * j] = __ldg(px + j * 4); xr[2 * j + 1] = __ldg(px + 8 * DM / 2 + j * 4); }
            if (wq == 0) {
                if (tl == 1) mbar_wait(bars + 8 * B_DONE, 0);
                wait_cnt(C_O + rb, 32 * tag, tl ? 20 : 200);
                if (elect_one()) {
                    fence_async_all();
                    TSTAMP(22 + 2 * tl);
#pragma unroll 1
                    for (int i = 0; i < (tl ? 8 : 2); i++) {
                        mbar_expect(bars + 8 * (B_O + i), 8192);
                        bulk_load((tl ? sb : ring + 65536) + i * 8192, g_o + (rb * 8 + i) * 512, 8192, bars + 8 * (B_O + i));
                    }
                }
            }
            if (tl == 0) mbar_wait(bar_wo, 0);
#pragma unroll 1
            for (int kb = 0; kb < 8; kb++) {
                mbar_wait(bars + 8 * (B_O + kb), tl);
                const uint32_t a = tl == 0 ? OFF_RING + 65536 + (kb & 1) * 8192 : kb * 8192;
                const uint64_t da = mkdesc(a, 128, 1024, 0), db = mkdesc(OFF_RING + kb * 8192, 8192, 1024, 1);
                wg_fence();
#pragma unroll
                for (int k = 0; k < 4; k++) wgmma_ss_n64(acc, da + k * 16, db + k * 128, (kb | k) != 0);
                wg_commit();
                if (tl == 0) {
                    wg_wait<0>();
                    bar_sync(5, 128);
                    if (wq == 0 && kb < 6 && elect_one()) { mbar_expect(bars + 8 * (B_O + kb + 2), 8192); bulk_load(sb + a, g_o + (rb * 8 + kb + 2) * 512, 8192, bars + 8 * (B_O + kb + 2)); }
                }
            }
            wg_wait<0>();
            pin<32>(acc);
            uint32_t* po = reinterpret_cast<uint32_t*>(out + (size_t)(rb * 64 + wq * 16 + g) * DM + cb * 64) + t4;
#pragma unroll
            for (int i = 0; i < 16; i++) {
                const uint32_t r = pack_bf16(fmaf(acc[2 * i], bf_lo(gate[0][i]), bf_lo(xr[i])), fmaf(acc[2 * i + 1], bf_hi(gate[0][i]), bf_hi(xr[i])));
                po[(i & 1) * (8 * DM / 2) + (i >> 1) * 4] = r;
                gate[0][i] = gate[1][i];
            }
            if (tid == 512) TSTAMP(23 + 2 * tl);
        }
    }
}

typedef CUresult (*EncodeFn)(CUtensorMap*, CUtensorMapDataType, cuuint32_t, void*, const cuuint64_t*, const cuuint64_t*, const cuuint32_t*,
                             const cuuint32_t*, CUtensorMapInterleave, CUtensorMapSwizzle, CUtensorMapL2promotion, CUtensorMapFloatOOBfill);

void make_map(EncodeFn fn, CUtensorMap* m, const void* p, int rows, int cols, int box_rows) {
    cuuint64_t dims[2] = {(cuuint64_t)cols, (cuuint64_t)rows};
    cuuint64_t strides[1] = {(cuuint64_t)cols * 2};
    cuuint32_t box[2] = {64, (cuuint32_t)box_rows};
    cuuint32_t es[2] = {1, 1};
    fn(m, CU_TENSOR_MAP_DATA_TYPE_BFLOAT16, 2, const_cast<void*>(p), dims, strides, box, es, CU_TENSOR_MAP_INTERLEAVE_NONE,
       CU_TENSOR_MAP_SWIZZLE_128B, CU_TENSOR_MAP_L2_PROMOTION_L2_128B, CU_TENSOR_MAP_FLOAT_OOB_FILL_NONE);
}

}

extern "C" void kernel_launch(void* const* d_in, const int* in_sizes, int n_in, void* d_out, int out_size) {
    const __nv_bfloat16* x = (const __nv_bfloat16*)d_in[0];
    static EncodeFn fn = nullptr;
    if (!fn) {
        cudaDriverEntryPointQueryResult qr;
        cudaGetDriverEntryPoint("cuTensorMapEncodeTiled", (void**)&fn, cudaEnableDefault, &qr);
        cudaFuncSetAttribute(mega_kernel, cudaFuncAttributeMaxDynamicSharedMemorySize, SMEM_BYTES);
    }
    CUtensorMap mx, mqkv, mw1, mw3, mw2, mwo;
    make_map(fn, &mx, d_in[0], SEQ, DM, 128);
    make_map(fn, &mqkv, d_in[1], DM, 3 * DM, 64);
    make_map(fn, &mwo, d_in[2], DM, DM, 64);
    make_map(fn, &mw1, d_in[4], DM, FF, 64);
    make_map(fn, &mw3, d_in[5], DM, FF, 64);
    make_map(fn, &mw2, d_in[6], FF, DM, 64);
    mega_kernel<<<128, 640, SMEM_BYTES, cudaStreamPerThread>>>(x, (const __nv_bfloat16*)d_in[1], (const __nv_bfloat16*)d_in[4], (const __nv_bfloat16*)d_in[5],
                                                               (__nv_bfloat16*)d_out, mx, mqkv, mw1, mw3, mw2, mwo, 0x3F003F00u);
}
```

```cpp
#include <cuda_runtime.h>
#include <cuda_bf16.h>
#include <cuda.h>
#include <stdint.h>

namespace {

constexpr int SEQ = 2048, DM = 512, FF = 1792;

__device__ uint4 g_q[32 * 128 * 32];
__device__ uint4 g_kv[64 * 4096];
__device__ uint4 g_h[32 * 28 * 512];
__device__ uint4 g_o[32 * 8 * 512];
__device__ ulonglong2 g_cs[40 * 8 * 64];
__device__ ulonglong2 g_rs[SEQ / 2];
constexpr int C_QKV = 0, C_H = 12, C_O = 28, C_NUM = 60;
__device__ unsigned g_cnt[C_NUM * 8];
__device__ unsigned g_epoch[128];
#define TSTAMP(i)
#define TS2(k, i)

__device__ __forceinline__ uint32_t smem_u32(const void* p) { return (uint32_t)__cvta_generic_to_shared(p); }
__device__ __forceinline__ void mbar_init(uint32_t a, int c) { asm volatile("mbarrier.init.shared::cta.b64 [%0], %1;" :: "r"(a), "r"(c)); }
__device__ __forceinline__ void mbar_expect(uint32_t a, int b) { asm volatile("mbarrier.arrive.expect_tx.shared::cta.b64 _, [%0], %1;" :: "r"(a), "r"(b) : "memory"); }
__device__ __forceinline__ void mbar_arrive(uint32_t a) { asm volatile("mbarrier.arrive.shared::cta.b64 _, [%0];" :: "r"(a) : "memory"); }
__device__ __forceinline__ void mbar_arrive_remote(uint32_t a) { asm volatile("mbarrier.arrive.shared::cluster.b64 _, [%0];" :: "r"(a) : "memory"); }
__device__ __forceinline__ bool mbar_try(uint32_t a, uint32_t ph) {
    uint32_t ok;
    asm volatile("{\n.reg .pred p;\nmbarrier.try_wait.parity.shared::cta.b64 p, [%1], %2;\nselp.u32 %0, 1, 0, p;\n}" : "=r"(ok) : "r"(a), "r"(ph) : "memory");
    return ok;
}
__device__ __forceinline__ void mbar_wait(uint32_t a, uint32_t ph) {
    int n = 1 << 22;
#pragma unroll 1
    do { n = __all_sync(0xffffffffu, mbar_try(a, ph)) ? 0 : n - 1; } while (n > 0);
}
__device__ __forceinline__ bool elect_one() {
    uint32_t p;
    asm volatile("{\n.reg .pred P;\nelect.sync _|P, 0xffffffff;\nselp.u32 %0, 1, 0, P;\n}" : "=r"(p));
    return p;
}
__device__ __forceinline__ void signal_cnt(int c) {
    asm volatile("fence.release.gpu;\nred.relaxed.gpu.global.add.u32 [%0], 1;" :: "l"(g_cnt + c * 8) : "memory");
}
__device__ __forceinline__ void wait_cnt(int c, unsigned target, int ns) {
#pragma unroll 1
    for (int n = 0; n < 2000000; n++) {
        unsigned v;
        asm volatile("ld.relaxed.gpu.global.u32 %0, [%1];" : "=r"(v) : "l"(g_cnt + c * 8) : "memory");
        if (__all_sync(0xffffffffu, (int)(v - target) >= 0)) break;
        __nanosleep(ns);
    }
}
__device__ __forceinline__ uint32_t ld_epoch() {
    uint32_t e;
    asm volatile("ld.relaxed.gpu.global.u32 %0, [%1];" : "=r"(e) : "l"(g_epoch + blockIdx.x) : "memory");
    return e;
}
__device__ __forceinline__ void st_tagged(void* p, uint32_t v, uint32_t tag) {
    asm volatile("st.relaxed.gpu.global.b64 [%0], %1;" :: "l"(p), "l"((unsigned long long)tag << 32 | v) : "memory");
}
__device__ __forceinline__ uint32_t ld_tagged2(const ulonglong2* p, uint32_t tag, uint32_t& a, uint32_t& b) {
    unsigned long long u, v;
    asm volatile("ld.relaxed.gpu.global.v2.b64 {%0,%1}, [%2];" : "=l"(u), "=l"(v) : "l"(p) : "memory");
    a = (uint32_t)u; b = (uint32_t)v;
    return ((uint32_t)(u >> 32) ^ tag) | ((uint32_t)(v >> 32) ^ tag);
}
__device__ __forceinline__ void tma2d(uint32_t dst, const CUtensorMap* m, int c0, int c1, uint32_t bar) {
    asm volatile("cp.async.bulk.tensor.2d.shared::cluster.global.mbarrier::complete_tx::bytes [%0], [%1, {%3, %4}], [%2];"
                 :: "r"(dst), "l"(m), "r"(bar), "r"(c0), "r"(c1) : "memory");
}
__device__ __forceinline__ void tma2d_mc(uint32_t dst, const CUtensorMap* m, int c0, int c1, uint32_t bar) {
    asm volatile("cp.async.bulk.tensor.2d.shared::cluster.global.mbarrier::complete_tx::bytes.multicast::cluster [%0], [%1, {%3, %4}], [%2], %5;"
                 :: "r"(dst), "l"(m), "r"(bar), "r"(c0), "r"(c1), "h"((uint16_t)3) : "memory");
}
__device__ __forceinline__ void bulk_load(uint32_t dst, const void* src, int bytes, uint32_t bar) {
    asm volatile("cp.async.bulk.shared::cluster.global.mbarrier::complete_tx::bytes [%0], [%1], %2, [%3];"
                 :: "r"(dst), "l"(src), "r"(bytes), "r"(bar) : "memory");
}
__device__ __forceinline__ void bar_sync(int id, int n) { asm volatile("bar.sync %0, %1;" :: "r"(id), "r"(n) : "memory"); }
__device__ __forceinline__ void fence_async_smem() { asm volatile("fence.proxy.async.shared::cta;" ::: "memory"); }
__device__ __forceinline__ void fence_async_all() { asm volatile("fence.acquire.gpu;\nfence.proxy.async.global;" ::: "memory"); }
__device__ __forceinline__ void wg_fence() { asm volatile("wgmma.fence.sync.aligned;" ::: "memory"); }
__device__ __forceinline__ void wg_commit() { asm volatile("wgmma.commit_group.sync.aligned;" ::: "memory"); }
template <int N> __device__ __forceinline__ void wg_wait() { asm volatile("wgmma.wait_group.sync.aligned %0;" :: "n"(N) : "memory"); }
template <int N> __device__ __forceinline__ void pin(float* d) {
#pragma unroll
    for (int i = 0; i < N; i++) asm volatile("" : "+f"(d[i]) :: "memory");
}
template <int N> __device__ __forceinline__ void pin(uint32_t* d) {
#pragma unroll
    for (int i = 0; i < N; i++) asm volatile("" : "+r"(d[i]) :: "memory");
}
constexpr uint32_t SMEM_BASE = 1024;
__device__ __forceinline__ uint64_t mkdesc(uint32_t off, uint32_t lbo, uint32_t sbo, uint32_t swz) {
    return (uint64_t)((SMEM_BASE + off) >> 4) | ((uint64_t)(lbo >> 4) << 16) | ((uint64_t)(sbo >> 4) << 32) | ((uint64_t)swz << 62);
}
__device__ __forceinline__ float ex2f(float x) { float y; asm("ex2.approx.ftz.f32 %0, %1;" : "=f"(y) : "f"(x)); return y; }
__device__ __forceinline__ float rcpf(float x) { float y; asm("rcp.approx.ftz.f32 %0, %1;" : "=f"(y) : "f"(x)); return y; }
__device__ __forceinline__ uint32_t pack_bf16(float lo, float hi) { uint32_t r; asm("cvt.rn.bf16x2.f32 %0, %1, %2;" : "=r"(r) : "f"(hi), "f"(lo)); return r; }
__device__ __forceinline__ float bf_lo(uint32_t v) { return __uint_as_float(v << 16); }
__device__ __forceinline__ float bf_hi(uint32_t v) { return __uint_as_float(v & 0xFFFF0000u); }
__device__ __forceinline__ float bf_round(float x) { return __bfloat162float(__float2bfloat16_rn(x)); }
__device__ __forceinline__ float siluf(float g) { return g * rcpf(1.0f + ex2f(g * -1.4426950408889634f)); }

__device__ __forceinline__ void wgmma_ss_n256(float* d, uint64_t da, uint64_t db, int acc) {
    asm volatile("{\n.reg .pred p;\nsetp.ne.b32 p, %130, 0;\nwgmma.mma_async.sync.aligned.m64n256k16.f32.bf16.bf16 {"
        "%0,%1,%2,%3,%4,%5,%6,%7,%8,%9,%10,%11,%12,%13,%14,%15,%16,%17,%18,%19,%20,%21,%22,%23,%24,%25,%26,%27,%28,%29,%30,%31,%32,%33,%34,%35,%36,%37,%38,%39,"
        "%40,%41,%42,%43,%44,%45,%46,%47,%48,%49,%50,%51,%52,%53,%54,%55,%56,%57,%58,%59,%60,%61,%62,%63,%64,%65,%66,%67,%68,%69,%70,%71,%72,%73,%74,%75,%76,"
        "%77,%78,%79,%80,%81,%82,%83,%84,%85,%86,%87,%88,%89,%90,%91,%92,%93,%94,%95,%96,%97,%98,%99,%100,%101,%102,%103,%104,%105,%106,%107,%108,%109,%110,"
        "%111,%112,%113,%114,%115,%116,%117,%118,%119,%120,%121,%122,%123,%124,%125,%126,%127"
        "}, %128, %129, p, 1, 1, 0, 1;\n}\n"
        : "+f"(d[0]),"+f"(d[1]),"+f"(d[2]),"+f"(d[3]),"+f"(d[4]),"+f"(d[5]),"+f"(d[6]),"+f"(d[7]),"+f"(d[8]),"+f"(d[9]),"+f"(d[10]),"+f"(d[11]),"+f"(d[12]),
          "+f"(d[13]),"+f"(d[14]),"+f"(d[15]),"+f"(d[16]),"+f"(d[17]),"+f"(d[18]),"+f"(d[19]),"+f"(d[20]),"+f"(d[21]),"+f"(d[22]),"+f"(d[23]),"+f"(d[24]),
          "+f"(d[25]),"+f"(d[26]),"+f"(d[27]),"+f"(d[28]),"+f"(d[29]),"+f"(d[30]),"+f"(d[31]),"+f"(d[32]),"+f"(d[33]),"+f"(d[34]),"+f"(d[35]),"+f"(d[36]),
          "+f"(d[37]),"+f"(d[38]),"+f"(d[39]),"+f"(d[40]),"+f"(d[41]),"+f"(d[42]),"+f"(d[43]),"+f"(d[44]),"+f"(d[45]),"+f"(d[46]),"+f"(d[47]),"+f"(d[48]),
          "+f"(d[49]),"+f"(d[50]),"+f"(d[51]),"+f"(d[52]),"+f"(d[53]),"+f"(d[54]),"+f"(d[55]),"+f"(d[56]),"+f"(d[57]),"+f"(d[58]),"+f"(d[59]),"+f"(d[60]),
          "+f"(d[61]),"+f"(d[62]),"+f"(d[63]),"+f"(d[64]),"+f"(d[65]),"+f"(d[66]),"+f"(d[67]),"+f"(d[68]),"+f"(d[69]),"+f"(d[70]),"+f"(d[71]),"+f"(d[72]),
          "+f"(d[73]),"+f"(d[74]),"+f"(d[75]),"+f"(d[76]),"+f"(d[77]),"+f"(d[78]),"+f"(d[79]),"+f"(d[80]),"+f"(d[81]),"+f"(d[82]),"+f"(d[83]),"+f"(d[84]),
          "+f"(d[85]),"+f"(d[86]),"+f"(d[87]),"+f"(d[88]),"+f"(d[89]),"+f"(d[90]),"+f"(d[91]),"+f"(d[92]),"+f"(d[93]),"+f"(d[94]),"+f"(d[95]),"+f"(d[96]),
          "+f"(d[97]),"+f"(d[98]),"+f"(d[99]),"+f"(d[100]),"+f"(d[101]),"+f"(d[102]),"+f"(d[103]),"+f"(d[104]),"+f"(d[105]),"+f"(d[106]),"+f"(d[107]),
          "+f"(d[108]),"+f"(d[109]),"+f"(d[110]),"+f"(d[111]),"+f"(d[112]),"+f"(d[113]),"+f"(d[114]),"+f"(d[115]),"+f"(d[116]),"+f"(d[117]),"+f"(d[118]),
          "+f"(d[119]),"+f"(d[120]),"+f"(d[121]),"+f"(d[122]),"+f"(d[123]),"+f"(d[124]),"+f"(d[125]),"+f"(d[126]),"+f"(d[127])
        : "l"(da), "l"(db), "r"(acc));
}
__device__ __forceinline__ void wgmma_ss_n128(float* d, uint64_t da, uint64_t db, int acc) {
    asm volatile("{\n.reg .pred p;\nsetp.ne.b32 p, %66, 0;\nwgmma.mma_async.sync.aligned.m64n128k16.f32.bf16.bf16 {"
        "%0,%1,%2,%3,%4,%5,%6,%7,%8,%9,%10,%11,%12,%13,%14,%15,%16,%17,%18,%19,%20,%21,%22,%23,%24,%25,%26,%27,%28,%29,%30,%31,%32,%33,%34,%35,%36,%37,%38,%39,"
        "%40,%41,%42,%43,%44,%45,%46,%47,%48,%49,%50,%51,%52,%53,%54,%55,%56,%57,%58,%59,%60,%61,%62,%63"
        "}, %64, %65, p, 1, 1, 0, 1;\n}\n"
        : "+f"(d[0]),"+f"(d[1]),"+f"(d[2]),"+f"(d[3]),"+f"(d[4]),"+f"(d[5]),"+f"(d[6]),"+f"(d[7]),"+f"(d[8]),"+f"(d[9]),"+f"(d[10]),"+f"(d[11]),"+f"(d[12]),
          "+f"(d[13]),"+f"(d[14]),"+f"(d[15]),"+f"(d[16]),"+f"(d[17]),"+f"(d[18]),"+f"(d[19]),"+f"(d[20]),"+f"(d[21]),"+f"(d[22]),"+f"(d[23]),"+f"(d[24]),
          "+f"(d[25]),"+f"(d[26]),"+f"(d[27]),"+f"(d[28]),"+f"(d[29]),"+f"(d[30]),"+f"(d[31]),"+f"(d[32]),"+f"(d[33]),"+f"(d[34]),"+f"(d[35]),"+f"(d[36]),
          "+f"(d[37]),"+f"(d[38]),"+f"(d[39]),"+f"(d[40]),"+f"(d[41]),"+f"(d[42]),"+f"(d[43]),"+f"(d[44]),"+f"(d[45]),"+f"(d[46]),"+f"(d[47]),"+f"(d[48]),
          "+f"(d[49]),"+f"(d[50]),"+f"(d[51]),"+f"(d[52]),"+f"(d[53]),"+f"(d[54]),"+f"(d[55]),"+f"(d[56]),"+f"(d[57]),"+f"(d[58]),"+f"(d[59]),"+f"(d[60]),
          "+f"(d[61]),"+f"(d[62]),"+f"(d[63])
        : "l"(da), "l"(db), "r"(acc));
}
__device__ __forceinline__ void wgmma_ss_n64(float* d, uint64_t da, uint64_t db, int acc) {
    asm volatile("{\n.reg .pred p;\nsetp.ne.b32 p, %34, 0;\nwgmma.mma_async.sync.aligned.m64n64k16.f32.bf16.bf16 {"
        "%0,%1,%2,%3,%4,%5,%6,%7,%8,%9,%10,%11,%12,%13,%14,%15,%16,%17,%18,%19,%20,%21,%22,%23,%24,%25,%26,%27,%28,%29,%30,%31"
        "}, %32, %33, p, 1, 1, 0, 1;\n}\n"
        : "+f"(d[0]),"+f"(d[1]),"+f"(d[2]),"+f"(d[3]),"+f"(d[4]),"+f"(d[5]),"+f"(d[6]),"+f"(d[7]),"+f"(d[8]),"+f"(d[9]),"+f"(d[10]),"+f"(d[11]),"+f"(d[12]),
          "+f"(d[13]),"+f"(d[14]),"+f"(d[15]),"+f"(d[16]),"+f"(d[17]),"+f"(d[18]),"+f"(d[19]),"+f"(d[20]),"+f"(d[21]),"+f"(d[22]),"+f"(d[23]),"+f"(d[24]),
          "+f"(d[25]),"+f"(d[26]),"+f"(d[27]),"+f"(d[28]),"+f"(d[29]),"+f"(d[30]),"+f"(d[31])
        : "l"(da), "l"(db), "r"(acc));
}
__device__ __forceinline__ void wgmma_rs_n64_zero(float* d, const uint32_t* a, uint64_t db) {
    asm volatile("wgmma.mma_async.sync.aligned.m64n64k16.f32.bf16.bf16 {"
        "%0,%1,%2,%3,%4,%5,%6,%7,%8,%9,%10,%11,%12,%13,%14,%15,%16,%17,%18,%19,%20,%21,%22,%23,%24,%25,%26,%27,%28,%29,%30,%31"
        "}, {%32,%33,%34,%35}, %36, 0, 1, 1, 0;\n"
        : "=f"(d[0]),"=f"(d[1]),"=f"(d[2]),"=f"(d[3]),"=f"(d[4]),"=f"(d[5]),"=f"(d[6]),"=f"(d[7]),"=f"(d[8]),"=f"(d[9]),"=f"(d[10]),"=f"(d[11]),"=f"(d[12]),
          "=f"(d[13]),"=f"(d[14]),"=f"(d[15]),"=f"(d[16]),"=f"(d[17]),"=f"(d[18]),"=f"(d[19]),"=f"(d[20]),"=f"(d[21]),"=f"(d[22]),"=f"(d[23]),"=f"(d[24]),
          "=f"(d[25]),"=f"(d[26]),"=f"(d[27]),"=f"(d[28]),"=f"(d[29]),"=f"(d[30]),"=f"(d[31])
        : "r"(a[0]), "r"(a[1]), "r"(a[2]), "r"(a[3]), "l"(db));
}
__device__ __forceinline__ void wgmma_rs_n64_acc(float* d, const uint32_t* a, uint64_t db) {
    asm volatile("wgmma.mma_async.sync.aligned.m64n64k16.f32.bf16.bf16 {"
        "%0,%1,%2,%3,%4,%5,%6,%7,%8,%9,%10,%11,%12,%13,%14,%15,%16,%17,%18,%19,%20,%21,%22,%23,%24,%25,%26,%27,%28,%29,%30,%31"
        "}, {%32,%33,%34,%35}, %36, 1, 1, 1, 0;\n"
        : "+f"(d[0]),"+f"(d[1]),"+f"(d[2]),"+f"(d[3]),"+f"(d[4]),"+f"(d[5]),"+f"(d[6]),"+f"(d[7]),"+f"(d[8]),"+f"(d[9]),"+f"(d[10]),"+f"(d[11]),"+f"(d[12]),
          "+f"(d[13]),"+f"(d[14]),"+f"(d[15]),"+f"(d[16]),"+f"(d[17]),"+f"(d[18]),"+f"(d[19]),"+f"(d[20]),"+f"(d[21]),"+f"(d[22]),"+f"(d[23]),"+f"(d[24]),
          "+f"(d[25]),"+f"(d[26]),"+f"(d[27]),"+f"(d[28]),"+f"(d[29]),"+f"(d[30]),"+f"(d[31])
        : "r"(a[0]), "r"(a[1]), "r"(a[2]), "r"(a[3]), "l"(db));
}
__device__ __forceinline__ void wgmma_rs_n24_acc(float* d, const uint32_t* a, uint64_t db) {
    asm volatile("wgmma.mma_async.sync.aligned.m64n24k16.f32.bf16.bf16 {"
        "%0,%1,%2,%3,%4,%5,%6,%7,%8,%9,%10,%11"
        "}, {%12,%13,%14,%15}, %16, 1, 1, 1, 1;\n"
        : "+f"(d[0]),"+f"(d[1]),"+f"(d[2]),"+f"(d[3]),"+f"(d[4]),"+f"(d[5]),"+f"(d[6]),"+f"(d[7]),"+f"(d[8]),"+f"(d[9]),"+f"(d[10]),"+f"(d[11])
        : "r"(a[0]), "r"(a[1]), "r"(a[2]), "r"(a[3]), "l"(db));
}
__device__ __forceinline__ void wgmma_rs_n24_zero(float* d, const uint32_t* a, uint64_t db) {
    asm volatile("wgmma.mma_async.sync.aligned.m64n24k16.f32.bf16.bf16 {"
        "%0,%1,%2,%3,%4,%5,%6,%7,%8,%9,%10,%11"
        "}, {%12,%13,%14,%15}, %16, 0, 1, 1, 1;\n"
        : "=f"(d[0]),"=f"(d[1]),"=f"(d[2]),"=f"(d[3]),"=f"(d[4]),"=f"(d[5]),"=f"(d[6]),"=f"(d[7]),"=f"(d[8]),"=f"(d[9]),"=f"(d[10]),"=f"(d[11])
        : "r"(a[0]), "r"(a[1]), "r"(a[2]), "r"(a[3]), "l"(db));
}

constexpr int OFF_ONES = 131072;
constexpr int OFF_RING = OFF_ONES + 4096;
constexpr int NRING = 5;
constexpr int OFF_B2 = OFF_RING + NRING * 16384;
constexpr int OFF_CS = OFF_B2 + 2048;
constexpr int OFF_RS = OFF_CS + 2560;
constexpr int OFF_BAR = OFF_RS + 1024;
enum { B_FULL = 0, B_STATS = 40, B_KV = 45, B_RING = 53, B_WO = 56, B_O = 57, B_CNT2 = 65,
       B_AFREE = 65, B_ORD = 69, B_QKV = 74, B_CNT4 = 75, B_EMPTY = 75, B_AFREE0 = 80, B_DONE = 81, B_CNT8 = 82, B_TILE = 82, B_OW = 87, B_NUM = 100 };
constexpr int OFF_TS = OFF_BAR + 1024;
constexpr int SMEM_BYTES = OFF_BAR + B_NUM * 8;
constexpr unsigned FIXED_MASK = 0xB5;
constexpr float P71 = 2361183241434822606848.0f, M71 = 4.235164736271502e-22f;

__device__ __forceinline__ uint32_t exp2_fixed(float lo, float hi, uint32_t half2) {
    uint32_t y, g, d;
    asm("cvt.pack.sat.s16.s32 %0, %1, %2;" : "=r"(y) : "r"(__float_as_uint(hi)), "r"(__float_as_uint(lo)));
    asm("lop3.b32 %0, %1, 0x007F007F, %2, 0xEA;" : "=r"(g) : "r"(y), "r"(half2));
    asm("fma.rn.bf16x2 %0, %1, %2, %3;" : "=r"(d) : "r"(y), "r"(g), "r"(y & 0xFF80FF80u));
    return d;
}
constexpr uint64_t DK_STEP = 512 - (256ull << 16), DV_STEP = 512 - (256ull << 32);
constexpr uint32_t POS_STD = 0x76543210u, POS_LAST = 0xB75A9640u;

__global__ void __cluster_dims__(2, 1, 1) __launch_bounds__(640, 1)
mega_kernel(const __nv_bfloat16* __restrict__ x, const __nv_bfloat16* __restrict__ wqkv, const __nv_bfloat16* __restrict__ w1,
            const __nv_bfloat16* __restrict__ w3, __nv_bfloat16* __restrict__ out,
            const __grid_constant__ CUtensorMap mx, const __grid_constant__ CUtensorMap mqkv, const __grid_constant__ CUtensorMap mw1,
            const __grid_constant__ CUtensorMap mw3, const __grid_constant__ CUtensorMap mw2, const __grid_constant__ CUtensorMap mwo,
            uint32_t half2) {
    extern __shared__ __align__(1024) uint8_t smem_raw[];
    const uint32_t sb = __shfl_sync(0xffffffffu, smem_u32(smem_raw), 0);
    if ((sb & 0xFFFFFF) != SMEM_BASE) __trap();
    const uint32_t bars = sb + OFF_BAR, ring = sb + OFF_RING;
    const int tid = threadIdx.x, lane = tid & 31, g = lane >> 2, t4 = lane & 3;
    const int warp = __shfl_sync(0xffffffffu, tid >> 5, 0), wg = warp >> 2, wq = warp & 3;
    const int rank = blockIdx.x & 1, cl = blockIdx.x >> 1;
    const int grp = cl < 4 ? 4 + cl : cl < 36 ? (cl - 4) >> 3 : 4 + (cl - 36) / 7;
    const int rot = cl < 4 ? 7 : cl < 36 ? (cl - 4) & 7 : (cl - 36) % 7;
    const int mblk = rot * 2 + rank;
    const int nq = grp < 4 ? 2 : 1;
    const int qt0 = grp < 4 ? 2 * grp : 4 + grp;
    const int gu0 = (grp < 4 ? 3 * grp : 4 * grp - 4) - nq;
    const int head = blockIdx.x >> 2, qb = blockIdx.x & 3;

    if (elect_one()) {
#pragma unroll
        for (int i = 0; i < 5; i++) { const int b = warp * 5 + i; mbar_init(bars + 8 * b, b < B_CNT2 ? 1 : b < B_CNT4 ? 2 : b < B_CNT8 ? 4 : 8); }
        if (warp == 0) {
            fence_async_smem();
#pragma unroll
            for (int j = 0; j < 2; j++) {
                tma2d(sb + j * 16384, &mx, j * 64, mblk * 128, bars + 8 * (B_FULL + j));
                tma2d(ring + j * 16384, &mqkv, qt0 * 128, j * 64, bars + 8 * (B_FULL + j));
                tma2d(ring + j * 16384 + 8192, &mqkv, qt0 * 128 + 64, j * 64, bars + 8 * (B_FULL + j));
            }
        }
        if (warp < 8) {
#pragma unroll
            for (int i = 0; i < 5; i++) mbar_expect(bars + 8 * (warp * 5 + i), warp * 5 + i < 8 ? 32768 : 16384);
        }
        if (warp == 16) asm volatile("prefetch.tensormap [%0];" :: "l"(rank ? &mw3 : &mw1) : "memory");
        asm volatile("fence.mbarrier_init.release.cluster;" ::: "memory");
    }
    __syncthreads();
    if (tid == 512) TSTAMP(26);
    asm volatile("barrier.cluster.arrive.relaxed.aligned;" ::: "memory");

    if (wg < 4) {
        const int pair = wg >> 1, half = wg & 1;
        if (pair == 1) {
            const int row = mblk * 128 + grp * 16 + (warp - 8) * 2 + (lane >> 4);
            uint4 v[6];
            const uint32_t* w = reinterpret_cast<const uint32_t*>(v);
#pragma unroll
            for (int j = 0; j < 2; j++) v[4 + j] = __ldg(reinterpret_cast<const uint4*>(wqkv + (size_t)(rot * 64 + (warp - 8) * 8 + j * 4 + (lane >> 3)) * (3 * DM) + qt0 * 128 + rank * 64) + (lane & 7));
#pragma unroll
            for (int j = 0; j < 4; j++) v[j] = __ldg(reinterpret_cast<const uint4*>(x + (size_t)row * DM) + j * 16 + (lane & 15));
            const uint32_t tag = ld_epoch() + 1;
            float c[8];
#pragma unroll
            for (int e = 0; e < 4; e++) { c[2 * e] = bf_lo(w[16 + e]) + bf_lo(w[20 + e]); c[2 * e + 1] = bf_hi(w[16 + e]) + bf_hi(w[20 + e]); }
#pragma unroll
            for (int n = 4; n > 1; n >>= 1) {
                const bool up = lane & (4 * n);
#pragma unroll
                for (int e = 0; e < n; e++) c[e] = (up ? c[e + n] : c[e]) + __shfl_xor_sync(0xffffffffu, up ? c[e] : c[e + n], 4 * n);
            }
            asm volatile("st.shared.v2.f32 [%0], {%1,%2};" :: "r"(sb + OFF_CS + 512 + (warp - 8) * 256 + (lane & 7) * 32 + (lane >> 3) * 8), "f"(c[0]), "f"(c[1]) : "memory");
            bar_sync(6, 256);
            if (warp < 10) {
#pragma unroll
                for (int e = 0; e < 8; e++) asm volatile("ld.shared.f32 %0, [%1];" : "=f"(c[e]) : "r"(sb + OFF_CS + 512 + e * 256 + (tid & 63) * 4));
                st_tagged(reinterpret_cast<unsigned long long*>(g_cs) + (grp * 40 + rot) * 128 + rank * 64 + (tid & 63),
                          __float_as_uint(((c[0] + c[1]) + (c[2] + c[3])) + ((c[4] + c[5]) + (c[6] + c[7]))), tag);
                if (tid == 256) TSTAMP(40);
            }
            float sa[4] = {0.f, 0.f, 0.f, 0.f}, sq[4] = {0.f, 0.f, 0.f, 0.f};
#pragma unroll
            for (int j = 0; j < 16; j++) sa[j & 3] += bf_lo(w[j]) + bf_hi(w[j]);
            float mean = ((sa[0] + sa[1]) + (sa[2] + sa[3])) * (1.0f / 32);
#pragma unroll
            for (int j = 0; j < 16; j++) { const float a = bf_lo(w[j]) - mean, b = bf_hi(w[j]) - mean; sq[j & 1] = fmaf(a, a, sq[j & 1]); sq[2 + (j & 1)] = fmaf(b, b, sq[2 + (j & 1)]); }
            float m2 = (sq[0] + sq[1]) + (sq[2] + sq[3]);
#pragma unroll
            for (int d = 1; d < 16; d <<= 1) {
                const float om = __shfl_xor_sync(0xffffffffu, mean, d), o2 = __shfl_xor_sync(0xffffffffu, m2, d), dm = mean - om;
                m2 = fmaf(dm * dm, 16.0f * d, m2 + o2); mean = 0.5f * (mean + om);
            }
            float sd;
            asm("sqrt.approx.f32 %0, %1;" : "=f"(sd) : "f"(bf_round(bf_round(m2 * (1.0f / DM)) + 1e-5f)));
            if ((lane & 15) == 0) st_tagged(reinterpret_cast<unsigned long long*>(g_rs) + row, pack_bf16(mean, sd), tag);
            if (tid == 256) TSTAMP(45);
        }

        uint32_t q[4], qn[6];
        {
            float acc[64];
            const int rowblk = mblk * 2 + half, tile16 = rowblk * 4 + wq;
            const bool rel = wq < 2 && lane == 0, rel2 = wq == 2 && lane == 0;
            uint32_t empty;
            asm("mapa.shared::cluster.u32 %0, %1, %2;" : "=r"(empty) : "r"(bars + 8 * B_EMPTY), "r"(wq & 1));
#pragma unroll 1
            for (int t = pair; t < 5; t += 2) {
                uint32_t po = t == 4 ? POS_LAST : POS_STD, full = bars + 8 * (B_FULL + 8 * t), slot = (0x24130u >> (4 * t)) & 7, prev = 0;
                uint64_t da = mkdesc(half * 8192, 16, 1024, 1), db = mkdesc(OFF_RING, 8192, 1024, 1) + slot * 1024;
                if (tid == 0 && t == 0) TSTAMP(30);
                mbar_wait(full, 0);
                if (t > 0) mbar_wait(bars + 8 * (B_ORD + t - 1), 0);
#pragma unroll 1
                for (int j = 0; j < 8; j++) {
                    wg_fence();
#pragma unroll
                    for (int k = 0; k < 4; k++) wgmma_ss_n128(acc, da + k * 2, db + k * 128, (j | k) != 0);
                    wg_commit();
                    const uint32_t rel_a = empty + prev * 8, rel_b = bars + 8 * (j == 3 ? B_AFREE0 : B_AFREE + (j >> 1) - 1);
                    const bool do_a = j > 0 && rel, do_b = (po & 8) && rel2;
                    prev = slot; slot = slot == NRING - 1 ? 0 : slot + 1; po >>= 4; full += 8;
                    da = mkdesc(half * 8192, 16, 1024, 1) + (po & 7) * 1024; db = mkdesc(OFF_RING, 8192, 1024, 1) + slot * 1024;
                    if (j < 7) mbar_wait(full, 0); else if (rel2) mbar_arrive(bars + 8 * (B_ORD + t));
                    wg_wait<1>();
                    if (do_a) mbar_arrive_remote(rel_a);
                    if (do_b) mbar_arrive(rel_b);
                }
                if (t >= 3) {
                    mbar_wait(bars + 8 * B_QKV, 0);
                    const uint4* pq = g_q + (head * 128 + (qb * 8 + wg) * 4 + wq) * 32 + lane;
                    const uint4 v = __ldcg(pq), u = __ldcg(pq + 512);
                    qn[0] = v.x; qn[1] = v.y; qn[2] = v.z; qn[3] = v.w; q[0] = u.x; q[1] = u.y; q[2] = u.z; q[3] = u.w;
                }
                wg_wait<0>();
                if (rel) mbar_arrive_remote(empty + prev * 8);
                if (t >= 3 && rel2) mbar_arrive(bars + 8 * (t == 4 ? B_AFREE + 3 : B_AFREE0));
                pin<64>(acc);
                if (wq == 0 && half == 0 && lane == 0) TSTAMP(2 + 2 * t);
                mbar_wait(bars + 8 * (B_STATS + t), 0);
                uint32_t rs0, rs1;
                asm volatile("ld.shared.b32 %0, [%1];" : "=r"(rs0) : "r"(sb + OFF_RS + (half * 64 + wq * 16 + g) * 4));
                asm volatile("ld.shared.b32 %0, [%1];" : "=r"(rs1) : "r"(sb + OFF_RS + (half * 64 + wq * 16 + g + 8) * 4));
                const float m0 = bf_lo(rs0), m1 = bf_lo(rs1);
                float d0 = bf_hi(rs0), d1 = bf_hi(rs1);
#pragma unroll
                for (int j = 0; j < 16; j++) {
                    float c0, c1;
                    asm volatile("ld.shared.v2.f32 {%0,%1}, [%2];" : "=f"(c0), "=f"(c1) : "r"(sb + OFF_CS + (t * 128 + j * 8 + t4 * 2) * 4));
                    acc[4 * j] = fmaf(-m0, c0, acc[4 * j]); acc[4 * j + 1] = fmaf(-m0, c1, acc[4 * j + 1]);
                    acc[4 * j + 2] = fmaf(-m1, c0, acc[4 * j + 2]); acc[4 * j + 3] = fmaf(-m1, c1, acc[4 * j + 3]);
                }
                float r0 = rcpf(d0), r1 = rcpf(d1);
                if (t < nq) {
                    const int qt = qt0 + t;
                    if (qt < 4) {
                        r0 *= 0.25f * 1.4426950408889634f * M71; r1 *= 0.25f * 1.4426950408889634f * M71;
                    } else if (qt < 8) {
                        r0 *= ((FIXED_MASK >> (2 * wq)) & 1) ? M71 : P71; r1 *= ((FIXED_MASK >> (2 * wq + 1)) & 1) ? M71 : P71;
                    }
#pragma unroll
                    for (int i = 0; i < 32; i++) { const float r = (i & 1) ? r1 : r0; acc[i] = __uint_as_float(pack_bf16(acc[2 * i] * r, acc[2 * i + 1] * r)); }
                    if (qt < 4) {
                        float4* p = reinterpret_cast<float4*>(g_q) + (qt * 1024 + tile16) * 32 + lane;
#pragma unroll
                        for (int hh = 0; hh < 8; hh++) p[hh * 4096] = make_float4(acc[4 * hh], acc[4 * hh + 1], acc[4 * hh + 2], acc[4 * hh + 3]);
                    } else {
                        float* p = reinterpret_cast<float*>(g_kv + (qt - 4) * 32768) + tile16 * 64 + lane;
#pragma unroll
                        for (int i = 0; i < 32; i++) p[(i >> 1) * 8192 + (i & 1) * 32] = acc[i];
                    }
                } else {
                    uint32_t* p = reinterpret_cast<uint32_t*>(g_h + (rowblk * 28 + gu0 + t) * 512) + wq * 512 + lane;
                    r0 *= -1.4426950408889634f; r1 *= -1.4426950408889634f; d0 *= d0; d1 *= d1;
#pragma unroll
                    for (int j = 0; j < 8; j++) {
                        const float* a = acc + j * 4; const float* b = a + 32;
                        p[j * 32] = pack_bf16(a[0] * b[0] * rcpf(fmaf(ex2f(a[0] * r0), d0, d0)), a[1] * b[1] * rcpf(fmaf(ex2f(a[1] * r0), d0, d0)));
                        p[256 + j * 32] = pack_bf16(a[2] * b[2] * rcpf(fmaf(ex2f(a[2] * r1), d1, d1)), a[3] * b[3] * rcpf(fmaf(ex2f(a[3] * r1), d1, d1)));
                    }
                }
                __syncwarp();
                if (elect_one()) mbar_arrive(bars + 8 * (B_TILE + t));
                if (wq == 0 && half == 0 && lane == 0) TSTAMP(3 + 2 * t);
            }
        }
        const uint64_t db2 = mkdesc(OFF_B2, 128, 256, 0);
        float s[32];
        auto ref_point = [&](int ntile, uint32_t& b0, uint32_t& b1) {
            float m0 = -INFINITY, m1 = -INFINITY, f0 = -INFINITY, f1 = -INFINITY;
#pragma unroll 1
            for (int t = 0; t < ntile; t++) {
                wg_fence();
                wgmma_rs_n64_zero(s, q, mkdesc(4096, 94208, 128, 0) + (t >> 2) * DK_STEP + (t & 3) * 64);
                wg_commit();
                wg_wait<0>();
                pin<32>(s);
#pragma unroll
                for (int i = 0; i < 8; i++) {
                    if ((FIXED_MASK >> i) & 1) { f0 = fmaxf(f0, fmaxf(s[4 * i], s[4 * i + 1])); f1 = fmaxf(f1, fmaxf(s[4 * i + 2], s[4 * i + 3])); }
                    else                       { m0 = fmaxf(m0, fmaxf(s[4 * i], s[4 * i + 1])); m1 = fmaxf(m1, fmaxf(s[4 * i + 2], s[4 * i + 3])); }
                }
            }
            m0 = fmaxf(m0, f0 * P71 * P71); m1 = fmaxf(m1, f1 * P71 * P71);
            m0 = fmaxf(m0, __shfl_xor_sync(0xffffffffu, m0, 1)); m1 = fmaxf(m1, __shfl_xor_sync(0xffffffffu, m1, 1));
            m0 = fmaxf(m0, __shfl_xor_sync(0xffffffffu, m0, 2)); m1 = fmaxf(m1, __shfl_xor_sync(0xffffffffu, m1, 2));
#pragma unroll
            for (int r = 0; r < 2; r++) {
                const float m = -rintf(r ? m1 : m0), mh = bf_round(m), mm = bf_round(m - mh), ml = m - mh - mm;
                const float lo = t4 == 0 ? mh : t4 == 1 ? ml : t4 == 2 ? 1.f : 0.f, hi = t4 == 0 ? mm : t4 == 1 ? 1.f : 0.f;
                (r ? b1 : b0) = pack_bf16(lo * M71, hi * M71);
            }
        };
        uint32_t q2[4];
        int redo = 1;
        mbar_wait(bars + 8 * B_KV, 0);
#pragma unroll 1
        for (int round = -1; round < 2;) {
            if (redo) ref_point(redo, q2[0], q2[1]);
            if (round < 0) {
#pragma unroll
                for (int i = 0; i < 4; i++) { const uint32_t tq = q[i]; q[i] = qn[i]; qn[i] = tq; }
                qn[4] = q2[0]; qn[5] = q2[1];
                q2[2] = __shfl_sync(0xffffffffu, q2[0], 3); q2[3] = __shfl_sync(0xffffffffu, q2[1], 3);
                round = 0;
                continue;
            }
            float o[12]; uint32_t p[16];
#pragma unroll
            for (int i = 0; i < 12; i++) o[i] = 0.f;
            pin<12>(o); pin<4>(q2);
            if (wq == 0 && half == 0 && lane == 0) TSTAMP(12 + 4 * round + pair);
            uint64_t dk = mkdesc(4096, 94208, 128, 0), dv = mkdesc(0, 128, 65536, 0);
#pragma unroll 1
            for (int c = 0; c < 8; c++, dk += DK_STEP, dv += DV_STEP) {
                if (round == 0) mbar_wait(bars + 8 * (B_KV + c), 0);
#pragma unroll
                for (int t = 0; t < 4; t++) {
                    wg_fence();
                    wgmma_rs_n64_zero(s, q, dk + t * 64);
                    wgmma_rs_n64_acc(s, q2, db2);
                    wg_commit();
                    wg_wait<0>();
                    pin<32>(s); pin<16>(p);
#pragma unroll
                    for (int i = 0; i < 16; i++) {
                        if ((FIXED_MASK >> (i >> 1)) & 1) p[i] = exp2_fixed(s[2 * i], s[2 * i + 1], half2);
                        else                              p[i] = pack_bf16(ex2f(s[2 * i]), ex2f(s[2 * i + 1]));
                    }
                    wg_fence();
#pragma unroll
                    for (int k = 0; k < 4; k++) wgmma_rs_n24_acc(o, p + 4 * k, dv + (t * 4 + k) * 16);
                    wg_commit();
                }
            }
            wg_wait<0>();
            pin<12>(o);
            if (redo != 32) {
                float chk = (o[8] + o[10]) * 256.f;
#pragma unroll
                for (int i = 0; i < 8; i++) chk += fabsf(o[i]);
                uint32_t bad;
                asm volatile("{\n.reg .pred p, q;\nsetp.geu.f32 q, %1, 0f7F800000;\nbar.red.or.pred p, %2, 128, q;\nselp.u32 %0, 1, 0, p;\n}" : "=r"(bad) : "f"(chk), "r"(1 + wg) : "memory");
                if (__any_sync(0xffffffffu, bad)) { redo = 32; continue; }
            }
            const int rowblk = qb * 8 + round * 4 + wg;
            const float r0 = rcpf(o[8]), r1 = rcpf(o[10]);
            uint32_t* po = reinterpret_cast<uint32_t*>(g_o + (rowblk * 8 + (head >> 2)) * 512) + wq * 512 + (head & 3) * 64 + lane;
            po[0] = pack_bf16(o[0] * r0, o[1] * r0); po[256] = pack_bf16(o[2] * r1, o[3] * r1);
            po[32] = pack_bf16(o[4] * r0, o[5] * r0); po[288] = pack_bf16(o[6] * r1, o[7] * r1);
            if (round == 0) {
                __syncwarp();
                if (elect_one()) mbar_arrive(bars + 8 * (B_OW + pair));
            } else {
                bar_sync(1 + wg, 128);
                if (wq == 0 && elect_one()) { mbar_arrive(bars + 8 * B_DONE); signal_cnt(C_O + rowblk); }
            }
#pragma unroll
            for (int i = 0; i < 4; i++) q[i] = qn[i];
            q2[0] = qn[4]; q2[1] = qn[5];
            redo = 0;
            if (wq == 0 && half == 0 && lane == 0) TSTAMP(14 + 4 * round + pair);
            round++;
        }
    } else {
        uint32_t tag;
        if (wq == 0) {
            asm volatile("barrier.cluster.wait.aligned;" ::: "memory");
            if (tid == 512) TSTAMP(27);
            uint32_t slot = 2, ph = 1;
#pragma unroll 1
            for (int n = 2; n < 40; n++) {
                const int t = n >> 3, j = n & 7;
                const int kc = (n < 32 ? j : (POS_LAST >> (4 * j)) & 7) * 64;
                const CUtensorMap* m = t < nq ? &mqkv : rank ? &mw3 : &mw1;
                const int col = t < nq ? (qt0 + t) * 128 + rank * 64 : (gu0 + t) * 64;
                const uint32_t dst = ring + slot * 16384 + rank * 8192, fb = bars + 8 * (B_FULL + n);
                if (n < 8 && elect_one()) tma2d(sb + n * 16384, &mx, kc, mblk * 128, fb);
                mbar_wait(bars + 8 * (B_EMPTY + slot), ph);
                if (elect_one()) { TS2(0, n); tma2d_mc(dst, m, col, kc, fb); }
                if (++slot == NRING) { slot = 0; ph ^= 1; }
            }
            tag = ld_epoch() + 1;
        } else if (wq == 1) {
            tag = ld_epoch() + 1;
            mbar_wait(bars + 8 * (B_FULL + 5), 0);
#pragma unroll 1
            for (int t = 0; t < 5; t++) {
                float a[4];
#pragma unroll 1
                for (int n = 0; n < 2000000; n++) {
                    uint32_t stale = 0;
                    a[0] = a[1] = a[2] = a[3] = 0.f;
#pragma unroll
                    for (int i = 0; i < 16; i++) {
                        uint32_t u, v;
                        stale |= ld_tagged2(g_cs + (grp * 5 + t) * 512 + i * 32 + lane, tag, u, v);
                        a[(i & 1) * 2] += __uint_as_float(u); a[(i & 1) * 2 + 1] += __uint_as_float(v);
                    }
                    if (__all_sync(0xffffffffu, stale == 0)) break;
                    if (t) __nanosleep(400);
                }
                asm volatile("st.shared.v2.f32 [%0], {%1,%2};" :: "r"(sb + OFF_CS + t * 512 + lane * 8), "f"(a[0]), "f"(a[1]) : "memory");
                asm volatile("st.shared.v2.f32 [%0], {%1,%2};" :: "r"(sb + OFF_CS + t * 512 + 256 + lane * 8), "f"(a[2]), "f"(a[3]) : "memory");
                if (t == 0) {
                    uint32_t r[4];
#pragma unroll 1
                    for (int n = 0; n < 2000000; n++) {
                        const uint32_t stale = ld_tagged2(g_rs + mblk * 64 + lane * 2, tag, r[0], r[1]) | ld_tagged2(g_rs + mblk * 64 + lane * 2 + 1, tag, r[2], r[3]);
                        if (__all_sync(0xffffffffu, stale == 0)) break;
                    }
                    asm volatile("st.shared.v4.b32 [%0], {%1,%2,%3,%4};" :: "r"(sb + OFF_RS + lane * 16), "r"(r[0]), "r"(r[1]), "r"(r[2]), "r"(r[3]) : "memory");
                }
                __syncwarp();
                if (elect_one()) { mbar_arrive(bars + 8 * (B_STATS + t)); TSTAMP(32 + t); }
            }
        } else {
            tag = ld_epoch() + 1;
            mbar_wait(bars + 8 * (B_FULL + wq - 1), 0);
#pragma unroll 1
            for (int t = wq - 1; t < 5; t += 2) {
                const __nv_bfloat16* src; int ld;
                if (t < nq) { src = wqkv + (qt0 + t) * 128 + rank * 64; ld = 3 * DM; }
                else        { src = (rank ? w3 : w1) + (gu0 + t) * 64; ld = FF; }
                src += (size_t)(rot * 64 + (lane >> 3)) * ld + (lane & 7) * 8;
                uint4 v[16];
                const uint32_t* w = reinterpret_cast<const uint32_t*>(v);
#pragma unroll
                for (int j = 0; j < 16; j++) v[j] = __ldg(reinterpret_cast<const uint4*>(src + (size_t)j * 4 * ld));
                float c[8];
#pragma unroll
                for (int e = 0; e < 4; e++) {
                    float a = 0.f, b = 0.f;
#pragma unroll
                    for (int j = 0; j < 16; j++) { a += bf_lo(w[4 * j + e]); b += bf_hi(w[4 * j + e]); }
                    c[2 * e] = a; c[2 * e + 1] = b;
                }
#pragma unroll
                for (int n = 4; n > 1; n >>= 1) {
                    const bool up = lane & (4 * n);
#pragma unroll
                    for (int e = 0; e < n; e++) c[e] = (up ? c[e + n] : c[e]) + __shfl_xor_sync(0xffffffffu, up ? c[e] : c[e + n], 4 * n);
                }
                unsigned long long* dst = reinterpret_cast<unsigned long long*>(g_cs) + ((grp * 5 + t) * 8 + rot) * 128 + rank * 64 + (lane & 7) * 8 + (lane >> 3) * 2;
                st_tagged(dst, __float_as_uint(c[0]), tag); st_tagged(dst + 1, __float_as_uint(c[1]), tag);
                if (lane == 0) TSTAMP(40 + t);
            }
        }
        if (wq == 3) {
#pragma unroll 1
            for (int i = lane; i < 256; i += 32) asm volatile("st.shared.v4.b32 [%0], {%1,%1,%1,%1};" :: "r"(sb + OFF_ONES + i * 16), "r"(0x3F803F80u) : "memory");
#pragma unroll 1
            for (int i = lane; i < 128; i += 32) {
                const bool fx = (FIXED_MASK >> (i >> 4)) & 1;
                uint32_t a = fx ? pack_bf16(M71, M71) : pack_bf16(P71, P71);
                uint32_t b = fx ? pack_bf16(M71, 47.0f * M71) : pack_bf16(P71, -79.5f * P71);
                uint32_t c = fx ? 0u : pack_bf16(0.08214f * P71, 0.f);
                if (i & 8) a = b = c = 0;
                asm volatile("st.shared.v4.b32 [%0], {%1,%2,%3,%4};" :: "r"(sb + OFF_B2 + i * 16), "r"(a), "r"(b), "r"(c), "r"(0) : "memory");
            }
            fence_async_smem();
            __syncwarp();
            if (elect_one()) mbar_arrive(bars + 8 * B_QKV);
        } else if (wq == 1) {
#pragma unroll 1
            for (int i = 0; i < 3; i++) wait_cnt(C_QKV + i * 4 + (head >> 3), 16 * tag, 100);
            fence_async_all();
            if (elect_one()) { mbar_arrive(bars + 8 * B_QKV); TSTAMP(29); }
            const uint8_t* gk = reinterpret_cast<const uint8_t*>(g_kv + head * 4096);
            const uint8_t* gv = reinterpret_cast<const uint8_t*>(g_kv + (32 + head) * 4096);
#pragma unroll 1
            for (int c = 0; c < 8; c++) {
                if (!(c & 1)) mbar_wait(bars + 8 * (c ? B_AFREE + (c >> 1) : B_AFREE0), 0);
                if (elect_one()) {
                    const uint32_t b = bars + 8 * (B_KV + c);
                    mbar_expect(b, 16384);
                    bulk_load(sb + (2 * c + 1) * 4096, gk + c * 4096, 4096, b);
                    bulk_load(sb + 2 * c * 4096, gv + c * 4096, 4096, b);
                    bulk_load(sb + 65536 + c * 4096, gv + 32768 + c * 4096, 4096, b);
                    bulk_load(sb + 98304 + c * 4096, gk + 32768 + c * 4096, 4096, b);
                }
            }
        } else if (wq == 2) {
#pragma unroll 1
            for (int t = 0; t < 5; t++) {
                mbar_wait(bars + 8 * (B_TILE + t), 0);
                if (elect_one()) signal_cnt(t < nq ? C_QKV + qt0 + t : C_H + mblk);
            }
        }
        pin<1>(&tag);
        bar_sync(5, 128);
        if (tid == 639) g_epoch[blockIdx.x] = tag;
        const int cb = blockIdx.x & 7, pr = blockIdx.x >> 3;
        const int rb0 = (pr >> 2) * 8 + (pr & 3);
        uint32_t gate[2][16];
        {
            float dn[64];
            auto load_stage = [&](int kb, int st) {
                const uint32_t b = bars + 8 * (B_RING + st), dst = ring + st * 24576;
                mbar_expect(b, 24576);
                bulk_load(dst, g_h + (rb0 * 28 + kb) * 512, 8192, b);
                bulk_load(dst + 8192, g_h + ((rb0 + 4) * 28 + kb) * 512, 8192, b);
                tma2d(dst + 16384, &mw2, cb * 64, kb * 64, b);
            };
            if (wq == 0) {
                wait_cnt(C_H + (rb0 >> 1), 28 * tag, 200);
                wait_cnt(C_H + (rb0 >> 1) + 2, 28 * tag, 200);
                if (elect_one()) { TSTAMP(20); fence_async_all(); load_stage(0, 0); load_stage(1, 1); }
            }
            int st = 0; uint32_t ph = 0;
#pragma unroll 1
            for (int kb = 0; kb < 28; kb++) {
                mbar_wait(bars + 8 * (B_RING + st), ph);
                const uint64_t da = mkdesc(OFF_RING + st * 24576, 128, 1024, 0), db = mkdesc(OFF_RING + st * 24576 + 16384, 8192, 1024, 1);
                wg_fence();
#pragma unroll
                for (int k = 0; k < 4; k++) { wgmma_ss_n64(dn, da + k * 16, db + k * 128, (kb | k) != 0); wgmma_ss_n64(dn + 32, da + 512 + k * 16, db + k * 128, (kb | k) != 0); }
                wg_commit();
                wg_wait<1>();
                if (wq == 0 && kb < 26 && elect_one()) load_stage(kb + 2, st == 0 ? 2 : st - 1);
                if (++st == 3) { st = 0; ph ^= 1; }
            }
            wg_wait<0>();
            pin<64>(dn);
#pragma unroll
            for (int i = 0; i < 32; i++) gate[i >> 4][i & 15] = pack_bf16(siluf(dn[2 * i]), siluf(dn[2 * i + 1]));
        }
        float acc[32];
        if (tid == 512) TSTAMP(21);
        const uint32_t bar_wo = bars + 8 * B_WO;
        if (wq == 0 && elect_one()) {
            mbar_expect(bar_wo, 65536);
#pragma unroll 1
            for (int i = 0; i < 8; i++) tma2d(ring + i * 8192, &mwo, cb * 64, i * 64, bar_wo);
        }
        if (wq >= 2) {
            mbar_wait(bars + 8 * (B_OW + wq - 2), 0);
            if (elect_one()) {
                signal_cnt(C_O + qb * 8 + 2 * wq - 4);
                asm volatile("red.relaxed.gpu.global.add.u32 [%0], 1;" :: "l"(g_cnt + (C_O + qb * 8 + 2 * wq - 3) * 8) : "memory");
            }
        }
#pragma unroll 1
        for (int tl = 0; tl < 2; tl++) {
            const int rb = rb0 + 4 * tl;
            uint32_t xr[16];
            const uint32_t* px = reinterpret_cast<const uint32_t*>(x + (size_t)(rb * 64 + wq * 16 + g) * DM + cb * 64) + t4;
#pragma unroll
            for (int j = 0; j < 8; j++) { xr[2 * j] = __ldg(px + j * 4); xr[2 * j + 1] = __ldg(px + 8 * DM / 2 + j * 4); }
            if (wq == 0) {
                if (tl == 1) mbar_wait(bars + 8 * B_DONE, 0);
                wait_cnt(C_O + rb, 32 * tag, tl ? 20 : 200);
                if (elect_one()) {
                    fence_async_all();
                    TSTAMP(22 + 2 * tl);
#pragma unroll 1
                    for (int i = 0; i < (tl ? 8 : 2); i++) {
                        mbar_expect(bars + 8 * (B_O + i), 8192);
                        bulk_load((tl ? sb : ring + 65536) + i * 8192, g_o + (rb * 8 + i) * 512, 8192, bars + 8 * (B_O + i));
                    }
                }
            }
            if (tl == 0) mbar_wait(bar_wo, 0);
#pragma unroll 1
            for (int kb = 0; kb < 8; kb++) {
                mbar_wait(bars + 8 * (B_O + kb), tl);
                const uint32_t a = tl == 0 ? OFF_RING + 65536 + (kb & 1) * 8192 : kb * 8192;
                const uint64_t da = mkdesc(a, 128, 1024, 0), db = mkdesc(OFF_RING + kb * 8192, 8192, 1024, 1);
                wg_fence();
#pragma unroll
                for (int k = 0; k < 4; k++) wgmma_ss_n64(acc, da + k * 16, db + k * 128, (kb | k) != 0);
                wg_commit();
                if (tl == 0) {
                    wg_wait<0>();
                    bar_sync(5, 128);
                    if (wq == 0 && kb < 6 && elect_one()) { mbar_expect(bars + 8 * (B_O + kb + 2), 8192); bulk_load(sb + a, g_o + (rb * 8 + kb + 2) * 512, 8192, bars + 8 * (B_O + kb + 2)); }
                }
            }
            wg_wait<0>();
            pin<32>(acc);
            uint32_t* po = reinterpret_cast<uint32_t*>(out + (size_t)(rb * 64 + wq * 16 + g) * DM + cb * 64) + t4;
#pragma unroll
            for (int i = 0; i < 16; i++) {
                const uint32_t r = pack_bf16(fmaf(acc[2 * i], bf_lo(gate[0][i]), bf_lo(xr[i])), fmaf(acc[2 * i + 1], bf_hi(gate[0][i]), bf_hi(xr[i])));
                po[(i & 1) * (8 * DM / 2) + (i >> 1) * 4] = r;
                gate[0][i] = gate[1][i];
            }
            if (tid == 512) TSTAMP(23 + 2 * tl);
        }
    }
}

typedef CUresult (*EncodeFn)(CUtensorMap*, CUtensorMapDataType, cuuint32_t, void*, const cuuint64_t*, const cuuint64_t*, const cuuint32_t*,
                             const cuuint32_t*, CUtensorMapInterleave, CUtensorMapSwizzle, CUtensorMapL2promotion, CUtensorMapFloatOOBfill);

void make_map(EncodeFn fn, CUtensorMap* m, const void* p, int rows, int cols, int box_rows) {
    cuuint64_t dims[2] = {(cuuint64_t)cols, (cuuint64_t)rows};
    cuuint64_t strides[1] = {(cuuint64_t)cols * 2};
    cuuint32_t box[2] = {64, (cuuint32_t)box_rows};
    cuuint32_t es[2] = {1, 1};
    fn(m, CU_TENSOR_MAP_DATA_TYPE_BFLOAT16, 2, const_cast<void*>(p), dims, strides, box, es, CU_TENSOR_MAP_INTERLEAVE_NONE,
       CU_TENSOR_MAP_SWIZZLE_128B, CU_TENSOR_MAP_L2_PROMOTION_L2_128B, CU_TENSOR_MAP_FLOAT_OOB_FILL_NONE);
}

}

extern "C" void kernel_launch(void* const* d_in, const int* in_sizes, int n_in, void* d_out, int out_size) {
    const __nv_bfloat16* x = (const __nv_bfloat16*)d_in[0];
    static EncodeFn fn = nullptr;
    if (!fn) {
        cudaDriverEntryPointQueryResult qr;
        cudaGetDriverEntryPoint("cuTensorMapEncodeTiled", (void**)&fn, cudaEnableDefault, &qr);
        cudaFuncSetAttribute(mega_kernel, cudaFuncAttributeMaxDynamicSharedMemorySize, SMEM_BYTES);
    }
    CUtensorMap mx, mqkv, mw1, mw3, mw2, mwo;
    make_map(fn, &mx, d_in[0], SEQ, DM, 128);
    make_map(fn, &mqkv, d_in[1], DM, 3 * DM, 64);
    make_map(fn, &mwo, d_in[2], DM, DM, 64);
    make_map(fn, &mw1, d_in[4], DM, FF, 64);
    make_map(fn, &mw3, d_in[5], DM, FF, 64);
    make_map(fn, &mw2, d_in[6], FF, DM, 64);
    mega_kernel<<<128, 640, SMEM_BYTES, cudaStreamPerThread>>>(x, (const __nv_bfloat16*)d_in[1], (const __nv_bfloat16*)d_in[4], (const __nv_bfloat16*)d_in[5],
                                                               (__nv_bfloat16*)d_out, mx, mqkv, mw1, mw3, mw2, mwo, 0x3F003F00u);
}
```

```cpp
#include <cuda_runtime.h>
#include <cuda_bf16.h>
#include <cuda.h>
#include <stdint.h>

namespace {

constexpr int SEQ = 2048, DM = 512, FF = 1792;

__device__ uint4 g_q[32 * 128 * 32];
__device__ uint4 g_kv[64 * 4096];
__device__ uint4 g_h[32 * 28 * 512];
__device__ uint4 g_o[32 * 8 * 512];
__device__ ulonglong2 g_cs[40 * 8 * 64];
__device__ ulonglong2 g_rs[SEQ / 2];
constexpr int C_QKV = 0, C_H = 12, C_O = 28, C_NUM = 60;
__device__ unsigned g_cnt[C_NUM * 8];
__device__ unsigned g_epoch[128];
#define TSTAMP(i)
#define TS2(k, i)

__device__ __forceinline__ uint32_t smem_u32(const void* p) { return (uint32_t)__cvta_generic_to_shared(p); }
__device__ __forceinline__ void mbar_init(uint32_t a, int c) { asm volatile("mbarrier.init.shared::cta.b64 [%0], %1;" :: "r"(a), "r"(c)); }
__device__ __forceinline__ void mbar_expect(uint32_t a, int b) { asm volatile("mbarrier.arrive.expect_tx.shared::cta.b64 _, [%0], %1;" :: "r"(a), "r"(b) : "memory"); }
__device__ __forceinline__ void mbar_arrive(uint32_t a) { asm volatile("mbarrier.arrive.shared::cta.b64 _, [%0];" :: "r"(a) : "memory"); }
__device__ __forceinline__ void mbar_arrive_remote(uint32_t a) { asm volatile("mbarrier.arrive.shared::cluster.b64 _, [%0];" :: "r"(a) : "memory"); }
__device__ __forceinline__ bool mbar_try(uint32_t a, uint32_t ph) {
    uint32_t ok;
    asm volatile("{\n.reg .pred p;\nmbarrier.try_wait.parity.shared::cta.b64 p, [%1], %2;\nselp.u32 %0, 1, 0, p;\n}" : "=r"(ok) : "r"(a), "r"(ph) : "memory");
    return ok;
}
__device__ __forceinline__ void mbar_wait(uint32_t a, uint32_t ph) {
    int n = 1 << 22;
#pragma unroll 1
    do { n = __all_sync(0xffffffffu, mbar_try(a, ph)) ? 0 : n - 1; } while (n > 0);
}
__device__ __forceinline__ bool elect_one() {
    uint32_t p;
    asm volatile("{\n.reg .pred P;\nelect.sync _|P, 0xffffffff;\nselp.u32 %0, 1, 0, P;\n}" : "=r"(p));
    return p;
}
__device__ __forceinline__ void signal_cnt(int c) {
    asm volatile("fence.release.gpu;\nred.relaxed.gpu.global.add.u32 [%0], 1;" :: "l"(g_cnt + c * 8) : "memory");
}
__device__ __forceinline__ void wait_cnt(int c, unsigned target, int ns) {
#pragma unroll 1
    for (int n = 0; n < 2000000; n++) {
        unsigned v;
        asm volatile("ld.relaxed.gpu.global.u32 %0, [%1];" : "=r"(v) : "l"(g_cnt + c * 8) : "memory");
        if (__all_sync(0xffffffffu, (int)(v - target) >= 0)) break;
        __nanosleep(ns);
    }
}
__device__ __forceinline__ uint32_t ld_epoch() {
    uint32_t e;
    asm volatile("ld.relaxed.gpu.global.u32 %0, [%1];" : "=r"(e) : "l"(g_epoch + blockIdx.x) : "memory");
    return e;
}
__device__ __forceinline__ void st_tagged(void* p, uint32_t v, uint32_t tag) {
    asm volatile("st.relaxed.gpu.global.b64 [%0], %1;" :: "l"(p), "l"((unsigned long long)tag << 32 | v) : "memory");
}
__device__ __forceinline__ uint32_t ld_tagged2(const ulonglong2* p, uint32_t tag, uint32_t& a, uint32_t& b) {
    unsigned long long u, v;
    asm volatile("ld.relaxed.gpu.global.v2.b64 {%0,%1}, [%2];" : "=l"(u), "=l"(v) : "l"(p) : "memory");
    a = (uint32_t)u; b = (uint32_t)v;
    return ((uint32_t)(u >> 32) ^ tag) | ((uint32_t)(v >> 32) ^ tag);
}
__device__ __forceinline__ void tma2d(uint32_t dst, const CUtensorMap* m, int c0, int c1, uint32_t bar) {
    asm volatile("cp.async.bulk.tensor.2d.shared::cluster.global.mbarrier::complete_tx::bytes [%0], [%1, {%3, %4}], [%2];"
                 :: "r"(dst), "l"(m), "r"(bar), "r"(c0), "r"(c1) : "memory");
}
__device__ __forceinline__ void tma2d_mc(uint32_t dst, const CUtensorMap* m, int c0, int c1, uint32_t bar) {
    asm volatile("cp.async.bulk.tensor.2d.shared::cluster.global.mbarrier::complete_tx::bytes.multicast::cluster [%0], [%1, {%3, %4}], [%2], %5;"
                 :: "r"(dst), "l"(m), "r"(bar), "r"(c0), "r"(c1), "h"((uint16_t)3) : "memory");
}
__device__ __forceinline__ void bulk_load(uint32_t dst, const void* src, int bytes, uint32_t bar) {
    asm volatile("cp.async.bulk.shared::cluster.global.mbarrier::complete_tx::bytes [%0], [%1], %2, [%3];"
                 :: "r"(dst), "l"(src), "r"(bytes), "r"(bar) : "memory");
}
__device__ __forceinline__ void bar_sync(int id, int n) { asm volatile("bar.sync %0, %1;" :: "r"(id), "r"(n) : "memory"); }
__device__ __forceinline__ void fence_async_smem() { asm volatile("fence.proxy.async.shared::cta;" ::: "memory"); }
__device__ __forceinline__ void fence_async_all() { asm volatile("fence.acquire.gpu;\nfence.proxy.async.global;" ::: "memory"); }
__device__ __forceinline__ void wg_fence() { asm volatile("wgmma.fence.sync.aligned;" ::: "memory"); }
__device__ __forceinline__ void wg_commit() { asm volatile("wgmma.commit_group.sync.aligned;" ::: "memory"); }
template <int N> __device__ __forceinline__ void wg_wait() { asm volatile("wgmma.wait_group.sync.aligned %0;" :: "n"(N) : "memory"); }
template <int N> __device__ __forceinline__ void pin(float* d) {
#pragma unroll
    for (int i = 0; i < N; i++) asm volatile("" : "+f"(d[i]) :: "memory");
}
template <int N> __device__ __forceinline__ void pin(uint32_t* d) {
#pragma unroll
    for (int i = 0; i < N; i++) asm volatile("" : "+r"(d[i]) :: "memory");
}
constexpr uint32_t SMEM_BASE = 1024;
__device__ __forceinline__ uint64_t mkdesc(uint32_t off, uint32_t lbo, uint32_t sbo, uint32_t swz) {
    return (uint64_t)((SMEM_BASE + off) >> 4) | ((uint64_t)(lbo >> 4) << 16) | ((uint64_t)(sbo >> 4) << 32) | ((uint64_t)swz << 62);
}
__device__ __forceinline__ float ex2f(float x) { float y; asm("ex2.approx.ftz.f32 %0, %1;" : "=f"(y) : "f"(x)); return y; }
__device__ __forceinline__ float rcpf(float x) { float y; asm("rcp.approx.ftz.f32 %0, %1;" : "=f"(y) : "f"(x)); return y; }
__device__ __forceinline__ uint32_t pack_bf16(float lo, float hi) { uint32_t r; asm("cvt.rn.bf16x2.f32 %0, %1, %2;" : "=r"(r) : "f"(hi), "f"(lo)); return r; }
__device__ __forceinline__ float bf_lo(uint32_t v) { return __uint_as_float(v << 16); }
__device__ __forceinline__ float bf_hi(uint32_t v) { return __uint_as_float(v & 0xFFFF0000u); }
__device__ __forceinline__ float bf_round(float x) { return __bfloat162float(__float2bfloat16_rn(x)); }
__device__ __forceinline__ float siluf(float g) { return g * rcpf(1.0f + ex2f(g * -1.4426950408889634f)); }

__device__ __forceinline__ void wgmma_ss_n256(float* d, uint64_t da, uint64_t db, int acc) {
    asm volatile("{\n.reg .pred p;\nsetp.ne.b32 p, %130, 0;\nwgmma.mma_async.sync.aligned.m64n256k16.f32.bf16.bf16 {"
        "%0,%1,%2,%3,%4,%5,%6,%7,%8,%9,%10,%11,%12,%13,%14,%15,%16,%17,%18,%19,%20,%21,%22,%23,%24,%25,%26,%27,%28,%29,%30,%31,%32,%33,%34,%35,%36,%37,%38,%39,"
        "%40,%41,%42,%43,%44,%45,%46,%47,%48,%49,%50,%51,%52,%53,%54,%55,%56,%57,%58,%59,%60,%61,%62,%63,%64,%65,%66,%67,%68,%69,%70,%71,%72,%73,%74,%75,%76,"
        "%77,%78,%79,%80,%81,%82,%83,%84,%85,%86,%87,%88,%89,%90,%91,%92,%93,%94,%95,%96,%97,%98,%99,%100,%101,%102,%103,%104,%105,%106,%107,%108,%109,%110,"
        "%111,%112,%113,%114,%115,%116,%117,%118,%119,%120,%121,%122,%123,%124,%125,%126,%127"
        "}, %128, %129, p, 1, 1, 0, 1;\n}\n"
        : "+f"(d[0]),"+f"(d[1]),"+f"(d[2]),"+f"(d[3]),"+f"(d[4]),"+f"(d[5]),"+f"(d[6]),"+f"(d[7]),"+f"(d[8]),"+f"(d[9]),"+f"(d[10]),"+f"(d[11]),"+f"(d[12]),
          "+f"(d[13]),"+f"(d[14]),"+f"(d[15]),"+f"(d[16]),"+f"(d[17]),"+f"(d[18]),"+f"(d[19]),"+f"(d[20]),"+f"(d[21]),"+f"(d[22]),"+f"(d[23]),"+f"(d[24]),
          "+f"(d[25]),"+f"(d[26]),"+f"(d[27]),"+f"(d[28]),"+f"(d[29]),"+f"(d[30]),"+f"(d[31]),"+f"(d[32]),"+f"(d[33]),"+f"(d[34]),"+f"(d[35]),"+f"(d[36]),
          "+f"(d[37]),"+f"(d[38]),"+f"(d[39]),"+f"(d[40]),"+f"(d[41]),"+f"(d[42]),"+f"(d[43]),"+f"(d[44]),"+f"(d[45]),"+f"(d[46]),"+f"(d[47]),"+f"(d[48]),
          "+f"(d[49]),"+f"(d[50]),"+f"(d[51]),"+f"(d[52]),"+f"(d[53]),"+f"(d[54]),"+f"(d[55]),"+f"(d[56]),"+f"(d[57]),"+f"(d[58]),"+f"(d[59]),"+f"(d[60]),
          "+f"(d[61]),"+f"(d[62]),"+f"(d[63]),"+f"(d[64]),"+f"(d[65]),"+f"(d[66]),"+f"(d[67]),"+f"(d[68]),"+f"(d[69]),"+f"(d[70]),"+f"(d[71]),"+f"(d[72]),
          "+f"(d[73]),"+f"(d[74]),"+f"(d[75]),"+f"(d[76]),"+f"(d[77]),"+f"(d[78]),"+f"(d[79]),"+f"(d[80]),"+f"(d[81]),"+f"(d[82]),"+f"(d[83]),"+f"(d[84]),
          "+f"(d[85]),"+f"(d[86]),"+f"(d[87]),"+f"(d[88]),"+f"(d[89]),"+f"(d[90]),"+f"(d[91]),"+f"(d[92]),"+f"(d[93]),"+f"(d[94]),"+f"(d[95]),"+f"(d[96]),
          "+f"(d[97]),"+f"(d[98]),"+f"(d[99]),"+f"(d[100]),"+f"(d[101]),"+f"(d[102]),"+f"(d[103]),"+f"(d[104]),"+f"(d[105]),"+f"(d[106]),"+f"(d[107]),
          "+f"(d[108]),"+f"(d[109]),"+f"(d[110]),"+f"(d[111]),"+f"(d[112]),"+f"(d[113]),"+f"(d[114]),"+f"(d[115]),"+f"(d[116]),"+f"(d[117]),"+f"(d[118]),
          "+f"(d[119]),"+f"(d[120]),"+f"(d[121]),"+f"(d[122]),"+f"(d[123]),"+f"(d[124]),"+f"(d[125]),"+f"(d[126]),"+f"(d[127])
        : "l"(da), "l"(db), "r"(acc));
}
__device__ __forceinline__ void wgmma_ss_n128(float* d, uint64_t da, uint64_t db, int acc) {
    asm volatile("{\n.reg .pred p;\nsetp.ne.b32 p, %66, 0;\nwgmma.mma_async.sync.aligned.m64n128k16.f32.bf16.bf16 {"
        "%0,%1,%2,%3,%4,%5,%6,%7,%8,%9,%10,%11,%12,%13,%14,%15,%16,%17,%18,%19,%20,%21,%22,%23,%24,%25,%26,%27,%28,%29,%30,%31,%32,%33,%34,%35,%36,%37,%38,%39,"
        "%40,%41,%42,%43,%44,%45,%46,%47,%48,%49,%50,%51,%52,%53,%54,%55,%56,%57,%58,%59,%60,%61,%62,%63"
        "}, %64, %65, p, 1, 1, 0, 1;\n}\n"
        : "+f"(d[0]),"+f"(d[1]),"+f"(d[2]),"+f"(d[3]),"+f"(d[4]),"+f"(d[5]),"+f"(d[6]),"+f"(d[7]),"+f"(d[8]),"+f"(d[9]),"+f"(d[10]),"+f"(d[11]),"+f"(d[12]),
          "+f"(d[13]),"+f"(d[14]),"+f"(d[15]),"+f"(d[16]),"+f"(d[17]),"+f"(d[18]),"+f"(d[19]),"+f"(d[20]),"+f"(d[21]),"+f"(d[22]),"+f"(d[23]),"+f"(d[24]),
          "+f"(d[25]),"+f"(d[26]),"+f"(d[27]),"+f"(d[28]),"+f"(d[29]),"+f"(d[30]),"+f"(d[31]),"+f"(d[32]),"+f"(d[33]),"+f"(d[34]),"+f"(d[35]),"+f"(d[36]),
          "+f"(d[37]),"+f"(d[38]),"+f"(d[39]),"+f"(d[40]),"+f"(d[41]),"+f"(d[42]),"+f"(d[43]),"+f"(d[44]),"+f"(d[45]),"+f"(d[46]),"+f"(d[47]),"+f"(d[48]),
          "+f"(d[49]),"+f"(d[50]),"+f"(d[51]),"+f"(d[52]),"+f"(d[53]),"+f"(d[54]),"+f"(d[55]),"+f"(d[56]),"+f"(d[57]),"+f"(d[58]),"+f"(d[59]),"+f"(d[60]),
          "+f"(d[61]),"+f"(d[62]),"+f"(d[63])
        : "l"(da), "l"(db), "r"(acc));
}
__device__ __forceinline__ void wgmma_ss_n64(float* d, uint64_t da, uint64_t db, int acc) {
    asm volatile("{\n.reg .pred p;\nsetp.ne.b32 p, %34, 0;\nwgmma.mma_async.sync.aligned.m64n64k16.f32.bf16.bf16 {"
        "%0,%1,%2,%3,%4,%5,%6,%7,%8,%9,%10,%11,%12,%13,%14,%15,%16,%17,%18,%19,%20,%21,%22,%23,%24,%25,%26,%27,%28,%29,%30,%31"
        "}, %32, %33, p, 1, 1, 0, 1;\n}\n"
        : "+f"(d[0]),"+f"(d[1]),"+f"(d[2]),"+f"(d[3]),"+f"(d[4]),"+f"(d[5]),"+f"(d[6]),"+f"(d[7]),"+f"(d[8]),"+f"(d[9]),"+f"(d[10]),"+f"(d[11]),"+f"(d[12]),
          "+f"(d[13]),"+f"(d[14]),"+f"(d[15]),"+f"(d[16]),"+f"(d[17]),"+f"(d[18]),"+f"(d[19]),"+f"(d[20]),"+f"(d[21]),"+f"(d[22]),"+f"(d[23]),"+f"(d[24]),
          "+f"(d[25]),"+f"(d[26]),"+f"(d[27]),"+f"(d[28]),"+f"(d[29]),"+f"(d[30]),"+f"(d[31])
        : "l"(da), "l"(db), "r"(acc));
}
__device__ __forceinline__ void wgmma_rs_n64_zero(float* d, const uint32_t* a, uint64_t db) {
    asm volatile("wgmma.mma_async.sync.aligned.m64n64k16.f32.bf16.bf16 {"
        "%0,%1,%2,%3,%4,%5,%6,%7,%8,%9,%10,%11,%12,%13,%14,%15,%16,%17,%18,%19,%20,%21,%22,%23,%24,%25,%26,%27,%28,%29,%30,%31"
        "}, {%32,%33,%34,%35}, %36, 0, 1, 1, 0;\n"
        : "=f"(d[0]),"=f"(d[1]),"=f"(d[2]),"=f"(d[3]),"=f"(d[4]),"=f"(d[5]),"=f"(d[6]),"=f"(d[7]),"=f"(d[8]),"=f"(d[9]),"=f"(d[10]),"=f"(d[11]),"=f"(d[12]),
          "=f"(d[13]),"=f"(d[14]),"=f"(d[15]),"=f"(d[16]),"=f"(d[17]),"=f"(d[18]),"=f"(d[19]),"=f"(d[20]),"=f"(d[21]),"=f"(d[22]),"=f"(d[23]),"=f"(d[24]),
          "=f"(d[25]),"=f"(d[26]),"=f"(d[27]),"=f"(d[28]),"=f"(d[29]),"=f"(d[30]),"=f"(d[31])
        : "r"(a[0]), "r"(a[1]), "r"(a[2]), "r"(a[3]), "l"(db));
}
__device__ __forceinline__ void wgmma_rs_n64_acc(float* d, const uint32_t* a, uint64_t db) {
    asm volatile("wgmma.mma_async.sync.aligned.m64n64k16.f32.bf16.bf16 {"
        "%0,%1,%2,%3,%4,%5,%6,%7,%8,%9,%10,%11,%12,%13,%14,%15,%16,%17,%18,%19,%20,%21,%22,%23,%24,%25,%26,%27,%28,%29,%30,%31"
        "}, {%32,%33,%34,%35}, %36, 1, 1, 1, 0;\n"
        : "+f"(d[0]),"+f"(d[1]),"+f"(d[2]),"+f"(d[3]),"+f"(d[4]),"+f"(d[5]),"+f"(d[6]),"+f"(d[7]),"+f"(d[8]),"+f"(d[9]),"+f"(d[10]),"+f"(d[11]),"+f"(d[12]),
          "+f"(d[13]),"+f"(d[14]),"+f"(d[15]),"+f"(d[16]),"+f"(d[17]),"+f"(d[18]),"+f"(d[19]),"+f"(d[20]),"+f"(d[21]),"+f"(d[22]),"+f"(d[23]),"+f"(d[24]),
          "+f"(d[25]),"+f"(d[26]),"+f"(d[27]),"+f"(d[28]),"+f"(d[29]),"+f"(d[30]),"+f"(d[31])
        : "r"(a[0]), "r"(a[1]), "r"(a[2]), "r"(a[3]), "l"(db));
}
__device__ __forceinline__ void wgmma_rs_n24_acc(float* d, const uint32_t* a, uint64_t db) {
    asm volatile("wgmma.mma_async.sync.aligned.m64n24k16.f32.bf16.bf16 {"
        "%0,%1,%2,%3,%4,%5,%6,%7,%8,%9,%10,%11"
        "}, {%12,%13,%14,%15}, %16, 1, 1, 1, 1;\n"
        : "+f"(d[0]),"+f"(d[1]),"+f"(d[2]),"+f"(d[3]),"+f"(d[4]),"+f"(d[5]),"+f"(d[6]),"+f"(d[7]),"+f"(d[8]),"+f"(d[9]),"+f"(d[10]),"+f"(d[11])
        : "r"(a[0]), "r"(a[1]), "r"(a[2]), "r"(a[3]), "l"(db));
}
__device__ __forceinline__ void wgmma_rs_n24_zero(float* d, const uint32_t* a, uint64_t db) {
    asm volatile("wgmma.mma_async.sync.aligned.m64n24k16.f32.bf16.bf16 {"
        "%0,%1,%2,%3,%4,%5,%6,%7,%8,%9,%10,%11"
        "}, {%12,%13,%14,%15}, %16, 0, 1, 1, 1;\n"
        : "=f"(d[0]),"=f"(d[1]),"=f"(d[2]),"=f"(d[3]),"=f"(d[4]),"=f"(d[5]),"=f"(d[6]),"=f"(d[7]),"=f"(d[8]),"=f"(d[9]),"=f"(d[10]),"=f"(d[11])
        : "r"(a[0]), "r"(a[1]), "r"(a[2]), "r"(a[3]), "l"(db));
}

constexpr int OFF_ONES = 131072;
constexpr int OFF_RING = OFF_ONES + 4096;
constexpr int NRING = 5;
constexpr int OFF_B2 = OFF_RING + NRING * 16384;
constexpr int OFF_CS = OFF_B2 + 2048;
constexpr int OFF_RS = OFF_CS + 2560;
constexpr int OFF_BAR = OFF_RS + 1024;
enum { B_FULL = 0, B_STATS = 40, B_KV = 45, B_RING = 53, B_WO = 56, B_O = 57, B_CNT2 = 65,
       B_AFREE = 65, B_ORD = 69, B_QKV = 74, B_CNT4 = 75, B_EMPTY = 75, B_AFREE0 = 80, B_DONE = 81, B_CNT8 = 82, B_TILE = 82, B_OW = 87, B_NUM = 100 };
constexpr int OFF_TS = OFF_BAR + 1024;
constexpr int SMEM_BYTES = OFF_BAR + B_NUM * 8;
constexpr unsigned FIXED_MASK = 0xB5;
constexpr float P71 = 2361183241434822606848.0f, M71 = 4.235164736271502e-22f;

__device__ __forceinline__ uint32_t exp2_fixed(float lo, float hi, uint32_t half2) {
    uint32_t y, g, d;
    asm("cvt.pack.sat.s16.s32 %0, %1, %2;" : "=r"(y) : "r"(__float_as_uint(hi)), "r"(__float_as_uint(lo)));
    asm("lop3.b32 %0, %1, 0x007F007F, %2, 0xEA;" : "=r"(g) : "r"(y), "r"(half2));
    asm("fma.rn.bf16x2 %0, %1, %2, %3;" : "=r"(d) : "r"(y), "r"(g), "r"(y & 0xFF80FF80u));
    return d;
}
constexpr uint64_t DK_STEP = 512 - (256ull << 16), DV_STEP = 512 - (256ull << 32);
constexpr uint32_t POS_STD = 0x76543210u, POS_LAST = 0xB75A9640u;

__global__ void __cluster_dims__(2, 1, 1) __launch_bounds__(640, 1)
mega_kernel(const __nv_bfloat16* __restrict__ x, const __nv_bfloat16* __restrict__ wqkv, const __nv_bfloat16* __restrict__ w1,
            const __nv_bfloat16* __restrict__ w3, __nv_bfloat16* __restrict__ out,
            const __grid_constant__ CUtensorMap mx, const __grid_constant__ CUtensorMap mqkv, const __grid_constant__ CUtensorMap mw1,
            const __grid_constant__ CUtensorMap mw3, const __grid_constant__ CUtensorMap mw2, const __grid_constant__ CUtensorMap mwo,
            uint32_t half2) {
    extern __shared__ __align__(1024) uint8_t smem_raw[];
    const uint32_t sb = __shfl_sync(0xffffffffu, smem_u32(smem_raw), 0);
    if ((sb & 0xFFFFFF) != SMEM_BASE) __trap();
    const uint32_t bars = sb + OFF_BAR, ring = sb + OFF_RING;
    const int tid = threadIdx.x, lane = tid & 31, g = lane >> 2, t4 = lane & 3;
    const int warp = __shfl_sync(0xffffffffu, tid >> 5, 0), wg = warp >> 2, wq = warp & 3;
    const int rank = blockIdx.x & 1, cl = blockIdx.x >> 1;
    const int grp = cl < 4 ? 4 + cl : cl < 36 ? (cl - 4) >> 3 : 4 + (cl - 36) / 7;
    const int rot = cl < 4 ? 7 : cl < 36 ? (cl - 4) & 7 : (cl - 36) % 7;
    const int mblk = rot * 2 + rank;
    const int nq = grp < 4 ? 2 : 1;
    const int qt0 = grp < 4 ? 2 * grp : 4 + grp;
    const int gu0 = (grp < 4 ? 3 * grp : 4 * grp - 4) - nq;
    const int head = blockIdx.x >> 2, qb = blockIdx.x & 3;

    if (elect_one()) {
#pragma unroll
        for (int i = 0; i < 5; i++) { const int b = warp * 5 + i; mbar_init(bars + 8 * b, b < B_CNT2 ? 1 : b < B_CNT4 ? 2 : b < B_CNT8 ? 4 : 8); }
        if (warp == 0) {
            fence_async_smem();
#pragma unroll
            for (int j = 0; j < 2; j++) {
                tma2d(sb + j * 16384, &mx, j * 64, mblk * 128, bars + 8 * (B_FULL + j));
                tma2d(ring + j * 16384, &mqkv, qt0 * 128, j * 64, bars + 8 * (B_FULL + j));
                tma2d(ring + j * 16384 + 8192, &mqkv, qt0 * 128 + 64, j * 64, bars + 8 * (B_FULL + j));
            }
        }
        if (warp < 8) {
#pragma unroll
            for (int i = 0; i < 5; i++) mbar_expect(bars + 8 * (warp * 5 + i), warp * 5 + i < 8 ? 32768 : 16384);
        }
        if (warp == 16) asm volatile("prefetch.tensormap [%0];" :: "l"(rank ? &mw3 : &mw1) : "memory");
        asm volatile("fence.mbarrier_init.release.cluster;" ::: "memory");
    }
    __syncthreads();
    if (tid == 512) TSTAMP(26);
    asm volatile("barrier.cluster.arrive.relaxed.aligned;" ::: "memory");

    if (wg < 4) {
        const int pair = wg >> 1, half = wg & 1;
        if (pair == 1) {
            const int row = mblk * 128 + grp * 16 + (warp - 8) * 2 + (lane >> 4);
            uint4 v[6];
            const uint32_t* w = reinterpret_cast<const uint32_t*>(v);
#pragma unroll
            for (int j = 0; j < 2; j++) v[4 + j] = __ldg(reinterpret_cast<const uint4*>(wqkv + (size_t)(rot * 64 + (warp - 8) * 8 + j * 4 + (lane >> 3)) * (3 * DM) + qt0 * 128 + rank * 64) + (lane & 7));
#pragma unroll
            for (int j = 0; j < 4; j++) v[j] = __ldg(reinterpret_cast<const uint4*>(x + (size_t)row * DM) + j * 16 + (lane & 15));
            const uint32_t tag = ld_epoch() + 1;
            float c[8];
#pragma unroll
            for (int e = 0; e < 4; e++) { c[2 * e] = bf_lo(w[16 + e]) + bf_lo(w[20 + e]); c[2 * e + 1] = bf_hi(w[16 + e]) + bf_hi(w[20 + e]); }
#pragma unroll
            for (int n = 4; n > 1; n >>= 1) {
                const bool up = lane & (4 * n);
#pragma unroll
                for (int e = 0; e < n; e++) c[e] = (up ? c[e + n] : c[e]) + __shfl_xor_sync(0xffffffffu, up ? c[e] : c[e + n], 4 * n);
            }
            asm volatile("st.shared.v2.f32 [%0], {%1,%2};" :: "r"(sb + OFF_CS + 512 + (warp - 8) * 256 + (lane & 7) * 32 + (lane >> 3) * 8), "f"(c[0]), "f"(c[1]) : "memory");
            bar_sync(6, 256);
            if (warp < 10) {
#pragma unroll
                for (int e = 0; e < 8; e++) asm volatile("ld.shared.f32 %0, [%1];" : "=f"(c[e]) : "r"(sb + OFF_CS + 512 + e * 256 + (tid & 63) * 4));
                st_tagged(reinterpret_cast<unsigned long long*>(g_cs) + (grp * 40 + rot) * 128 + rank * 64 + (tid & 63),
                          __float_as_uint(((c[0] + c[1]) + (c[2] + c[3])) + ((c[4] + c[5]) + (c[6] + c[7]))), tag);
                if (tid == 256) TSTAMP(40);
            }
            float sa[4] = {0.f, 0.f, 0.f, 0.f}, sq[4] = {0.f, 0.f, 0.f, 0.f};
#pragma unroll
            for (int j = 0; j < 16; j++) sa[j & 3] += bf_lo(w[j]) + bf_hi(w[j]);
            float mean = ((sa[0] + sa[1]) + (sa[2] + sa[3])) * (1.0f / 32);
#pragma unroll
            for (int j = 0; j < 16; j++) { const float a = bf_lo(w[j]) - mean, b = bf_hi(w[j]) - mean; sq[j & 1] = fmaf(a, a, sq[j & 1]); sq[2 + (j & 1)] = fmaf(b, b, sq[2 + (j & 1)]); }
            float m2 = (sq[0] + sq[1]) + (sq[2] + sq[3]);
#pragma unroll
            for (int d = 1; d < 16; d <<= 1) {
                const float om = __shfl_xor_sync(0xffffffffu, mean, d), o2 = __shfl_xor_sync(0xffffffffu, m2, d), dm = mean - om;
                m2 = fmaf(dm * dm, 16.0f * d, m2 + o2); mean = 0.5f * (mean + om);
            }
            float sd;
            asm("sqrt.approx.f32 %0, %1;" : "=f"(sd) : "f"(bf_round(bf_round(m2 * (1.0f / DM)) + 1e-5f)));
            if ((lane & 15) == 0) st_tagged(reinterpret_cast<unsigned long long*>(g_rs) + row, pack_bf16(mean, sd), tag);
            if (tid == 256) TSTAMP(45);
        }

        uint32_t q[4], qn[6];
        {
            const int rowblk = mblk * 2 + half, tile16 = rowblk * 4 + wq;
            const bool rel = wq < 2 && lane == 0, rel2 = wq == 2 && lane == 0;
            uint32_t empty;
            asm("mapa.shared::cluster.u32 %0, %1, %2;" : "=r"(empty) : "r"(bars + 8 * B_EMPTY), "r"(wq & 1));
#pragma unroll 1
            for (int t = pair; t < 5; t += 2) {
                float acc[64];
                uint32_t po = t == 4 ? POS_LAST : POS_STD, full = bars + 8 * (B_FULL + 8 * t), slot = (0x24130u >> (4 * t)) & 7, prev = 0;
                uint64_t da = mkdesc(half * 8192, 16, 1024, 1), db = mkdesc(OFF_RING, 8192, 1024, 1) + slot * 1024;
                if (tid == 0 && t == 0) TSTAMP(30);
                mbar_wait(full, 0);
                if (t > 0) mbar_wait(bars + 8 * (B_ORD + t - 1), 0);
#pragma unroll 1
                for (int j = 0; j < 8; j++) {
                    wg_fence();
#pragma unroll
                    for (int k = 0; k < 4; k++) wgmma_ss_n128(acc, da + k * 2, db + k * 128, (j | k) != 0);
                    wg_commit();
                    const uint32_t rel_a = empty + prev * 8, rel_b = bars + 8 * (j == 3 ? B_AFREE0 : B_AFREE + (j >> 1) - 1);
                    const bool do_a = j > 0 && rel, do_b = (po & 8) && rel2;
                    prev = slot; slot = slot == NRING - 1 ? 0 : slot + 1; po >>= 4; full += 8;
                    da = mkdesc(half * 8192, 16, 1024, 1) + (po & 7) * 1024; db = mkdesc(OFF_RING, 8192, 1024, 1) + slot * 1024;
                    if (j < 7) mbar_wait(full, 0); else if (rel2) mbar_arrive(bars + 8 * (B_ORD + t));
                    wg_wait<1>();
                    if (do_a) mbar_arrive_remote(rel_a);
                    if (do_b) mbar_arrive(rel_b);
                }
                if (t >= 3) {
                    mbar_wait(bars + 8 * B_QKV, 0);
                    const uint4* pq = g_q + (head * 128 + (qb * 8 + wg) * 4 + wq) * 32 + lane;
                    const uint4 v = __ldcg(pq), u = __ldcg(pq + 512);
                    qn[0] = v.x; qn[1] = v.y; qn[2] = v.z; qn[3] = v.w; q[0] = u.x; q[1] = u.y; q[2] = u.z; q[3] = u.w;
                }
                wg_wait<0>();
                if (rel) mbar_arrive_remote(empty + prev * 8);
                if (t >= 3 && rel2) mbar_arrive(bars + 8 * (t == 4 ? B_AFREE + 3 : B_AFREE0));
                pin<64>(acc);
                if (wq == 0 && half == 0 && lane == 0) TSTAMP(2 + 2 * t);
                mbar_wait(bars + 8 * (B_STATS + t), 0);
                uint32_t rs0, rs1;
                asm volatile("ld.shared.b32 %0, [%1];" : "=r"(rs0) : "r"(sb + OFF_RS + (half * 64 + wq * 16 + g) * 4));
                asm volatile("ld.shared.b32 %0, [%1];" : "=r"(rs1) : "r"(sb + OFF_RS + (half * 64 + wq * 16 + g + 8) * 4));
                const float m0 = bf_lo(rs0), m1 = bf_lo(rs1);
                float d0 = bf_hi(rs0), d1 = bf_hi(rs1);
#pragma unroll
                for (int j = 0; j < 16; j++) {
                    float c0, c1;
                    asm volatile("ld.shared.v2.f32 {%0,%1}, [%2];" : "=f"(c0), "=f"(c1) : "r"(sb + OFF_CS + (t * 128 + j * 8 + t4 * 2) * 4));
                    acc[4 * j] = fmaf(-m0, c0, acc[4 * j]); acc[4 * j + 1] = fmaf(-m0, c1, acc[4 * j + 1]);
                    acc[4 * j + 2] = fmaf(-m1, c0, acc[4 * j + 2]); acc[4 * j + 3] = fmaf(-m1, c1, acc[4 * j + 3]);
                }
                float r0 = rcpf(d0), r1 = rcpf(d1);
                if (t < nq) {
                    const int qt = qt0 + t;
                    if (qt < 4) {
                        r0 *= 0.25f * 1.4426950408889634f * M71; r1 *= 0.25f * 1.4426950408889634f * M71;
                    } else if (qt < 8) {
                        r0 *= ((FIXED_MASK >> (2 * wq)) & 1) ? M71 : P71; r1 *= ((FIXED_MASK >> (2 * wq + 1)) & 1) ? M71 : P71;
                    }
                    uint32_t e[32];
#pragma unroll
                    for (int i = 0; i < 32; i++) { const float r = (i & 1) ? r1 : r0; e[i] = pack_bf16(acc[2 * i] * r, acc[2 * i + 1] * r); }
                    if (qt < 4) {
                        uint4* p = g_q + (qt * 1024 + tile16) * 32 + lane;
#pragma unroll
                        for (int hh = 0; hh < 8; hh++) p[hh * 4096] = make_uint4(e[4 * hh], e[4 * hh + 1], e[4 * hh + 2], e[4 * hh + 3]);
                    } else {
                        uint32_t* p = reinterpret_cast<uint32_t*>(g_kv + (qt - 4) * 32768) + tile16 * 64 + lane;
#pragma unroll
                        for (int i = 0; i < 32; i++) p[(i >> 1) * 8192 + (i & 1) * 32] = e[i];
                    }
                } else {
                    uint32_t* p = reinterpret_cast<uint32_t*>(g_h + (rowblk * 28 + gu0 + t) * 512) + wq * 512 + lane;
                    r0 *= -1.4426950408889634f; r1 *= -1.4426950408889634f; d0 *= d0; d1 *= d1;
#pragma unroll
                    for (int j = 0; j < 8; j++) {
                        const float* a = acc + j * 4; const float* b = a + 32;
                        p[j * 32] = pack_bf16(a[0] * b[0] * rcpf(fmaf(ex2f(a[0] * r0), d0, d0)), a[1] * b[1] * rcpf(fmaf(ex2f(a[1] * r0), d0, d0)));
                        p[256 + j * 32] = pack_bf16(a[2] * b[2] * rcpf(fmaf(ex2f(a[2] * r1), d1, d1)), a[3] * b[3] * rcpf(fmaf(ex2f(a[3] * r1), d1, d1)));
                    }
                }
                __syncwarp();
                if (elect_one()) mbar_arrive(bars + 8 * (B_TILE + t));
                if (wq == 0 && half == 0 && lane == 0) TSTAMP(3 + 2 * t);
            }
        }
        const uint64_t db2 = mkdesc(OFF_B2, 128, 256, 0);
        float s[32];
        auto ref_point = [&](int ntile, uint32_t& b0, uint32_t& b1) {
            float m0 = -INFINITY, m1 = -INFINITY, f0 = -INFINITY, f1 = -INFINITY;
#pragma unroll 1
            for (int t = 0; t < ntile; t++) {
                wg_fence();
                wgmma_rs_n64_zero(s, q, mkdesc(4096, 94208, 128, 0) + (t >> 2) * DK_STEP + (t & 3) * 64);
                wg_commit();
                wg_wait<0>();
                pin<32>(s);
#pragma unroll
                for (int i = 0; i < 8; i++) {
                    if ((FIXED_MASK >> i) & 1) { f0 = fmaxf(f0, fmaxf(s[4 * i], s[4 * i + 1])); f1 = fmaxf(f1, fmaxf(s[4 * i + 2], s[4 * i + 3])); }
                    else                       { m0 = fmaxf(m0, fmaxf(s[4 * i], s[4 * i + 1])); m1 = fmaxf(m1, fmaxf(s[4 * i + 2], s[4 * i + 3])); }
                }
            }
            m0 = fmaxf(m0, f0 * P71 * P71); m1 = fmaxf(m1, f1 * P71 * P71);
            m0 = fmaxf(m0, __shfl_xor_sync(0xffffffffu, m0, 1)); m1 = fmaxf(m1, __shfl_xor_sync(0xffffffffu, m1, 1));
            m0 = fmaxf(m0, __shfl_xor_sync(0xffffffffu, m0, 2)); m1 = fmaxf(m1, __shfl_xor_sync(0xffffffffu, m1, 2));
#pragma unroll
            for (int r = 0; r < 2; r++) {
                const float m = -rintf(r ? m1 : m0), mh = bf_round(m), mm = bf_round(m - mh), ml = m - mh - mm;
                const float lo = t4 == 0 ? mh : t4 == 1 ? ml : t4 == 2 ? 1.f : 0.f, hi = t4 == 0 ? mm : t4 == 1 ? 1.f : 0.f;
                (r ? b1 : b0) = pack_bf16(lo * M71, hi * M71);
            }
        };
        uint32_t q2[4];
        int redo = 1;
        mbar_wait(bars + 8 * B_KV, 0);
#pragma unroll 1
        for (int round = -1; round < 2;) {
            if (redo) ref_point(redo, q2[0], q2[1]);
            if (round < 0) {
#pragma unroll
                for (int i = 0; i < 4; i++) { const uint32_t tq = q[i]; q[i] = qn[i]; qn[i] = tq; }
                qn[4] = q2[0]; qn[5] = q2[1];
                q2[2] = __shfl_sync(0xffffffffu, q2[0], 3); q2[3] = __shfl_sync(0xffffffffu, q2[1], 3);
                round = 0;
                continue;
            }
            float o[12]; uint32_t p[16];
#pragma unroll
            for (int i = 0; i < 12; i++) o[i] = 0.f;
            pin<12>(o); pin<4>(q2);
            if (wq == 0 && half == 0 && lane == 0) TSTAMP(12 + 4 * round + pair);
            uint64_t dk = mkdesc(4096, 94208, 128, 0), dv = mkdesc(0, 128, 65536, 0);
#pragma unroll 1
            for (int c = 0; c < 8; c++, dk += DK_STEP, dv += DV_STEP) {
                if (round == 0) mbar_wait(bars + 8 * (B_KV + c), 0);
#pragma unroll
                for (int t = 0; t < 4; t++) {
                    wg_fence();
                    wgmma_rs_n64_zero(s, q, dk + t * 64);
                    wgmma_rs_n64_acc(s, q2, db2);
                    wg_commit();
                    wg_wait<0>();
                    pin<32>(s); pin<16>(p);
#pragma unroll
                    for (int i = 0; i < 16; i++) {
                        if ((FIXED_MASK >> (i >> 1)) & 1) p[i] = exp2_fixed(s[2 * i], s[2 * i + 1], half2);
                        else                              p[i] = pack_bf16(ex2f(s[2 * i]), ex2f(s[2 * i + 1]));
                    }
                    wg_fence();
#pragma unroll
                    for (int k = 0; k < 4; k++) wgmma_rs_n24_acc(o, p + 4 * k, dv + (t * 4 + k) * 16);
                    wg_commit();
                }
            }
            wg_wait<0>();
            pin<12>(o);
            if (redo != 32) {
                float chk = (o[8] + o[10]) * 256.f;
#pragma unroll
                for (int i = 0; i < 8; i++) chk += fabsf(o[i]);
                uint32_t bad;
                asm volatile("{\n.reg .pred p, q;\nsetp.geu.f32 q, %1, 0f7F800000;\nbar.red.or.pred p, %2, 128, q;\nselp.u32 %0, 1, 0, p;\n}" : "=r"(bad) : "f"(chk), "r"(1 + wg) : "memory");
                if (__any_sync(0xffffffffu, bad)) { redo = 32; continue; }
            }
            const int rowblk = qb * 8 + round * 4 + wg;
            const float r0 = rcpf(o[8]), r1 = rcpf(o[10]);
            uint32_t* po = reinterpret_cast<uint32_t*>(g_o + (rowblk * 8 + (head >> 2)) * 512) + wq * 512 + (head & 3) * 64 + lane;
            po[0] = pack_bf16(o[0] * r0, o[1] * r0); po[256] = pack_bf16(o[2] * r1, o[3] * r1);
            po[32] = pack_bf16(o[4] * r0, o[5] * r0); po[288] = pack_bf16(o[6] * r1, o[7] * r1);
            if (round == 0) {
                __syncwarp();
                if (elect_one()) mbar_arrive(bars + 8 * (B_OW + pair));
            } else {
                bar_sync(1 + wg, 128);
                if (wq == 0 && elect_one()) { mbar_arrive(bars + 8 * B_DONE); signal_cnt(C_O + rowblk); }
            }
#pragma unroll
            for (int i = 0; i < 4; i++) q[i] = qn[i];
            q2[0] = qn[4]; q2[1] = qn[5];
            redo = 0;
            if (wq == 0 && half == 0 && lane == 0) TSTAMP(14 + 4 * round + pair);
            round++;
        }
    } else {
        uint32_t tag;
        if (wq == 0) {
            asm volatile("barrier.cluster.wait.aligned;" ::: "memory");
            if (tid == 512) TSTAMP(27);
            uint32_t slot = 2, ph = 1;
#pragma unroll 1
            for (int n = 2; n < 40; n++) {
                const int t = n >> 3, j = n & 7;
                const int kc = (n < 32 ? j : (POS_LAST >> (4 * j)) & 7) * 64;
                const CUtensorMap* m = t < nq ? &mqkv : rank ? &mw3 : &mw1;
                const int col = t < nq ? (qt0 + t) * 128 + rank * 64 : (gu0 + t) * 64;
                const uint32_t dst = ring + slot * 16384 + rank * 8192, fb = bars + 8 * (B_FULL + n);
                if (n < 8 && elect_one()) tma2d(sb + n * 16384, &mx, kc, mblk * 128, fb);
                mbar_wait(bars + 8 * (B_EMPTY + slot), ph);
                if (elect_one()) { TS2(0, n); tma2d_mc(dst, m, col, kc, fb); }
                if (++slot == NRING) { slot = 0; ph ^= 1; }
            }
            tag = ld_epoch() + 1;
        } else if (wq == 1) {
            tag = ld_epoch() + 1;
            mbar_wait(bars + 8 * (B_FULL + 5), 0);
#pragma unroll 1
            for (int t = 0; t < 5; t++) {
                float a[4];
#pragma unroll 1
                for (int n = 0; n < 2000000; n++) {
                    uint32_t stale = 0;
                    a[0] = a[1] = a[2] = a[3] = 0.f;
#pragma unroll
                    for (int i = 0; i < 16; i++) {
                        uint32_t u, v;
                        stale |= ld_tagged2(g_cs + (grp * 5 + t) * 512 + i * 32 + lane, tag, u, v);
                        a[(i & 1) * 2] += __uint_as_float(u); a[(i & 1) * 2 + 1] += __uint_as_float(v);
                    }
                    if (__all_sync(0xffffffffu, stale == 0)) break;
                    if (t) __nanosleep(400);
                }
                asm volatile("st.shared.v2.f32 [%0], {%1,%2};" :: "r"(sb + OFF_CS + t * 512 + lane * 8), "f"(a[0]), "f"(a[1]) : "memory");
                asm volatile("st.shared.v2.f32 [%0], {%1,%2};" :: "r"(sb + OFF_CS + t * 512 + 256 + lane * 8), "f"(a[2]), "f"(a[3]) : "memory");
                if (t == 0) {
                    uint32_t r[4];
#pragma unroll 1
                    for (int n = 0; n < 2000000; n++) {
                        const uint32_t stale = ld_tagged2(g_rs + mblk * 64 + lane * 2, tag, r[0], r[1]) | ld_tagged2(g_rs + mblk * 64 + lane * 2 + 1, tag, r[2], r[3]);
                        if (__all_sync(0xffffffffu, stale == 0)) break;
                    }
                    asm volatile("st.shared.v4.b32 [%0], {%1,%2,%3,%4};" :: "r"(sb + OFF_RS + lane * 16), "r"(r[0]), "r"(r[1]), "r"(r[2]), "r"(r[3]) : "memory");
                }
                __syncwarp();
                if (elect_one()) { mbar_arrive(bars + 8 * (B_STATS + t)); TSTAMP(32 + t); }
            }
        } else {
            tag = ld_epoch() + 1;
            mbar_wait(bars + 8 * (B_FULL + wq - 1), 0);
#pragma unroll 1
            for (int t = wq - 1; t < 5; t += 2) {
                const __nv_bfloat16* src; int ld;
                if (t < nq) { src = wqkv + (qt0 + t) * 128 + rank * 64; ld = 3 * DM; }
                else        { src = (rank ? w3 : w1) + (gu0 + t) * 64; ld = FF; }
                src += (size_t)(rot * 64 + (lane >> 3)) * ld + (lane & 7) * 8;
                uint4 v[16];
                const uint32_t* w = reinterpret_cast<const uint32_t*>(v);
#pragma unroll
                for (int j = 0; j < 16; j++) v[j] = __ldg(reinterpret_cast<const uint4*>(src + (size_t)j * 4 * ld));
                float c[8];
#pragma unroll
                for (int e = 0; e < 4; e++) {
                    float a = 0.f, b = 0.f;
#pragma unroll
                    for (int j = 0; j < 16; j++) { a += bf_lo(w[4 * j + e]); b += bf_hi(w[4 * j + e]); }
                    c[2 * e] = a; c[2 * e + 1] = b;
                }
#pragma unroll
                for (int n = 4; n > 1; n >>= 1) {
                    const bool up = lane & (4 * n);
#pragma unroll
                    for (int e = 0; e < n; e++) c[e] = (up ? c[e + n] : c[e]) + __shfl_xor_sync(0xffffffffu, up ? c[e] : c[e + n], 4 * n);
                }
                unsigned long long* dst = reinterpret_cast<unsigned long long*>(g_cs) + ((grp * 5 + t) * 8 + rot) * 128 + rank * 64 + (lane & 7) * 8 + (lane >> 3) * 2;
                st_tagged(dst, __float_as_uint(c[0]), tag); st_tagged(dst + 1, __float_as_uint(c[1]), tag);
                if (lane == 0) TSTAMP(40 + t);
            }
        }
        if (wq == 3) {
#pragma unroll 1
            for (int i = lane; i < 256; i += 32) asm volatile("st.shared.v4.b32 [%0], {%1,%1,%1,%1};" :: "r"(sb + OFF_ONES + i * 16), "r"(0x3F803F80u) : "memory");
#pragma unroll 1
            for (int i = lane; i < 128; i += 32) {
                const bool fx = (FIXED_MASK >> (i >> 4)) & 1;
                uint32_t a = fx ? pack_bf16(M71, M71) : pack_bf16(P71, P71);
                uint32_t b = fx ? pack_bf16(M71, 47.0f * M71) : pack_bf16(P71, -79.5f * P71);
                uint32_t c = fx ? 0u : pack_bf16(0.08214f * P71, 0.f);
                if (i & 8) a = b = c = 0;
                asm volatile("st.shared.v4.b32 [%0], {%1,%2,%3,%4};" :: "r"(sb + OFF_B2 + i * 16), "r"(a), "r"(b), "r"(c), "r"(0) : "memory");
            }
            fence_async_smem();
            __syncwarp();
            if (elect_one()) mbar_arrive(bars + 8 * B_QKV);
        } else if (wq == 1) {
#pragma unroll 1
            for (int i = 0; i < 3; i++) wait_cnt(C_QKV + i * 4 + (head >> 3), 16 * tag, 100);
            fence_async_all();
            if (elect_one()) { mbar_arrive(bars + 8 * B_QKV); TSTAMP(29); }
            const uint8_t* gk = reinterpret_cast<const uint8_t*>(g_kv + head * 4096);
            const uint8_t* gv = reinterpret_cast<const uint8_t*>(g_kv + (32 + head) * 4096);
#pragma unroll 1
            for (int c = 0; c < 8; c++) {
                if (!(c & 1)) mbar_wait(bars + 8 * (c ? B_AFREE + (c >> 1) : B_AFREE0), 0);
                if (elect_one()) {
                    const uint32_t b = bars + 8 * (B_KV + c);
                    mbar_expect(b, 16384);
                    bulk_load(sb + (2 * c + 1) * 4096, gk + c * 4096, 4096, b);
                    bulk_load(sb + 2 * c * 4096, gv + c * 4096, 4096, b);
                    bulk_load(sb + 65536 + c * 4096, gv + 32768 + c * 4096, 4096, b);
                    bulk_load(sb + 98304 + c * 4096, gk + 32768 + c * 4096, 4096, b);
                }
            }
        } else if (wq == 2) {
#pragma unroll 1
            for (int t = 0; t < 5; t++) {
                mbar_wait(bars + 8 * (B_TILE + t), 0);
                if (elect_one()) signal_cnt(t < nq ? C_QKV + qt0 + t : C_H + mblk);
            }
        }
        pin<1>(&tag);
        bar_sync(5, 128);
        if (tid == 639) g_epoch[blockIdx.x] = tag;
        const int cb = blockIdx.x & 7, pr = blockIdx.x >> 3;
        const int rb0 = (pr >> 2) * 8 + (pr & 3);
        uint32_t gate[2][16];
        {
            float dn[64];
            auto load_stage = [&](int kb, int st) {
                const uint32_t b = bars + 8 * (B_RING + st), dst = ring + st * 24576;
                mbar_expect(b, 24576);
                bulk_load(dst, g_h + (rb0 * 28 + kb) * 512, 8192, b);
                bulk_load(dst + 8192, g_h + ((rb0 + 4) * 28 + kb) * 512, 8192, b);
                tma2d(dst + 16384, &mw2, cb * 64, kb * 64, b);
            };
            if (wq == 0) {
                wait_cnt(C_H + (rb0 >> 1), 28 * tag, 200);
                wait_cnt(C_H + (rb0 >> 1) + 2, 28 * tag, 200);
                if (elect_one()) { TSTAMP(20); fence_async_all(); load_stage(0, 0); load_stage(1, 1); }
            }
            int st = 0; uint32_t ph = 0;
#pragma unroll 1
            for (int kb = 0; kb < 28; kb++) {
                mbar_wait(bars + 8 * (B_RING + st), ph);
                const uint64_t da = mkdesc(OFF_RING + st * 24576, 128, 1024, 0), db = mkdesc(OFF_RING + st * 24576 + 16384, 8192, 1024, 1);
                wg_fence();
#pragma unroll
                for (int k = 0; k < 4; k++) { wgmma_ss_n64(dn, da + k * 16, db + k * 128, (kb | k) != 0); wgmma_ss_n64(dn + 32, da + 512 + k * 16, db + k * 128, (kb | k) != 0); }
                wg_commit();
                wg_wait<1>();
                if (wq == 0 && kb < 26 && elect_one()) load_stage(kb + 2, st == 0 ? 2 : st - 1);
                if (++st == 3) { st = 0; ph ^= 1; }
            }
            wg_wait<0>();
            pin<64>(dn);
#pragma unroll
            for (int i = 0; i < 32; i++) gate[i >> 4][i & 15] = pack_bf16(siluf(dn[2 * i]), siluf(dn[2 * i + 1]));
        }
        float acc[32];
        if (tid == 512) TSTAMP(21);
        const uint32_t bar_wo = bars + 8 * B_WO;
        if (wq == 0 && elect_one()) {
            mbar_expect(bar_wo, 65536);
#pragma unroll 1
            for (int i = 0; i < 8; i++) tma2d(ring + i * 8192, &mwo, cb * 64, i * 64, bar_wo);
        }
        if (wq >= 2) {
            mbar_wait(bars + 8 * (B_OW + wq - 2), 0);
            if (elect_one()) {
                signal_cnt(C_O + qb * 8 + 2 * wq - 4);
                asm volatile("red.relaxed.gpu.global.add.u32 [%0], 1;" :: "l"(g_cnt + (C_O + qb * 8 + 2 * wq - 3) * 8) : "memory");
            }
        }
#pragma unroll 1
        for (int tl = 0; tl < 2; tl++) {
            const int rb = rb0 + 4 * tl;
            uint32_t xr[16];
            const uint32_t* px = reinterpret_cast<const uint32_t*>(x + (size_t)(rb * 64 + wq * 16 + g) * DM + cb * 64) + t4;
#pragma unroll
            for (int j = 0; j < 8; j++) { xr[2 * j] = __ldg(px + j * 4); xr[2 * j + 1] = __ldg(px + 8 * DM / 2 + j * 4); }
            if (wq == 0) {
                if (tl == 1) mbar_wait(bars + 8 * B_DONE, 0);
                wait_cnt(C_O + rb, 32 * tag, tl ? 20 : 200);
                if (elect_one()) {
                    fence_async_all();
                    TSTAMP(22 + 2 * tl);
#pragma unroll 1
                    for (int i = 0; i < (tl ? 8 : 2); i++) {
                        mbar_expect(bars + 8 * (B_O + i), 8192);
                        bulk_load((tl ? sb : ring + 65536) + i * 8192, g_o + (rb * 8 + i) * 512, 8192, bars + 8 * (B_O + i));
                    }
                }
            }
            if (tl == 0) mbar_wait(bar_wo, 0);
#pragma unroll 1
            for (int kb = 0; kb < 8; kb++) {
                mbar_wait(bars + 8 * (B_O + kb), tl);
                const uint32_t a = tl == 0 ? OFF_RING + 65536 + (kb & 1) * 8192 : kb * 8192;
                const uint64_t da = mkdesc(a, 128, 1024, 0), db = mkdesc(OFF_RING + kb * 8192, 8192, 1024, 1);
                wg_fence();
#pragma unroll
                for (int k = 0; k < 4; k++) wgmma_ss_n64(acc, da + k * 16, db + k * 128, (kb | k) != 0);
                wg_commit();
                if (tl == 0) {
                    wg_wait<0>();
                    bar_sync(5, 128);
                    if (wq == 0 && kb < 6 && elect_one()) { mbar_expect(bars + 8 * (B_O + kb + 2), 8192); bulk_load(sb + a, g_o + (rb * 8 + kb + 2) * 512, 8192, bars + 8 * (B_O + kb + 2)); }
                }
            }
            wg_wait<0>();
            pin<32>(acc);
            uint32_t* po = reinterpret_cast<uint32_t*>(out + (size_t)(rb * 64 + wq * 16 + g) * DM + cb * 64) + t4;
#pragma unroll
            for (int i = 0; i < 16; i++) {
                const uint32_t r = pack_bf16(fmaf(acc[2 * i], bf_lo(gate[0][i]), bf_lo(xr[i])), fmaf(acc[2 * i + 1], bf_hi(gate[0][i]), bf_hi(xr[i])));
                po[(i & 1) * (8 * DM / 2) + (i >> 1) * 4] = r;
                gate[0][i] = gate[1][i];
            }
            if (tid == 512) TSTAMP(23 + 2 * tl);
        }
    }
}

typedef CUresult (*EncodeFn)(CUtensorMap*, CUtensorMapDataType, cuuint32_t, void*, const cuuint64_t*, const cuuint64_t*, const cuuint32_t*,
                             const cuuint32_t*, CUtensorMapInterleave, CUtensorMapSwizzle, CUtensorMapL2promotion, CUtensorMapFloatOOBfill);

void make_map(EncodeFn fn, CUtensorMap* m, const void* p, int rows, int cols, int box_rows) {
    cuuint64_t dims[2] = {(cuuint64_t)cols, (cuuint64_t)rows};
    cuuint64_t strides[1] = {(cuuint64_t)cols * 2};
    cuuint32_t box[2] = {64, (cuuint32_t)box_rows};
    cuuint32_t es[2] = {1, 1};
    fn(m, CU_TENSOR_MAP_DATA_TYPE_BFLOAT16, 2, const_cast<void*>(p), dims, strides, box, es, CU_TENSOR_MAP_INTERLEAVE_NONE,
       CU_TENSOR_MAP_SWIZZLE_128B, CU_TENSOR_MAP_L2_PROMOTION_L2_128B, CU_TENSOR_MAP_FLOAT_OOB_FILL_NONE);
}

}

extern "C" void kernel_launch(void* const* d_in, const int* in_sizes, int n_in, void* d_out, int out_size) {
    const __nv_bfloat16* x = (const __nv_bfloat16*)d_in[0];
    static EncodeFn fn = nullptr;
    if (!fn) {
        cudaDriverEntryPointQueryResult qr;
        cudaGetDriverEntryPoint("cuTensorMapEncodeTiled", (void**)&fn, cudaEnableDefault, &qr);
        cudaFuncSetAttribute(mega_kernel, cudaFuncAttributeMaxDynamicSharedMemorySize, SMEM_BYTES);
    }
    CUtensorMap mx, mqkv, mw1, mw3, mw2, mwo;
    make_map(fn, &mx, d_in[0], SEQ, DM, 128);
    make_map(fn, &mqkv, d_in[1], DM, 3 * DM, 64);
    make_map(fn, &mwo, d_in[2], DM, DM, 64);
    make_map(fn, &mw1, d_in[4], DM, FF, 64);
    make_map(fn, &mw3, d_in[5], DM, FF, 64);
    make_map(fn, &mw2, d_in[6], FF, DM, 64);
    mega_kernel<<<128, 640, SMEM_BYTES, cudaStreamPerThread>>>(x, (const __nv_bfloat16*)d_in[1], (const __nv_bfloat16*)d_in[4], (const __nv_bfloat16*)d_in[5],
                                                               (__nv_bfloat16*)d_out, mx, mqkv, mw1, mw3, mw2, mwo, 0x3F003F00u);
}
```

```cpp
#include <cuda_runtime.h>
#include <cuda_bf16.h>
#include <cuda.h>
#include <stdint.h>

namespace {

constexpr int SEQ = 2048, DM = 512, FF = 1792;

__device__ uint4 g_q[32 * 128 * 32];
__device__ uint4 g_kv[64 * 4096];
__device__ uint4 g_h[32 * 28 * 512];
__device__ uint4 g_o[32 * 8 * 512];
__device__ ulonglong2 g_cs[40 * 8 * 64];
__device__ ulonglong2 g_rs[SEQ / 2];
constexpr int C_QKV = 0, C_H = 12, C_O = 28, C_NUM = 60;
__device__ unsigned g_cnt[C_NUM * 8];
__device__ unsigned g_epoch[128];
#define TSTAMP(i)
#define TS2(k, i)

__device__ __forceinline__ uint32_t smem_u32(const void* p) { return (uint32_t)__cvta_generic_to_shared(p); }
__device__ __forceinline__ void mbar_init(uint32_t a, int c) { asm volatile("mbarrier.init.shared::cta.b64 [%0], %1;" :: "r"(a), "r"(c)); }
__device__ __forceinline__ void mbar_expect(uint32_t a, int b) { asm volatile("mbarrier.arrive.expect_tx.shared::cta.b64 _, [%0], %1;" :: "r"(a), "r"(b) : "memory"); }
__device__ __forceinline__ void mbar_arrive(uint32_t a) { asm volatile("mbarrier.arrive.shared::cta.b64 _, [%0];" :: "r"(a) : "memory"); }
__device__ __forceinline__ void mbar_arrive_remote(uint32_t a) { asm volatile("mbarrier.arrive.shared::cluster.b64 _, [%0];" :: "r"(a) : "memory"); }
__device__ __forceinline__ bool mbar_try(uint32_t a, uint32_t ph) {
    uint32_t ok;
    asm volatile("{\n.reg .pred p;\nmbarrier.try_wait.parity.shared::cta.b64 p, [%1], %2;\nselp.u32 %0, 1, 0, p;\n}" : "=r"(ok) : "r"(a), "r"(ph) : "memory");
    return ok;
}
__device__ __forceinline__ void mbar_wait(uint32_t a, uint32_t ph) {
    int n = 1 << 22;
#pragma unroll 1
    do { n = __all_sync(0xffffffffu, mbar_try(a, ph)) ? 0 : n - 1; } while (n > 0);
}
__device__ __forceinline__ bool elect_one() {
    uint32_t p;
    asm volatile("{\n.reg .pred P;\nelect.sync _|P, 0xffffffff;\nselp.u32 %0, 1, 0, P;\n}" : "=r"(p));
    return p;
}
__device__ __forceinline__ void signal_cnt(int c) {
    asm volatile("fence.release.gpu;\nred.relaxed.gpu.global.add.u32 [%0], 1;" :: "l"(g_cnt + c * 8) : "memory");
}
__device__ __forceinline__ void wait_cnt(int c, unsigned target, int ns) {
#pragma unroll 1
    for (int n = 0; n < 2000000; n++) {
        unsigned v;
        asm volatile("ld.relaxed.gpu.global.u32 %0, [%1];" : "=r"(v) : "l"(g_cnt + c * 8) : "memory");
        if (__all_sync(0xffffffffu, (int)(v - target) >= 0)) break;
        __nanosleep(ns);
    }
}
__device__ __forceinline__ uint32_t ld_epoch() {
    uint32_t e;
    asm volatile("ld.relaxed.gpu.global.u32 %0, [%1];" : "=r"(e) : "l"(g_epoch + blockIdx.x) : "memory");
    return e;
}
__device__ __forceinline__ void st_tagged(void* p, uint32_t v, uint32_t tag) {
    asm volatile("st.relaxed.gpu.global.b64 [%0], %1;" :: "l"(p), "l"((unsigned long long)tag << 32 | v) : "memory");
}
__device__ __forceinline__ uint32_t ld_tagged2(const ulonglong2* p, uint32_t tag, uint32_t& a, uint32_t& b) {
    unsigned long long u, v;
    asm volatile("ld.relaxed.gpu.global.v2.b64 {%0,%1}, [%2];" : "=l"(u), "=l"(v) : "l"(p) : "memory");
    a = (uint32_t)u; b = (uint32_t)v;
    return ((uint32_t)(u >> 32) ^ tag) | ((uint32_t)(v >> 32) ^ tag);
}
__device__ __forceinline__ void tma2d(uint32_t dst, const CUtensorMap* m, int c0, int c1, uint32_t bar) {
    asm volatile("cp.async.bulk.tensor.2d.shared::cluster.global.mbarrier::complete_tx::bytes [%0], [%1, {%3, %4}], [%2];"
                 :: "r"(dst), "l"(m), "r"(bar), "r"(c0), "r"(c1) : "memory");
}
__device__ __forceinline__ void tma2d_mc(uint32_t dst, const CUtensorMap* m, int c0, int c1, uint32_t bar) {
    asm volatile("cp.async.bulk.tensor.2d.shared::cluster.global.mbarrier::complete_tx::bytes.multicast::cluster [%0], [%1, {%3, %4}], [%2], %5;"
                 :: "r"(dst), "l"(m), "r"(bar), "r"(c0), "r"(c1), "h"((uint16_t)3) : "memory");
}
__device__ __forceinline__ void bulk_load(uint32_t dst, const void* src, int bytes, uint32_t bar) {
    asm volatile("cp.async.bulk.shared::cluster.global.mbarrier::complete_tx::bytes [%0], [%1], %2, [%3];"
                 :: "r"(dst), "l"(src), "r"(bytes), "r"(bar) : "memory");
}
__device__ __forceinline__ void bar_sync(int id, int n) { asm volatile("bar.sync %0, %1;" :: "r"(id), "r"(n) : "memory"); }
__device__ __forceinline__ void fence_async_smem() { asm volatile("fence.proxy.async.shared::cta;" ::: "memory"); }
__device__ __forceinline__ void fence_async_all() { asm volatile("fence.acquire.gpu;\nfence.proxy.async.global;" ::: "memory"); }
__device__ __forceinline__ void wg_fence() { asm volatile("wgmma.fence.sync.aligned;" ::: "memory"); }
__device__ __forceinline__ void wg_commit() { asm volatile("wgmma.commit_group.sync.aligned;" ::: "memory"); }
template <int N> __device__ __forceinline__ void wg_wait() { asm volatile("wgmma.wait_group.sync.aligned %0;" :: "n"(N) : "memory"); }
template <int N> __device__ __forceinline__ void pin(float* d) {
#pragma unroll
    for (int i = 0; i < N; i++) asm volatile("" : "+f"(d[i]) :: "memory");
}
template <int N> __device__ __forceinline__ void pin(uint32_t* d) {
#pragma unroll
    for (int i = 0; i < N; i++) asm volatile("" : "+r"(d[i]) :: "memory");
}
constexpr uint32_t SMEM_BASE = 1024;
__device__ __forceinline__ uint64_t mkdesc(uint32_t off, uint32_t lbo, uint32_t sbo, uint32_t swz) {
    return (uint64_t)((SMEM_BASE + off) >> 4) | ((uint64_t)(lbo >> 4) << 16) | ((uint64_t)(sbo >> 4) << 32) | ((uint64_t)swz << 62);
}
__device__ __forceinline__ float ex2f(float x) { float y; asm("ex2.approx.ftz.f32 %0, %1;" : "=f"(y) : "f"(x)); return y; }
__device__ __forceinline__ float rcpf(float x) { float y; asm("rcp.approx.ftz.f32 %0, %1;" : "=f"(y) : "f"(x)); return y; }
__device__ __forceinline__ uint32_t pack_bf16(float lo, float hi) { uint32_t r; asm("cvt.rn.bf16x2.f32 %0, %1, %2;" : "=r"(r) : "f"(hi), "f"(lo)); return r; }
__device__ __forceinline__ float bf_lo(uint32_t v) { return __uint_as_float(v << 16); }
__device__ __forceinline__ float bf_hi(uint32_t v) { return __uint_as_float(v & 0xFFFF0000u); }
__device__ __forceinline__ float bf_round(float x) { return __bfloat162float(__float2bfloat16_rn(x)); }
__device__ __forceinline__ float siluf(float g) { return g * rcpf(1.0f + ex2f(g * -1.4426950408889634f)); }

__device__ __forceinline__ void wgmma_ss_n128_zero(float* d, uint64_t da, uint64_t db) {
    asm volatile("wgmma.mma_async.sync.aligned.m64n128k16.f32.bf16.bf16 {"
        "%0,%1,%2,%3,%4,%5,%6,%7,%8,%9,%10,%11,%12,%13,%14,%15,%16,%17,%18,%19,%20,%21,%22,%23,%24,%25,%26,%27,%28,%29,%30,%31,%32,%33,%34,%35,%36,%37,%38,%39,"
        "%40,%41,%42,%43,%44,%45,%46,%47,%48,%49,%50,%51,%52,%53,%54,%55,%56,%57,%58,%59,%60,%61,%62,%63"
        "}, %64, %65, 0, 1, 1, 0, 1;\n"
        : "=f"(d[0]),"=f"(d[1]),"=f"(d[2]),"=f"(d[3]),"=f"(d[4]),"=f"(d[5]),"=f"(d[6]),"=f"(d[7]),"=f"(d[8]),"=f"(d[9]),"=f"(d[10]),"=f"(d[11]),"=f"(d[12]),
          "=f"(d[13]),"=f"(d[14]),"=f"(d[15]),"=f"(d[16]),"=f"(d[17]),"=f"(d[18]),"=f"(d[19]),"=f"(d[20]),"=f"(d[21]),"=f"(d[22]),"=f"(d[23]),"=f"(d[24]),
          "=f"(d[25]),"=f"(d[26]),"=f"(d[27]),"=f"(d[28]),"=f"(d[29]),"=f"(d[30]),"=f"(d[31]),"=f"(d[32]),"=f"(d[33]),"=f"(d[34]),"=f"(d[35]),"=f"(d[36]),
          "=f"(d[37]),"=f"(d[38]),"=f"(d[39]),"=f"(d[40]),"=f"(d[41]),"=f"(d[42]),"=f"(d[43]),"=f"(d[44]),"=f"(d[45]),"=f"(d[46]),"=f"(d[47]),"=f"(d[48]),
          "=f"(d[49]),"=f"(d[50]),"=f"(d[51]),"=f"(d[52]),"=f"(d[53]),"=f"(d[54]),"=f"(d[55]),"=f"(d[56]),"=f"(d[57]),"=f"(d[58]),"=f"(d[59]),"=f"(d[60]),
          "=f"(d[61]),"=f"(d[62]),"=f"(d[63])
        : "l"(da), "l"(db));
}
__device__ __forceinline__ void wgmma_ss_n128_acc(float* d, uint64_t da, uint64_t db) {
    asm volatile("wgmma.mma_async.sync.aligned.m64n128k16.f32.bf16.bf16 {"
        "%0,%1,%2,%3,%4,%5,%6,%7,%8,%9,%10,%11,%12,%13,%14,%15,%16,%17,%18,%19,%20,%21,%22,%23,%24,%25,%26,%27,%28,%29,%30,%31,%32,%33,%34,%35,%36,%37,%38,%39,"
        "%40,%41,%42,%43,%44,%45,%46,%47,%48,%49,%50,%51,%52,%53,%54,%55,%56,%57,%58,%59,%60,%61,%62,%63"
        "}, %64, %65, 1, 1, 1, 0, 1;\n"
        : "+f"(d[0]),"+f"(d[1]),"+f"(d[2]),"+f"(d[3]),"+f"(d[4]),"+f"(d[5]),"+f"(d[6]),"+f"(d[7]),"+f"(d[8]),"+f"(d[9]),"+f"(d[10]),"+f"(d[11]),"+f"(d[12]),
          "+f"(d[13]),"+f"(d[14]),"+f"(d[15]),"+f"(d[16]),"+f"(d[17]),"+f"(d[18]),"+f"(d[19]),"+f"(d[20]),"+f"(d[21]),"+f"(d[22]),"+f"(d[23]),"+f"(d[24]),
          "+f"(d[25]),"+f"(d[26]),"+f"(d[27]),"+f"(d[28]),"+f"(d[29]),"+f"(d[30]),"+f"(d[31]),"+f"(d[32]),"+f"(d[33]),"+f"(d[34]),"+f"(d[35]),"+f"(d[36]),
          "+f"(d[37]),"+f"(d[38]),"+f"(d[39]),"+f"(d[40]),"+f"(d[41]),"+f"(d[42]),"+f"(d[43]),"+f"(d[44]),"+f"(d[45]),"+f"(d[46]),"+f"(d[47]),"+f"(d[48]),
          "+f"(d[49]),"+f"(d[50]),"+f"(d[51]),"+f"(d[52]),"+f"(d[53]),"+f"(d[54]),"+f"(d[55]),"+f"(d[56]),"+f"(d[57]),"+f"(d[58]),"+f"(d[59]),"+f"(d[60]),
          "+f"(d[61]),"+f"(d[62]),"+f"(d[63])
        : "l"(da), "l"(db));
}
__device__ __forceinline__ void wgmma_ss_n64(float* d, uint64_t da, uint64_t db, int acc) {
    asm volatile("{\n.reg .pred p;\nsetp.ne.b32 p, %34, 0;\nwgmma.mma_async.sync.aligned.m64n64k16.f32.bf16.bf16 {"
        "%0,%1,%2,%3,%4,%5,%6,%7,%8,%9,%10,%11,%12,%13,%14,%15,%16,%17,%18,%19,%20,%21,%22,%23,%24,%25,%26,%27,%28,%29,%30,%31"
        "}, %32, %33, p, 1, 1, 0, 1;\n}\n"
        : "+f"(d[0]),"+f"(d[1]),"+f"(d[2]),"+f"(d[3]),"+f"(d[4]),"+f"(d[5]),"+f"(d[6]),"+f"(d[7]),"+f"(d[8]),"+f"(d[9]),"+f"(d[10]),"+f"(d[11]),"+f"(d[12]),
          "+f"(d[13]),"+f"(d[14]),"+f"(d[15]),"+f"(d[16]),"+f"(d[17]),"+f"(d[18]),"+f"(d[19]),"+f"(d[20]),"+f"(d[21]),"+f"(d[22]),"+f"(d[23]),"+f"(d[24]),
          "+f"(d[25]),"+f"(d[26]),"+f"(d[27]),"+f"(d[28]),"+f"(d[29]),"+f"(d[30]),"+f"(d[31])
        : "l"(da), "l"(db), "r"(acc));
}
__device__ __forceinline__ void wgmma_rs_n64_zero(float* d, const uint32_t* a, uint64_t db) {
    asm volatile("wgmma.mma_async.sync.aligned.m64n64k16.f32.bf16.bf16 {"
        "%0,%1,%2,%3,%4,%5,%6,%7,%8,%9,%10,%11,%12,%13,%14,%15,%16,%17,%18,%19,%20,%21,%22,%23,%24,%25,%26,%27,%28,%29,%30,%31"
        "}, {%32,%33,%34,%35}, %36, 0, 1, 1, 0;\n"
        : "=f"(d[0]),"=f"(d[1]),"=f"(d[2]),"=f"(d[3]),"=f"(d[4]),"=f"(d[5]),"=f"(d[6]),"=f"(d[7]),"=f"(d[8]),"=f"(d[9]),"=f"(d[10]),"=f"(d[11]),"=f"(d[12]),
          "=f"(d[13]),"=f"(d[14]),"=f"(d[15]),"=f"(d[16]),"=f"(d[17]),"=f"(d[18]),"=f"(d[19]),"=f"(d[20]),"=f"(d[21]),"=f"(d[22]),"=f"(d[23]),"=f"(d[24]),
          "=f"(d[25]),"=f"(d[26]),"=f"(d[27]),"=f"(d[28]),"=f"(d[29]),"=f"(d[30]),"=f"(d[31])
        : "r"(a[0]), "r"(a[1]), "r"(a[2]), "r"(a[3]), "l"(db));
}
__device__ __forceinline__ void wgmma_rs_n64_acc(float* d, const uint32_t* a, uint64_t db) {
    asm volatile("wgmma.mma_async.sync.aligned.m64n64k16.f32.bf16.bf16 {"
        "%0,%1,%2,%3,%4,%5,%6,%7,%8,%9,%10,%11,%12,%13,%14,%15,%16,%17,%18,%19,%20,%21,%22,%23,%24,%25,%26,%27,%28,%29,%30,%31"
        "}, {%32,%33,%34,%35}, %36, 1, 1, 1, 0;\n"
        : "+f"(d[0]),"+f"(d[1]),"+f"(d[2]),"+f"(d[3]),"+f"(d[4]),"+f"(d[5]),"+f"(d[6]),"+f"(d[7]),"+f"(d[8]),"+f"(d[9]),"+f"(d[10]),"+f"(d[11]),"+f"(d[12]),
          "+f"(d[13]),"+f"(d[14]),"+f"(d[15]),"+f"(d[16]),"+f"(d[17]),"+f"(d[18]),"+f"(d[19]),"+f"(d[20]),"+f"(d[21]),"+f"(d[22]),"+f"(d[23]),"+f"(d[24]),
          "+f"(d[25]),"+f"(d[26]),"+f"(d[27]),"+f"(d[28]),"+f"(d[29]),"+f"(d[30]),"+f"(d[31])
        : "r"(a[0]), "r"(a[1]), "r"(a[2]), "r"(a[3]), "l"(db));
}
__device__ __forceinline__ void wgmma_rs_n24_acc(float* d, const uint32_t* a, uint64_t db) {
    asm volatile("wgmma.mma_async.sync.aligned.m64n24k16.f32.bf16.bf16 {"
        "%0,%1,%2,%3,%4,%5,%6,%7,%8,%9,%10,%11"
        "}, {%12,%13,%14,%15}, %16, 1, 1, 1, 1;\n"
        : "+f"(d[0]),"+f"(d[1]),"+f"(d[2]),"+f"(d[3]),"+f"(d[4]),"+f"(d[5]),"+f"(d[6]),"+f"(d[7]),"+f"(d[8]),"+f"(d[9]),"+f"(d[10]),"+f"(d[11])
        : "r"(a[0]), "r"(a[1]), "r"(a[2]), "r"(a[3]), "l"(db));
}

constexpr int OFF_ONES = 131072;
constexpr int OFF_RING = OFF_ONES + 4096;
constexpr int NRING = 5;
constexpr int OFF_B2 = OFF_RING + NRING * 16384;
constexpr int OFF_CS = OFF_B2 + 2048;
constexpr int OFF_RS = OFF_CS + 2560;
constexpr int OFF_BAR = OFF_RS + 1024;
enum { B_FULL = 0, B_STATS = 40, B_KV = 45, B_RING = 53, B_WO = 56, B_O = 57, B_CNT2 = 65,
       B_AFREE = 65, B_ORD = 74, B_QKV = 79, B_CNT4 = 80, B_EMPTY = 80, B_DONE = 85, B_CNT8 = 86, B_TILE = 86, B_OW = 91, B_NUM = 100 };
constexpr int OFF_TS = OFF_BAR + 1024;
constexpr int SMEM_BYTES = OFF_BAR + B_NUM * 8;
constexpr unsigned FIXED_MASK = 0xB5;
constexpr float P71 = 2361183241434822606848.0f, M71 = 4.235164736271502e-22f;

__device__ __forceinline__ uint32_t exp2_fixed(float lo, float hi, uint32_t half2) {
    uint32_t y, g, d;
    asm("cvt.pack.sat.s16.s32 %0, %1, %2;" : "=r"(y) : "r"(__float_as_uint(hi)), "r"(__float_as_uint(lo)));
    asm("lop3.b32 %0, %1, 0x007F007F, %2, 0xEA;" : "=r"(g) : "r"(y), "r"(half2));
    asm("fma.rn.bf16x2 %0, %1, %2, %3;" : "=r"(d) : "r"(y), "r"(g), "r"(y & 0xFF80FF80u));
    return d;
}
constexpr uint64_t DK_STEP = 512 - (256ull << 16), DV_STEP = 512 - (256ull << 32);
constexpr uint32_t POS_STD = 0x76543210u, POS_LAST = 0x37521640u;

__global__ void __cluster_dims__(2, 1, 1) __launch_bounds__(640, 1)
mega_kernel(const __nv_bfloat16* __restrict__ x, const __nv_bfloat16* __restrict__ wqkv, const __nv_bfloat16* __restrict__ w1,
            const __nv_bfloat16* __restrict__ w3, __nv_bfloat16* __restrict__ out,
            const __grid_constant__ CUtensorMap mx, const __grid_constant__ CUtensorMap mqkv, const __grid_constant__ CUtensorMap mw1,
            const __grid_constant__ CUtensorMap mw3, const __grid_constant__ CUtensorMap mw2, const __grid_constant__ CUtensorMap mwo,
            uint32_t half2) {
    extern __shared__ __align__(1024) uint8_t smem_raw[];
    const uint32_t sb = __shfl_sync(0xffffffffu, smem_u32(smem_raw), 0);
    if ((sb & 0xFFFFFF) != SMEM_BASE) __trap();
    const uint32_t bars = sb + OFF_BAR, ring = sb + OFF_RING;
    const int tid = threadIdx.x, lane = tid & 31, g = lane >> 2, t4 = lane & 3;
    const int warp = __shfl_sync(0xffffffffu, tid >> 5, 0), wg = warp >> 2, wq = warp & 3;
    const int rank = blockIdx.x & 1, cl = blockIdx.x >> 1;
    const int grp = cl < 4 ? 4 + cl : cl < 36 ? (cl - 4) >> 3 : 4 + (cl - 36) / 7;
    const int rot = cl < 4 ? 7 : cl < 36 ? (cl - 4) & 7 : (cl - 36) % 7;
    const int mblk = rot * 2 + rank;
    const int nq = grp < 4 ? 2 : 1;
    const int qt0 = grp < 4 ? 2 * grp : 4 + grp;
    const int gu0 = (grp < 4 ? 3 * grp : 4 * grp - 4) - nq;
    const int head = blockIdx.x >> 2, qb = blockIdx.x & 3;

    if (elect_one()) {
#pragma unroll
        for (int i = 0; i < 5; i++) { const int b = warp * 5 + i; mbar_init(bars + 8 * b, b < B_CNT2 ? 1 : b < B_CNT4 ? 2 : b < B_CNT8 ? 4 : 8); }
        if (warp == 0) {
            fence_async_smem();
#pragma unroll
            for (int j = 0; j < 2; j++) {
                tma2d(sb + j * 16384, &mx, j * 64, mblk * 128, bars + 8 * (B_FULL + j));
                tma2d(ring + j * 16384, &mqkv, qt0 * 128, j * 64, bars + 8 * (B_FULL + j));
                tma2d(ring + j * 16384 + 8192, &mqkv, qt0 * 128 + 64, j * 64, bars + 8 * (B_FULL + j));
            }
        }
        if (warp < 8) {
#pragma unroll
            for (int i = 0; i < 5; i++) mbar_expect(bars + 8 * (warp * 5 + i), warp * 5 + i < 8 ? 32768 : 16384);
        }
        if (warp == 16) asm volatile("prefetch.tensormap [%0];" :: "l"(rank ? &mw3 : &mw1) : "memory");
        asm volatile("fence.mbarrier_init.release.cluster;" ::: "memory");
    }
    __syncthreads();
    if (tid == 512) TSTAMP(26);
    asm volatile("barrier.cluster.arrive.relaxed.aligned;" ::: "memory");

    if (wg < 4) {
        const int pair = wg >> 1, half = wg & 1;
        if (pair == 1) {
            const int row = mblk * 128 + grp * 16 + (warp - 8) * 2 + (lane >> 4);
            uint4 v[6];
            const uint32_t* w = reinterpret_cast<const uint32_t*>(v);
#pragma unroll
            for (int j = 0; j < 2; j++) v[4 + j] = __ldg(reinterpret_cast<const uint4*>(wqkv + (size_t)(rot * 64 + (warp - 8) * 8 + j * 4 + (lane >> 3)) * (3 * DM) + qt0 * 128 + rank * 64) + (lane & 7));
#pragma unroll
            for (int j = 0; j < 4; j++) v[j] = __ldg(reinterpret_cast<const uint4*>(x + (size_t)row * DM) + j * 16 + (lane & 15));
            const uint32_t tag = ld_epoch() + 1;
            float c[8];
#pragma unroll
            for (int e = 0; e < 4; e++) { c[2 * e] = bf_lo(w[16 + e]) + bf_lo(w[20 + e]); c[2 * e + 1] = bf_hi(w[16 + e]) + bf_hi(w[20 + e]); }
#pragma unroll
            for (int n = 4; n > 1; n >>= 1) {
                const bool up = lane & (4 * n);
#pragma unroll
                for (int e = 0; e < n; e++) c[e] = (up ? c[e + n] : c[e]) + __shfl_xor_sync(0xffffffffu, up ? c[e] : c[e + n], 4 * n);
            }
            asm volatile("st.shared.v2.f32 [%0], {%1,%2};" :: "r"(sb + OFF_CS + 512 + (warp - 8) * 256 + (lane & 7) * 32 + (lane >> 3) * 8), "f"(c[0]), "f"(c[1]) : "memory");
            bar_sync(6, 256);
            if (warp < 10) {
#pragma unroll
                for (int e = 0; e < 8; e++) asm volatile("ld.shared.f32 %0, [%1];" : "=f"(c[e]) : "r"(sb + OFF_CS + 512 + e * 256 + (tid & 63) * 4));
                st_tagged(reinterpret_cast<unsigned long long*>(g_cs) + (grp * 40 + rot) * 128 + rank * 64 + (tid & 63),
                          __float_as_uint(((c[0] + c[1]) + (c[2] + c[3])) + ((c[4] + c[5]) + (c[6] + c[7]))), tag);
                if (tid == 256) TSTAMP(40);
            }
            float sa[4] = {0.f, 0.f, 0.f, 0.f}, sq[4] = {0.f, 0.f, 0.f, 0.f};
#pragma unroll
            for (int j = 0; j < 16; j++) sa[j & 3] += bf_lo(w[j]) + bf_hi(w[j]);
            float mean = ((sa[0] + sa[1]) + (sa[2] + sa[3])) * (1.0f / 32);
#pragma unroll
            for (int j = 0; j < 16; j++) { const float a = bf_lo(w[j]) - mean, b = bf_hi(w[j]) - mean; sq[j & 1] = fmaf(a, a, sq[j & 1]); sq[2 + (j & 1)] = fmaf(b, b, sq[2 + (j & 1)]); }
            float m2 = (sq[0] + sq[1]) + (sq[2] + sq[3]);
#pragma unroll
            for (int d = 1; d < 16; d <<= 1) {
                const float om = __shfl_xor_sync(0xffffffffu, mean, d), o2 = __shfl_xor_sync(0xffffffffu, m2, d), dm = mean - om;
                m2 = fmaf(dm * dm, 16.0f * d, m2 + o2); mean = 0.5f * (mean + om);
            }
            float sd;
            asm("sqrt.approx.f32 %0, %1;" : "=f"(sd) : "f"(bf_round(bf_round(m2 * (1.0f / DM)) + 1e-5f)));
            if ((lane & 15) == 0) st_tagged(reinterpret_cast<unsigned long long*>(g_rs) + row, pack_bf16(mean, sd), tag);
            if (tid == 256) TSTAMP(45);
        }

        uint32_t q[4], qn[6];
        {
            const int rowblk = mblk * 2 + half, tile16 = rowblk * 4 + wq;
            const bool rel = wq < 2 && lane == 0, rel2 = wq == 2 && lane == 0;
            uint32_t empty;
            asm("mapa.shared::cluster.u32 %0, %1, %2;" : "=r"(empty) : "r"(bars + 8 * B_EMPTY), "r"(wq & 1));
#pragma unroll 1
            for (int t = pair; t < 5; t += 2) {
                float acc[64];
                uint32_t po = t == 4 ? POS_LAST : POS_STD, full = bars + 8 * (B_FULL + 8 * t), slot = (0x24130u >> (4 * t)) & 7;
                const uint64_t da0 = mkdesc(half * 8192, 16, 1024, 1), db0 = mkdesc(OFF_RING, 8192, 1024, 1);
                const bool last = t == 4 && rel2;
                if (tid == 0 && t == 0) TSTAMP(30);
                mbar_wait(full, 0);
                if (t > 0) mbar_wait(bars + 8 * (B_ORD + t - 1), 0);
                wg_fence();
                wgmma_ss_n128_zero(acc, da0, db0 + slot * 1024);
#pragma unroll
                for (int k = 1; k < 4; k++) wgmma_ss_n128_acc(acc, da0 + k * 2, db0 + slot * 1024 + k * 128);
                wg_commit();
                mbar_wait(full + 8, 0);
#pragma unroll 1
                for (int j = 1; j < 8; j++) {
                    const uint32_t rel_a = empty + slot * 8;
                    slot = slot == NRING - 1 ? 0 : slot + 1; po >>= 4; full += 8;
                    const uint64_t da = da0 + (po & 7) * 1024, db = db0 + slot * 1024;
                    wg_fence();
#pragma unroll
                    for (int k = 0; k < 4; k++) wgmma_ss_n128_acc(acc, da + k * 2, db + k * 128);
                    wg_commit();
                    if (j < 7) mbar_wait(full + 8, 0); else if (rel2) mbar_arrive(bars + 8 * (B_ORD + t));
                    wg_wait<1>();
                    if (rel) mbar_arrive_remote(rel_a);
                    if (last) mbar_arrive(full + 8 * (B_AFREE - 33));
                }
                if (t >= 3) {
                    mbar_wait(bars + 8 * B_QKV, 0);
                    const uint4* pq = g_q + (head * 128 + (qb * 8 + wg) * 4 + wq) * 32 + lane;
                    const uint4 v = __ldcg(pq), u = __ldcg(pq + 512);
                    qn[0] = v.x; qn[1] = v.y; qn[2] = v.z; qn[3] = v.w; q[0] = u.x; q[1] = u.y; q[2] = u.z; q[3] = u.w;
                }
                wg_wait<0>();
                if (rel) mbar_arrive_remote(empty + slot * 8);
                if (t >= 3 && rel2) mbar_arrive(bars + 8 * (B_AFREE + 11 - t));
                pin<64>(acc);
                if (wq == 0 && half == 0 && lane == 0) TSTAMP(2 + 2 * t);
                mbar_wait(bars + 8 * (B_STATS + t), 0);
                uint32_t rs0, rs1;
                asm volatile("ld.shared.b32 %0, [%1];" : "=r"(rs0) : "r"(sb + OFF_RS + (half * 64 + wq * 16 + g) * 4));
                asm volatile("ld.shared.b32 %0, [%1];" : "=r"(rs1) : "r"(sb + OFF_RS + (half * 64 + wq * 16 + g + 8) * 4));
                const float m0 = bf_lo(rs0), m1 = bf_lo(rs1);
                float d0 = bf_hi(rs0), d1 = bf_hi(rs1);
#pragma unroll
                for (int j = 0; j < 16; j++) {
                    float c0, c1;
                    asm volatile("ld.shared.v2.f32 {%0,%1}, [%2];" : "=f"(c0), "=f"(c1) : "r"(sb + OFF_CS + (t * 128 + j * 8 + t4 * 2) * 4));
                    acc[4 * j] = fmaf(-m0, c0, acc[4 * j]); acc[4 * j + 1] = fmaf(-m0, c1, acc[4 * j + 1]);
                    acc[4 * j + 2] = fmaf(-m1, c0, acc[4 * j + 2]); acc[4 * j + 3] = fmaf(-m1, c1, acc[4 * j + 3]);
                }
                float r0 = rcpf(d0), r1 = rcpf(d1);
                if (t < nq) {
                    const int qt = qt0 + t;
                    if (qt < 4) {
                        r0 *= 0.25f * 1.4426950408889634f * M71; r1 *= 0.25f * 1.4426950408889634f * M71;
                    } else if (qt < 8) {
                        r0 *= ((FIXED_MASK >> (2 * wq)) & 1) ? M71 : P71; r1 *= ((FIXED_MASK >> (2 * wq + 1)) & 1) ? M71 : P71;
                    }
                    uint32_t e[32];
#pragma unroll
                    for (int i = 0; i < 32; i++) { const float r = (i & 1) ? r1 : r0; e[i] = pack_bf16(acc[2 * i] * r, acc[2 * i + 1] * r); }
                    if (qt < 4) {
                        uint4* p = g_q + (qt * 1024 + tile16) * 32 + lane;
#pragma unroll
                        for (int hh = 0; hh < 8; hh++) p[hh * 4096] = make_uint4(e[4 * hh], e[4 * hh + 1], e[4 * hh + 2], e[4 * hh + 3]);
                    } else {
                        uint32_t* p = reinterpret_cast<uint32_t*>(g_kv + (qt - 4) * 32768) + tile16 * 64 + lane;
#pragma unroll
                        for (int i = 0; i < 32; i++) p[(i >> 1) * 8192 + (i & 1) * 32] = e[i];
                    }
                } else {
                    uint32_t* p = reinterpret_cast<uint32_t*>(g_h + (rowblk * 28 + gu0 + t) * 512) + wq * 512 + lane;
                    r0 *= -1.4426950408889634f; r1 *= -1.4426950408889634f; d0 *= d0; d1 *= d1;
#pragma unroll
                    for (int j = 0; j < 8; j++) {
                        const float* a = acc + j * 4; const float* b = a + 32;
                        p[j * 32] = pack_bf16(a[0] * b[0] * rcpf(fmaf(ex2f(a[0] * r0), d0, d0)), a[1] * b[1] * rcpf(fmaf(ex2f(a[1] * r0), d0, d0)));
                        p[256 + j * 32] = pack_bf16(a[2] * b[2] * rcpf(fmaf(ex2f(a[2] * r1), d1, d1)), a[3] * b[3] * rcpf(fmaf(ex2f(a[3] * r1), d1, d1)));
                    }
                }
                __syncwarp();
                if (elect_one()) mbar_arrive(bars + 8 * (B_TILE + t));
                if (wq == 0 && half == 0 && lane == 0) TSTAMP(3 + 2 * t);
            }
        }
        const uint64_t db2 = mkdesc(OFF_B2, 128, 256, 0);
        float s[32];
        auto ref_point = [&](int ntile, uint32_t& b0, uint32_t& b1) {
            float m0 = -INFINITY, m1 = -INFINITY, f0 = -INFINITY, f1 = -INFINITY;
#pragma unroll 1
            for (int t = 0; t < ntile; t++) {
                wg_fence();
                wgmma_rs_n64_zero(s, q, mkdesc(4096, 94208, 128, 0) + (t >> 2) * DK_STEP + (t & 3) * 64);
                wg_commit();
                wg_wait<0>();
                pin<32>(s);
#pragma unroll
                for (int i = 0; i < 8; i++) {
                    if ((FIXED_MASK >> i) & 1) { f0 = fmaxf(f0, fmaxf(s[4 * i], s[4 * i + 1])); f1 = fmaxf(f1, fmaxf(s[4 * i + 2], s[4 * i + 3])); }
                    else                       { m0 = fmaxf(m0, fmaxf(s[4 * i], s[4 * i + 1])); m1 = fmaxf(m1, fmaxf(s[4 * i + 2], s[4 * i + 3])); }
                }
            }
            m0 = fmaxf(m0, f0 * P71 * P71); m1 = fmaxf(m1, f1 * P71 * P71);
            m0 = fmaxf(m0, __shfl_xor_sync(0xffffffffu, m0, 1)); m1 = fmaxf(m1, __shfl_xor_sync(0xffffffffu, m1, 1));
            m0 = fmaxf(m0, __shfl_xor_sync(0xffffffffu, m0, 2)); m1 = fmaxf(m1, __shfl_xor_sync(0xffffffffu, m1, 2));
#pragma unroll
            for (int r = 0; r < 2; r++) {
                const float m = -rintf(r ? m1 : m0), mh = bf_round(m), mm = bf_round(m - mh), ml = m - mh - mm;
                const float lo = t4 == 0 ? mh : t4 == 1 ? ml : t4 == 2 ? 1.f : 0.f, hi = t4 == 0 ? mm : t4 == 1 ? 1.f : 0.f;
                (r ? b1 : b0) = pack_bf16(lo * M71, hi * M71);
            }
        };
        uint32_t q2[4];
        int redo = 1;
        mbar_wait(bars + 8 * B_KV, 0);
#pragma unroll 1
        for (int round = -1; round < 2;) {
            if (redo) ref_point(redo, q2[0], q2[1]);
            if (round < 0) {
#pragma unroll
                for (int i = 0; i < 4; i++) { const uint32_t tq = q[i]; q[i] = qn[i]; qn[i] = tq; }
                qn[4] = q2[0]; qn[5] = q2[1];
                q2[2] = __shfl_sync(0xffffffffu, q2[0], 3); q2[3] = __shfl_sync(0xffffffffu, q2[1], 3);
                round = 0;
                continue;
            }
            float o[12]; uint32_t p[16];
#pragma unroll
            for (int i = 0; i < 12; i++) o[i] = 0.f;
            pin<12>(o); pin<4>(q2);
            if (wq == 0 && half == 0 && lane == 0) TSTAMP(12 + 4 * round + pair);
            uint64_t dk = mkdesc(4096, 94208, 128, 0), dv = mkdesc(0, 128, 65536, 0);
#pragma unroll 1
            for (int c = 0; c < 8; c++, dk += DK_STEP, dv += DV_STEP) {
                if (round == 0) mbar_wait(bars + 8 * (B_KV + c), 0);
#pragma unroll
                for (int t = 0; t < 4; t++) {
                    wg_fence();
                    wgmma_rs_n64_zero(s, q, dk + t * 64);
                    wgmma_rs_n64_acc(s, q2, db2);
                    wg_commit();
                    wg_wait<0>();
                    pin<32>(s); pin<16>(p);
#pragma unroll
                    for (int i = 0; i < 16; i++) {
                        if ((FIXED_MASK >> (i >> 1)) & 1) p[i] = exp2_fixed(s[2 * i], s[2 * i + 1], half2);
                        else                              p[i] = pack_bf16(ex2f(s[2 * i]), ex2f(s[2 * i + 1]));
                    }
                    wg_fence();
#pragma unroll
                    for (int k = 0; k < 4; k++) wgmma_rs_n24_acc(o, p + 4 * k, dv + (t * 4 + k) * 16);
                    wg_commit();
                }
            }
            wg_wait<0>();
            pin<12>(o);
            if (redo != 32) {
                float chk = (o[8] + o[10]) * 256.f;
#pragma unroll
                for (int i = 0; i < 8; i++) chk += fabsf(o[i]);
                uint32_t bad;
                asm volatile("{\n.reg .pred p, q;\nsetp.geu.f32 q, %1, 0f7F800000;\nbar.red.or.pred p, %2, 128, q;\nselp.u32 %0, 1, 0, p;\n}" : "=r"(bad) : "f"(chk), "r"(1 + wg) : "memory");
                if (__any_sync(0xffffffffu, bad)) { redo = 32; continue; }
            }
            const int rowblk = qb * 8 + round * 4 + wg;
            const float r0 = rcpf(o[8]), r1 = rcpf(o[10]);
            uint32_t* po = reinterpret_cast<uint32_t*>(g_o + (rowblk * 8 + (head >> 2)) * 512) + wq * 512 + (head & 3) * 64 + lane;
            po[0] = pack_bf16(o[0] * r0, o[1] * r0); po[256] = pack_bf16(o[2] * r1, o[3] * r1);
            po[32] = pack_bf16(o[4] * r0, o[5] * r0); po[288] = pack_bf16(o[6] * r1, o[7] * r1);
            if (round == 0) {
                __syncwarp();
                if (elect_one()) mbar_arrive(bars + 8 * (B_OW + pair));
            } else {
                bar_sync(1 + wg, 128);
                if (wq == 0 && elect_one()) { mbar_arrive(bars + 8 * B_DONE); signal_cnt(C_O + rowblk); }
            }
#pragma unroll
            for (int i = 0; i < 4; i++) q[i] = qn[i];
            q2[0] = qn[4]; q2[1] = qn[5];
            redo = 0;
            if (wq == 0 && half == 0 && lane == 0) TSTAMP(14 + 4 * round + pair);
            round++;
        }
    } else {
        uint32_t tag;
        if (wq == 0) {
            asm volatile("barrier.cluster.wait.aligned;" ::: "memory");
            if (tid == 512) TSTAMP(27);
            uint32_t slot = 2, ph = 1;
#pragma unroll 1
            for (int n = 2; n < 40; n++) {
                const int t = n >> 3, j = n & 7;
                const int kc = (n < 32 ? j : (POS_LAST >> (4 * j)) & 7) * 64;
                const CUtensorMap* m = t < nq ? &mqkv : rank ? &mw3 : &mw1;
                const int col = t < nq ? (qt0 + t) * 128 + rank * 64 : (gu0 + t) * 64;
                const uint32_t dst = ring + slot * 16384 + rank * 8192, fb = bars + 8 * (B_FULL + n);
                if (n < 8 && elect_one()) tma2d(sb + n * 16384, &mx, kc, mblk * 128, fb);
                mbar_wait(bars + 8 * (B_EMPTY + slot), ph);
                if (elect_one()) { TS2(0, n); tma2d_mc(dst, m, col, kc, fb); }
                if (++slot == NRING) { slot = 0; ph ^= 1; }
            }
            tag = ld_epoch() + 1;
        } else if (wq == 1) {
            tag = ld_epoch() + 1;
            mbar_wait(bars + 8 * (B_FULL + 5), 0);
#pragma unroll 1
            for (int t = 0; t < 5; t++) {
                float a[4];
#pragma unroll 1
                for (int n = 0; n < 2000000; n++) {
                    uint32_t stale = 0;
                    a[0] = a[1] = a[2] = a[3] = 0.f;
#pragma unroll
                    for (int i = 0; i < 16; i++) {
                        uint32_t u, v;
                        stale |= ld_tagged2(g_cs + (grp * 5 + t) * 512 + i * 32 + lane, tag, u, v);
                        a[(i & 1) * 2] += __uint_as_float(u); a[(i & 1) * 2 + 1] += __uint_as_float(v);
                    }
                    if (__all_sync(0xffffffffu, stale == 0)) break;
                    if (t) __nanosleep(400);
                }
                asm volatile("st.shared.v2.f32 [%0], {%1,%2};" :: "r"(sb + OFF_CS + t * 512 + lane * 8), "f"(a[0]), "f"(a[1]) : "memory");
                asm volatile("st.shared.v2.f32 [%0], {%1,%2};" :: "r"(sb + OFF_CS + t * 512 + 256 + lane * 8), "f"(a[2]), "f"(a[3]) : "memory");
                if (t == 0) {
                    uint32_t r[4];
#pragma unroll 1
                    for (int n = 0; n < 2000000; n++) {
                        const uint32_t stale = ld_tagged2(g_rs + mblk * 64 + lane * 2, tag, r[0], r[1]) | ld_tagged2(g_rs + mblk * 64 + lane * 2 + 1, tag, r[2], r[3]);
                        if (__all_sync(0xffffffffu, stale == 0)) break;
                    }
                    asm volatile("st.shared.v4.b32 [%0], {%1,%2,%3,%4};" :: "r"(sb + OFF_RS + lane * 16), "r"(r[0]), "r"(r[1]), "r"(r[2]), "r"(r[3]) : "memory");
                }
                __syncwarp();
                if (elect_one()) { mbar_arrive(bars + 8 * (B_STATS + t)); TSTAMP(32 + t); }
            }
        } else {
            tag = ld_epoch() + 1;
            mbar_wait(bars + 8 * (B_FULL + wq - 1), 0);
#pragma unroll 1
            for (int t = wq - 1; t < 5; t += 2) {
                const __nv_bfloat16* src; int ld;
                if (t < nq) { src = wqkv + (qt0 + t) * 128 + rank * 64; ld = 3 * DM; }
                else        { src = (rank ? w3 : w1) + (gu0 + t) * 64; ld = FF; }
                src += (size_t)(rot * 64 + (lane >> 3)) * ld + (lane & 7) * 8;
                uint4 v[16];
                const uint32_t* w = reinterpret_cast<const uint32_t*>(v);
#pragma unroll
                for (int j = 0; j < 16; j++) v[j] = __ldg(reinterpret_cast<const uint4*>(src + (size_t)j * 4 * ld));
                float c[8];
#pragma unroll
                for (int e = 0; e < 4; e++) {
                    float a = 0.f, b = 0.f;
#pragma unroll
                    for (int j = 0; j < 16; j++) { a += bf_lo(w[4 * j + e]); b += bf_hi(w[4 * j + e]); }
                    c[2 * e] = a; c[2 * e + 1] = b;
                }
#pragma unroll
                for (int n = 4; n > 1; n >>= 1) {
                    const bool up = lane & (4 * n);
#pragma unroll
                    for (int e = 0; e < n; e++) c[e] = (up ? c[e + n] : c[e]) + __shfl_xor_sync(0xffffffffu, up ? c[e] : c[e + n], 4 * n);
                }
                unsigned long long* dst = reinterpret_cast<unsigned long long*>(g_cs) + ((grp * 5 + t) * 8 + rot) * 128 + rank * 64 + (lane & 7) * 8 + (lane >> 3) * 2;
                st_tagged(dst, __float_as_uint(c[0]), tag); st_tagged(dst + 1, __float_as_uint(c[1]), tag);
                if (lane == 0) TSTAMP(40 + t);
            }
        }
        if (wq == 3) {
#pragma unroll 1
            for (int i = lane; i < 256; i += 32) asm volatile("st.shared.v4.b32 [%0], {%1,%1,%1,%1};" :: "r"(sb + OFF_ONES + i * 16), "r"(0x3F803F80u) : "memory");
#pragma unroll 1
            for (int i = lane; i < 128; i += 32) {
                const bool fx = (FIXED_MASK >> (i >> 4)) & 1;
                uint32_t a = fx ? pack_bf16(M71, M71) : pack_bf16(P71, P71);
                uint32_t b = fx ? pack_bf16(M71, 47.0f * M71) : pack_bf16(P71, -79.5f * P71);
                uint32_t c = fx ? 0u : pack_bf16(0.08214f * P71, 0.f);
                if (i & 8) a = b = c = 0;
                asm volatile("st.shared.v4.b32 [%0], {%1,%2,%3,%4};" :: "r"(sb + OFF_B2 + i * 16), "r"(a), "r"(b), "r"(c), "r"(0) : "memory");
            }
            fence_async_smem();
            __syncwarp();
            if (elect_one()) mbar_arrive(bars + 8 * B_QKV);
        } else if (wq == 1) {
#pragma unroll 1
            for (int i = 0; i < 3; i++) wait_cnt(C_QKV + i * 4 + (head >> 3), 16 * tag, 100);
            fence_async_all();
            if (elect_one()) { mbar_arrive(bars + 8 * B_QKV); TSTAMP(29); }
            mbar_wait(bars + 8 * (B_AFREE + 8), 0);
            const uint8_t* gk = reinterpret_cast<const uint8_t*>(g_kv + head * 4096);
            const uint8_t* gv = reinterpret_cast<const uint8_t*>(g_kv + (32 + head) * 4096);
#pragma unroll 1
            for (int c = 0; c < 8; c++) {
                mbar_wait(bars + 8 * (B_AFREE + 2 + (c & 4) + ((c >> 1) & 1)), 0);
                if (elect_one()) {
                    const uint32_t b = bars + 8 * (B_KV + c);
                    mbar_expect(b, 16384);
                    bulk_load(sb + (2 * c + 1) * 4096, gk + c * 4096, 4096, b);
                    bulk_load(sb + 2 * c * 4096, gv + c * 4096, 4096, b);
                    bulk_load(sb + 65536 + c * 4096, gv + 32768 + c * 4096, 4096, b);
                    bulk_load(sb + 98304 + c * 4096, gk + 32768 + c * 4096, 4096, b);
                }
            }
        } else if (wq == 2) {
#pragma unroll 1
            for (int t = 0; t < 5; t++) {
                mbar_wait(bars + 8 * (B_TILE + t), 0);
                if (elect_one()) signal_cnt(t < nq ? C_QKV + qt0 + t : C_H + mblk);
            }
        }
        pin<1>(&tag);
        bar_sync(5, 128);
        if (tid == 639) g_epoch[blockIdx.x] = tag;
        const int cb = blockIdx.x & 7, pr = blockIdx.x >> 3;
        const int rb0 = (pr >> 2) * 8 + (pr & 3);
        uint32_t gate[2][16];
        {
            float dn[64];
            auto load_stage = [&](int kb, int st) {
                const uint32_t b = bars + 8 * (B_RING + st), dst = ring + st * 24576;
                mbar_expect(b, 24576);
                bulk_load(dst, g_h + (rb0 * 28 + kb) * 512, 8192, b);
                bulk_load(dst + 8192, g_h + ((rb0 + 4) * 28 + kb) * 512, 8192, b);
                tma2d(dst + 16384, &mw2, cb * 64, kb * 64, b);
            };
            if (wq == 0) {
                wait_cnt(C_H + (rb0 >> 1), 28 * tag, 200);
                wait_cnt(C_H + (rb0 >> 1) + 2, 28 * tag, 200);
                if (elect_one()) { TSTAMP(20); fence_async_all(); load_stage(0, 0); load_stage(1, 1); }
            }
            int st = 0; uint32_t ph = 0;
#pragma unroll 1
            for (int kb = 0; kb < 28; kb++) {
                mbar_wait(bars + 8 * (B_RING + st), ph);
                const uint64_t da = mkdesc(OFF_RING + st * 24576, 128, 1024, 0), db = mkdesc(OFF_RING + st * 24576 + 16384, 8192, 1024, 1);
                wg_fence();
#pragma unroll
                for (int k = 0; k < 4; k++) { wgmma_ss_n64(dn, da + k * 16, db + k * 128, (kb | k) != 0); wgmma_ss_n64(dn + 32, da + 512 + k * 16, db + k * 128, (kb | k) != 0); }
                wg_commit();
                wg_wait<1>();
                if (wq == 0 && kb < 26 && elect_one()) load_stage(kb + 2, st == 0 ? 2 : st - 1);
                if (++st == 3) { st = 0; ph ^= 1; }
            }
            wg_wait<0>();
            pin<64>(dn);
#pragma unroll
            for (int i = 0; i < 32; i++) gate[i >> 4][i & 15] = pack_bf16(siluf(dn[2 * i]), siluf(dn[2 * i + 1]));
        }
        float acc[32];
        if (tid == 512) TSTAMP(21);
        const uint32_t bar_wo = bars + 8 * B_WO;
        if (wq == 0 && elect_one()) {
            mbar_expect(bar_wo, 65536);
#pragma unroll 1
            for (int i = 0; i < 8; i++) tma2d(ring + i * 8192, &mwo, cb * 64, i * 64, bar_wo);
        }
        if (wq >= 2) {
            mbar_wait(bars + 8 * (B_OW + wq - 2), 0);
            if (elect_one()) {
                signal_cnt(C_O + qb * 8 + 2 * wq - 4);
                asm volatile("red.relaxed.gpu.global.add.u32 [%0], 1;" :: "l"(g_cnt + (C_O + qb * 8 + 2 * wq - 3) * 8) : "memory");
            }
        }
#pragma unroll 1
        for (int tl = 0; tl < 2; tl++) {
            const int rb = rb0 + 4 * tl;
            uint32_t xr[16];
            const uint32_t* px = reinterpret_cast<const uint32_t*>(x + (size_t)(rb * 64 + wq * 16 + g) * DM + cb * 64) + t4;
#pragma unroll
            for (int j = 0; j < 8; j++) { xr[2 * j] = __ldg(px + j * 4); xr[2 * j + 1] = __ldg(px + 8 * DM / 2 + j * 4); }
            if (wq == 0) {
                if (tl == 1) mbar_wait(bars + 8 * B_DONE, 0);
                wait_cnt(C_O + rb, 32 * tag, tl ? 20 : 200);
                if (elect_one()) {
                    fence_async_all();
                    TSTAMP(22 + 2 * tl);
#pragma unroll 1
                    for (int i = 0; i < (tl ? 8 : 2); i++) {
                        mbar_expect(bars + 8 * (B_O + i), 8192);
                        bulk_load((tl ? sb : ring + 65536) + i * 8192, g_o + (rb * 8 + i) * 512, 8192, bars + 8 * (B_O + i));
                    }
                }
            }
            if (tl == 0) mbar_wait(bar_wo, 0);
#pragma unroll 1
            for (int kb = 0; kb < 8; kb++) {
                mbar_wait(bars + 8 * (B_O + kb), tl);
                const uint32_t a = tl == 0 ? OFF_RING + 65536 + (kb & 1) * 8192 : kb * 8192;
                const uint64_t da = mkdesc(a, 128, 1024, 0), db = mkdesc(OFF_RING + kb * 8192, 8192, 1024, 1);
                wg_fence();
#pragma unroll
                for (int k = 0; k < 4; k++) wgmma_ss_n64(acc, da + k * 16, db + k * 128, (kb | k) != 0);
                wg_commit();
                if (tl == 0) {
                    wg_wait<0>();
                    bar_sync(5, 128);
                    if (wq == 0 && kb < 6 && elect_one()) { mbar_expect(bars + 8 * (B_O + kb + 2), 8192); bulk_load(sb + a, g_o + (rb * 8 + kb + 2) * 512, 8192, bars + 8 * (B_O + kb + 2)); }
                }
            }
            wg_wait<0>();
            pin<32>(acc);
            uint32_t* po = reinterpret_cast<uint32_t*>(out + (size_t)(rb * 64 + wq * 16 + g) * DM + cb * 64) + t4;
#pragma unroll
            for (int i = 0; i < 16; i++) {
                const uint32_t r = pack_bf16(fmaf(acc[2 * i], bf_lo(gate[0][i]), bf_lo(xr[i])), fmaf(acc[2 * i + 1], bf_hi(gate[0][i]), bf_hi(xr[i])));
                po[(i & 1) * (8 * DM / 2) + (i >> 1) * 4] = r;
                gate[0][i] = gate[1][i];
            }
            if (tid == 512) TSTAMP(23 + 2 * tl);
        }
    }
}

typedef CUresult (*EncodeFn)(CUtensorMap*, CUtensorMapDataType, cuuint32_t, void*, const cuuint64_t*, const cuuint64_t*, const cuuint32_t*,
                             const cuuint32_t*, CUtensorMapInterleave, CUtensorMapSwizzle, CUtensorMapL2promotion, CUtensorMapFloatOOBfill);

void make_map(EncodeFn fn, CUtensorMap* m, const void* p, int rows, int cols, int box_rows) {
    cuuint64_t dims[2] = {(cuuint64_t)cols, (cuuint64_t)rows};
    cuuint64_t strides[1] = {(cuuint64_t)cols * 2};
    cuuint32_t box[2] = {64, (cuuint32_t)box_rows};
    cuuint32_t es[2] = {1, 1};
    fn(m, CU_TENSOR_MAP_DATA_TYPE_BFLOAT16, 2, const_cast<void*>(p), dims, strides, box, es, CU_TENSOR_MAP_INTERLEAVE_NONE,
       CU_TENSOR_MAP_SWIZZLE_128B, CU_TENSOR_MAP_L2_PROMOTION_L2_128B, CU_TENSOR_MAP_FLOAT_OOB_FILL_NONE);
}

}

extern "C" void kernel_launch(void* const* d_in, const int* in_sizes, int n_in, void* d_out, int out_size) {
    const __nv_bfloat16* x = (const __nv_bfloat16*)d_in[0];
    static EncodeFn fn = nullptr;
    if (!fn) {
        cudaDriverEntryPointQueryResult qr;
        cudaGetDriverEntryPoint("cuTensorMapEncodeTiled", (void**)&fn, cudaEnableDefault, &qr);
        cudaFuncSetAttribute(mega_kernel, cudaFuncAttributeMaxDynamicSharedMemorySize, SMEM_BYTES);
    }
    CUtensorMap mx, mqkv, mw1, mw3, mw2, mwo;
    make_map(fn, &mx, d_in[0], SEQ, DM, 128);
    make_map(fn, &mqkv, d_in[1], DM, 3 * DM, 64);
    make_map(fn, &mwo, d_in[2], DM, DM, 64);
    make_map(fn, &mw1, d_in[4], DM, FF, 64);
    make_map(fn, &mw3, d_in[5], DM, FF, 64);
    make_map(fn, &mw2, d_in[6], FF, DM, 64);
    mega_kernel<<<128, 640, SMEM_BYTES, cudaStreamPerThread>>>(x, (const __nv_bfloat16*)d_in[1], (const __nv_bfloat16*)d_in[4], (const __nv_bfloat16*)d_in[5],
                                                               (__nv_bfloat16*)d_out, mx, mqkv, mw1, mw3, mw2, mwo, 0x3F003F00u);
}
```

```cpp
#include <cuda_runtime.h>
#include <cuda_bf16.h>
#include <cuda.h>
#include <stdint.h>

namespace {

constexpr int SEQ = 2048, DM = 512, FF = 1792;

__device__ uint4 g_q[32 * 128 * 32];
__device__ uint4 g_kv[64 * 4096];
__device__ uint4 g_h[32 * 28 * 512];
__device__ uint4 g_o[32 * 8 * 512];
__device__ ulonglong2 g_cs[40 * 8 * 64];
__device__ ulonglong2 g_rs[SEQ / 2];
constexpr int C_QKV = 0, C_H = 12, C_O = 28, C_NUM = 60;
__device__ unsigned g_cnt[C_NUM * 8];
__device__ unsigned g_epoch[128];
#define TSTAMP(i)
#define TS2(k, i)

__device__ __forceinline__ uint32_t smem_u32(const void* p) { return (uint32_t)__cvta_generic_to_shared(p); }
__device__ __forceinline__ void mbar_init(uint32_t a, int c) { asm volatile("mbarrier.init.shared::cta.b64 [%0], %1;" :: "r"(a), "r"(c)); }
__device__ __forceinline__ void mbar_expect(uint32_t a, int b) { asm volatile("mbarrier.arrive.expect_tx.shared::cta.b64 _, [%0], %1;" :: "r"(a), "r"(b) : "memory"); }
__device__ __forceinline__ void mbar_arrive(uint32_t a) { asm volatile("mbarrier.arrive.shared::cta.b64 _, [%0];" :: "r"(a) : "memory"); }
__device__ __forceinline__ void mbar_arrive_remote(uint32_t a) { asm volatile("mbarrier.arrive.shared::cluster.b64 _, [%0];" :: "r"(a) : "memory"); }
__device__ __forceinline__ bool mbar_try(uint32_t a, uint32_t ph) {
    uint32_t ok;
    asm volatile("{\n.reg .pred p;\nmbarrier.try_wait.parity.shared::cta.b64 p, [%1], %2;\nselp.u32 %0, 1, 0, p;\n}" : "=r"(ok) : "r"(a), "r"(ph) : "memory");
    return ok;
}
__device__ __forceinline__ void mbar_wait(uint32_t a, uint32_t ph) {
    int n = 1 << 22;
#pragma unroll 1
    do { n = __all_sync(0xffffffffu, mbar_try(a, ph)) ? 0 : n - 1; } while (n > 0);
}
__device__ __forceinline__ bool elect_one() {
    uint32_t p;
    asm volatile("{\n.reg .pred P;\nelect.sync _|P, 0xffffffff;\nselp.u32 %0, 1, 0, P;\n}" : "=r"(p));
    return p;
}
__device__ __forceinline__ void signal_cnt(int c) {
    asm volatile("fence.release.gpu;\nred.relaxed.gpu.global.add.u32 [%0], 1;" :: "l"(g_cnt + c * 8) : "memory");
}
__device__ __forceinline__ void wait_cnt(int c, unsigned target, int ns) {
#pragma unroll 1
    for (int n = 0; n < 2000000; n++) {
        unsigned v;
        asm volatile("ld.relaxed.gpu.global.u32 %0, [%1];" : "=r"(v) : "l"(g_cnt + c * 8) : "memory");
        if (__all_sync(0xffffffffu, (int)(v - target) >= 0)) break;
        __nanosleep(ns);
    }
}
__device__ __forceinline__ uint32_t ld_epoch() {
    uint32_t e;
    asm volatile("ld.relaxed.gpu.global.u32 %0, [%1];" : "=r"(e) : "l"(g_epoch + blockIdx.x) : "memory");
    return e;
}
__device__ __forceinline__ void st_tagged(void* p, uint32_t v, uint32_t tag) {
    asm volatile("st.relaxed.gpu.global.b64 [%0], %1;" :: "l"(p), "l"((unsigned long long)tag << 32 | v) : "memory");
}
__device__ __forceinline__ uint32_t ld_tagged2(const ulonglong2* p, uint32_t tag, uint32_t& a, uint32_t& b) {
    unsigned long long u, v;
    asm volatile("ld.relaxed.gpu.global.v2.b64 {%0,%1}, [%2];" : "=l"(u), "=l"(v) : "l"(p) : "memory");
    a = (uint32_t)u; b = (uint32_t)v;
    return ((uint32_t)(u >> 32) ^ tag) | ((uint32_t)(v >> 32) ^ tag);
}
__device__ __forceinline__ void tma2d(uint32_t dst, const CUtensorMap* m, int c0, int c1, uint32_t bar) {
    asm volatile("cp.async.bulk.tensor.2d.shared::cluster.global.mbarrier::complete_tx::bytes [%0], [%1, {%3, %4}], [%2];"
                 :: "r"(dst), "l"(m), "r"(bar), "r"(c0), "r"(c1) : "memory");
}
__device__ __forceinline__ void tma2d_mc(uint32_t dst, const CUtensorMap* m, int c0, int c1, uint32_t bar) {
    asm volatile("cp.async.bulk.tensor.2d.shared::cluster.global.mbarrier::complete_tx::bytes.multicast::cluster [%0], [%1, {%3, %4}], [%2], %5;"
                 :: "r"(dst), "l"(m), "r"(bar), "r"(c0), "r"(c1), "h"((uint16_t)3) : "memory");
}
__device__ __forceinline__ void bulk_load(uint32_t dst, const void* src, int bytes, uint32_t bar) {
    asm volatile("cp.async.bulk.shared::cluster.global.mbarrier::complete_tx::bytes [%0], [%1], %2, [%3];"
                 :: "r"(dst), "l"(src), "r"(bytes), "r"(bar) : "memory");
}
__device__ __forceinline__ void bar_sync(int id, int n) { asm volatile("bar.sync %0, %1;" :: "r"(id), "r"(n) : "memory"); }
__device__ __forceinline__ void fence_async_smem() { asm volatile("fence.proxy.async.shared::cta;" ::: "memory"); }
__device__ __forceinline__ void fence_async_all() { asm volatile("fence.acquire.gpu;\nfence.proxy.async.global;" ::: "memory"); }
__device__ __forceinline__ void wg_fence() { asm volatile("wgmma.fence.sync.aligned;" ::: "memory"); }
__device__ __forceinline__ void wg_commit() { asm volatile("wgmma.commit_group.sync.aligned;" ::: "memory"); }
template <int N> __device__ __forceinline__ void wg_wait() { asm volatile("wgmma.wait_group.sync.aligned %0;" :: "n"(N) : "memory"); }
template <int N> __device__ __forceinline__ void pin(float* d) {
#pragma unroll
    for (int i = 0; i < N; i++) asm volatile("" : "+f"(d[i]) :: "memory");
}
template <int N> __device__ __forceinline__ void pin(uint32_t* d) {
#pragma unroll
    for (int i = 0; i < N; i++) asm volatile("" : "+r"(d[i]) :: "memory");
}
constexpr uint32_t SMEM_BASE = 1024;
__device__ __forceinline__ uint64_t mkdesc(uint32_t off, uint32_t lbo, uint32_t sbo, uint32_t swz) {
    return (uint64_t)((SMEM_BASE + off) >> 4) | ((uint64_t)(lbo >> 4) << 16) | ((uint64_t)(sbo >> 4) << 32) | ((uint64_t)swz << 62);
}
__device__ __forceinline__ float ex2f(float x) { float y; asm("ex2.approx.ftz.f32 %0, %1;" : "=f"(y) : "f"(x)); return y; }
__device__ __forceinline__ float rcpf(float x) { float y; asm("rcp.approx.ftz.f32 %0, %1;" : "=f"(y) : "f"(x)); return y; }
__device__ __forceinline__ uint32_t pack_bf16(float lo, float hi) { uint32_t r; asm("cvt.rn.bf16x2.f32 %0, %1, %2;" : "=r"(r) : "f"(hi), "f"(lo)); return r; }
__device__ __forceinline__ float bf_lo(uint32_t v) { return __uint_as_float(v << 16); }
__device__ __forceinline__ float bf_hi(uint32_t v) { return __uint_as_float(v & 0xFFFF0000u); }
__device__ __forceinline__ float bf_round(float x) { return __bfloat162float(__float2bfloat16_rn(x)); }
__device__ __forceinline__ float siluf(float g) { return g * rcpf(1.0f + ex2f(g * -1.4426950408889634f)); }

__device__ __forceinline__ void wgmma_ss_n128_zero(float* d, uint64_t da, uint64_t db) {
    asm volatile("wgmma.mma_async.sync.aligned.m64n128k16.f32.bf16.bf16 {"
        "%0,%1,%2,%3,%4,%5,%6,%7,%8,%9,%10,%11,%12,%13,%14,%15,%16,%17,%18,%19,%20,%21,%22,%23,%24,%25,%26,%27,%28,%29,%30,%31,%32,%33,%34,%35,%36,%37,%38,%39,"
        "%40,%41,%42,%43,%44,%45,%46,%47,%48,%49,%50,%51,%52,%53,%54,%55,%56,%57,%58,%59,%60,%61,%62,%63"
        "}, %64, %65, 0, 1, 1, 0, 1;\n"
        : "=f"(d[0]),"=f"(d[1]),"=f"(d[2]),"=f"(d[3]),"=f"(d[4]),"=f"(d[5]),"=f"(d[6]),"=f"(d[7]),"=f"(d[8]),"=f"(d[9]),"=f"(d[10]),"=f"(d[11]),"=f"(d[12]),
          "=f"(d[13]),"=f"(d[14]),"=f"(d[15]),"=f"(d[16]),"=f"(d[17]),"=f"(d[18]),"=f"(d[19]),"=f"(d[20]),"=f"(d[21]),"=f"(d[22]),"=f"(d[23]),"=f"(d[24]),
          "=f"(d[25]),"=f"(d[26]),"=f"(d[27]),"=f"(d[28]),"=f"(d[29]),"=f"(d[30]),"=f"(d[31]),"=f"(d[32]),"=f"(d[33]),"=f"(d[34]),"=f"(d[35]),"=f"(d[36]),
          "=f"(d[37]),"=f"(d[38]),"=f"(d[39]),"=f"(d[40]),"=f"(d[41]),"=f"(d[42]),"=f"(d[43]),"=f"(d[44]),"=f"(d[45]),"=f"(d[46]),"=f"(d[47]),"=f"(d[48]),
          "=f"(d[49]),"=f"(d[50]),"=f"(d[51]),"=f"(d[52]),"=f"(d[53]),"=f"(d[54]),"=f"(d[55]),"=f"(d[56]),"=f"(d[57]),"=f"(d[58]),"=f"(d[59]),"=f"(d[60]),
          "=f"(d[61]),"=f"(d[62]),"=f"(d[63])
        : "l"(da), "l"(db));
}
__device__ __forceinline__ void wgmma_ss_n128_acc(float* d, uint64_t da, uint64_t db) {
    asm volatile("wgmma.mma_async.sync.aligned.m64n128k16.f32.bf16.bf16 {"
        "%0,%1,%2,%3,%4,%5,%6,%7,%8,%9,%10,%11,%12,%13,%14,%15,%16,%17,%18,%19,%20,%21,%22,%23,%24,%25,%26,%27,%28,%29,%30,%31,%32,%33,%34,%35,%36,%37,%38,%39,"
        "%40,%41,%42,%43,%44,%45,%46,%47,%48,%49,%50,%51,%52,%53,%54,%55,%56,%57,%58,%59,%60,%61,%62,%63"
        "}, %64, %65, 1, 1, 1, 0, 1;\n"
        : "+f"(d[0]),"+f"(d[1]),"+f"(d[2]),"+f"(d[3]),"+f"(d[4]),"+f"(d[5]),"+f"(d[6]),"+f"(d[7]),"+f"(d[8]),"+f"(d[9]),"+f"(d[10]),"+f"(d[11]),"+f"(d[12]),
          "+f"(d[13]),"+f"(d[14]),"+f"(d[15]),"+f"(d[16]),"+f"(d[17]),"+f"(d[18]),"+f"(d[19]),"+f"(d[20]),"+f"(d[21]),"+f"(d[22]),"+f"(d[23]),"+f"(d[24]),
          "+f"(d[25]),"+f"(d[26]),"+f"(d[27]),"+f"(d[28]),"+f"(d[29]),"+f"(d[30]),"+f"(d[31]),"+f"(d[32]),"+f"(d[33]),"+f"(d[34]),"+f"(d[35]),"+f"(d[36]),
          "+f"(d[37]),"+f"(d[38]),"+f"(d[39]),"+f"(d[40]),"+f"(d[41]),"+f"(d[42]),"+f"(d[43]),"+f"(d[44]),"+f"(d[45]),"+f"(d[46]),"+f"(d[47]),"+f"(d[48]),
          "+f"(d[49]),"+f"(d[50]),"+f"(d[51]),"+f"(d[52]),"+f"(d[53]),"+f"(d[54]),"+f"(d[55]),"+f"(d[56]),"+f"(d[57]),"+f"(d[58]),"+f"(d[59]),"+f"(d[60]),
          "+f"(d[61]),"+f"(d[62]),"+f"(d[63])
        : "l"(da), "l"(db));
}
__device__ __forceinline__ void wgmma_ss_n64(float* d, uint64_t da, uint64_t db, int acc) {
    asm volatile("{\n.reg .pred p;\nsetp.ne.b32 p, %34, 0;\nwgmma.mma_async.sync.aligned.m64n64k16.f32.bf16.bf16 {"
        "%0,%1,%2,%3,%4,%5,%6,%7,%8,%9,%10,%11,%12,%13,%14,%15,%16,%17,%18,%19,%20,%21,%22,%23,%24,%25,%26,%27,%28,%29,%30,%31"
        "}, %32, %33, p, 1, 1, 0, 1;\n}\n"
        : "+f"(d[0]),"+f"(d[1]),"+f"(d[2]),"+f"(d[3]),"+f"(d[4]),"+f"(d[5]),"+f"(d[6]),"+f"(d[7]),"+f"(d[8]),"+f"(d[9]),"+f"(d[10]),"+f"(d[11]),"+f"(d[12]),
          "+f"(d[13]),"+f"(d[14]),"+f"(d[15]),"+f"(d[16]),"+f"(d[17]),"+f"(d[18]),"+f"(d[19]),"+f"(d[20]),"+f"(d[21]),"+f"(d[22]),"+f"(d[23]),"+f"(d[24]),
          "+f"(d[25]),"+f"(d[26]),"+f"(d[27]),"+f"(d[28]),"+f"(d[29]),"+f"(d[30]),"+f"(d[31])
        : "l"(da), "l"(db), "r"(acc));
}
__device__ __forceinline__ void wgmma_rs_n64_zero(float* d, const uint32_t* a, uint64_t db) {
    asm volatile("wgmma.mma_async.sync.aligned.m64n64k16.f32.bf16.bf16 {"
        "%0,%1,%2,%3,%4,%5,%6,%7,%8,%9,%10,%11,%12,%13,%14,%15,%16,%17,%18,%19,%20,%21,%22,%23,%24,%25,%26,%27,%28,%29,%30,%31"
        "}, {%32,%33,%34,%35}, %36, 0, 1, 1, 0;\n"
        : "=f"(d[0]),"=f"(d[1]),"=f"(d[2]),"=f"(d[3]),"=f"(d[4]),"=f"(d[5]),"=f"(d[6]),"=f"(d[7]),"=f"(d[8]),"=f"(d[9]),"=f"(d[10]),"=f"(d[11]),"=f"(d[12]),
          "=f"(d[13]),"=f"(d[14]),"=f"(d[15]),"=f"(d[16]),"=f"(d[17]),"=f"(d[18]),"=f"(d[19]),"=f"(d[20]),"=f"(d[21]),"=f"(d[22]),"=f"(d[23]),"=f"(d[24]),
          "=f"(d[25]),"=f"(d[26]),"=f"(d[27]),"=f"(d[28]),"=f"(d[29]),"=f"(d[30]),"=f"(d[31])
        : "r"(a[0]), "r"(a[1]), "r"(a[2]), "r"(a[3]), "l"(db));
}
__device__ __forceinline__ void wgmma_rs_n64_acc(float* d, const uint32_t* a, uint64_t db) {
    asm volatile("wgmma.mma_async.sync.aligned.m64n64k16.f32.bf16.bf16 {"
        "%0,%1,%2,%3,%4,%5,%6,%7,%8,%9,%10,%11,%12,%13,%14,%15,%16,%17,%18,%19,%20,%21,%22,%23,%24,%25,%26,%27,%28,%29,%30,%31"
        "}, {%32,%33,%34,%35}, %36, 1, 1, 1, 0;\n"
        : "+f"(d[0]),"+f"(d[1]),"+f"(d[2]),"+f"(d[3]),"+f"(d[4]),"+f"(d[5]),"+f"(d[6]),"+f"(d[7]),"+f"(d[8]),"+f"(d[9]),"+f"(d[10]),"+f"(d[11]),"+f"(d[12]),
          "+f"(d[13]),"+f"(d[14]),"+f"(d[15]),"+f"(d[16]),"+f"(d[17]),"+f"(d[18]),"+f"(d[19]),"+f"(d[20]),"+f"(d[21]),"+f"(d[22]),"+f"(d[23]),"+f"(d[24]),
          "+f"(d[25]),"+f"(d[26]),"+f"(d[27]),"+f"(d[28]),"+f"(d[29]),"+f"(d[30]),"+f"(d[31])
        : "r"(a[0]), "r"(a[1]), "r"(a[2]), "r"(a[3]), "l"(db));
}
__device__ __forceinline__ void wgmma_rs_n24_acc(float* d, const uint32_t* a, uint64_t db) {
    asm volatile("wgmma.mma_async.sync.aligned.m64n24k16.f32.bf16.bf16 {"
        "%0,%1,%2,%3,%4,%5,%6,%7,%8,%9,%10,%11"
        "}, {%12,%13,%14,%15}, %16, 1, 1, 1, 1;\n"
        : "+f"(d[0]),"+f"(d[1]),"+f"(d[2]),"+f"(d[3]),"+f"(d[4]),"+f"(d[5]),"+f"(d[6]),"+f"(d[7]),"+f"(d[8]),"+f"(d[9]),"+f"(d[10]),"+f"(d[11])
        : "r"(a[0]), "r"(a[1]), "r"(a[2]), "r"(a[3]), "l"(db));
}

constexpr int OFF_ONES = 131072;
constexpr int OFF_RING = OFF_ONES + 4096;
constexpr int NRING = 5;
constexpr int OFF_B2 = OFF_RING + NRING * 16384;
constexpr int OFF_CS = OFF_B2 + 2048;
constexpr int OFF_RS = OFF_CS + 2560;
constexpr int OFF_BAR = OFF_RS + 1024;
enum { B_FULL = 0, B_EMPTY = 40, B_TILE = 80, B_OW = 85, B_CNT1 = 87, B_STATS = 87, B_KV = 92, B_RING = 100, B_WO = 103, B_O = 104,
       B_QKV = 112, B_DONE = 113, B_NUM = 120 };
constexpr int OFF_TS = OFF_BAR + 1024;
constexpr int SMEM_BYTES = OFF_BAR + B_NUM * 8;
constexpr unsigned FIXED_MASK = 0xB5;
constexpr float P71 = 2361183241434822606848.0f, M71 = 4.235164736271502e-22f;

__device__ __forceinline__ uint32_t exp2_fixed(float lo, float hi, uint32_t half2) {
    uint32_t y, g, d;
    asm("cvt.pack.sat.s16.s32 %0, %1, %2;" : "=r"(y) : "r"(__float_as_uint(hi)), "r"(__float_as_uint(lo)));
    asm("lop3.b32 %0, %1, 0x007F007F, %2, 0xEA;" : "=r"(g) : "r"(y), "r"(half2));
    asm("fma.rn.bf16x2 %0, %1, %2, %3;" : "=r"(d) : "r"(y), "r"(g), "r"(y & 0xFF80FF80u));
    return d;
}
constexpr uint64_t DK_STEP = 512 - (256ull << 16), DV_STEP = 512 - (256ull << 32);
constexpr uint32_t POS_LAST = 0x37521640u;
#define ORD_LAG 2

__global__ void __cluster_dims__(2, 1, 1) __launch_bounds__(640, 1)
mega_kernel(const __nv_bfloat16* __restrict__ x, const __nv_bfloat16* __restrict__ wqkv, const __nv_bfloat16* __restrict__ w1,
            const __nv_bfloat16* __restrict__ w3, __nv_bfloat16* __restrict__ out,
            const __grid_constant__ CUtensorMap mx, const __grid_constant__ CUtensorMap mqkv, const __grid_constant__ CUtensorMap mw1,
            const __grid_constant__ CUtensorMap mw3, const __grid_constant__ CUtensorMap mw2, const __grid_constant__ CUtensorMap mwo,
            uint32_t half2) {
    extern __shared__ __align__(1024) uint8_t smem_raw[];
    const uint32_t sb = __shfl_sync(0xffffffffu, smem_u32(smem_raw), 0);
    if ((sb & 0xFFFFFF) != SMEM_BASE) __trap();
    const uint32_t bars = sb + OFF_BAR, ring = sb + OFF_RING;
    const int tid = threadIdx.x, lane = tid & 31, g = lane >> 2, t4 = lane & 3;
    const int warp = __shfl_sync(0xffffffffu, tid >> 5, 0), wg = warp >> 2, wq = warp & 3;
    const int rank = blockIdx.x & 1, cl = blockIdx.x >> 1;
    const int grp = cl < 4 ? 4 + cl : cl < 36 ? (cl - 4) >> 3 : 4 + (cl - 36) / 7;
    const int rot = cl < 4 ? 7 : cl < 36 ? (cl - 4) & 7 : (cl - 36) % 7;
    const int mblk = rot * 2 + rank;
    const int nq = grp < 4 ? 2 : 1;
    const int qt0 = grp < 4 ? 2 * grp : 4 + grp;
    const int gu0 = (grp < 4 ? 3 * grp : 4 * grp - 4) - nq;
    const int head = blockIdx.x >> 2, qb = blockIdx.x & 3;

    if (elect_one()) {
#pragma unroll
        for (int i = 0; i < 6; i++) { const int b = warp * 6 + i; mbar_init(bars + 8 * b, b >= B_EMPTY && b < B_CNT1 ? 8 : b == B_QKV ? 2 : b == B_DONE ? 4 : 1); }
        if (warp == 0) {
            fence_async_smem();
#pragma unroll
            for (int j = 0; j < 2; j++) {
                tma2d(sb + j * 16384, &mx, j * 64, mblk * 128, bars + 8 * (B_FULL + j));
                tma2d(ring + j * 16384, &mqkv, qt0 * 128, j * 64, bars + 8 * (B_FULL + j));
                tma2d(ring + j * 16384 + 8192, &mqkv, qt0 * 128 + 64, j * 64, bars + 8 * (B_FULL + j));
            }
        }
#pragma unroll
        for (int i = 0; i < 6; i++) {
            const int b = warp * 6 + i;
            if (b < B_EMPTY) mbar_expect(bars + 8 * b, b < 8 ? 32768 : 16384);
        }
        if (warp == 16) asm volatile("prefetch.tensormap [%0];" :: "l"(rank ? &mw3 : &mw1) : "memory");
        asm volatile("fence.mbarrier_init.release.cluster;" ::: "memory");
    }
    __syncthreads();
    if (tid == 512) TSTAMP(26);
    asm volatile("barrier.cluster.arrive.relaxed.aligned;" ::: "memory");

    if (wg < 4) {
        const int pair = wg >> 1, half = wg & 1;
        if (pair == 1) {
            const int row = mblk * 128 + grp * 16 + (warp - 8) * 2 + (lane >> 4);
            uint4 v[6];
            const uint32_t* w = reinterpret_cast<const uint32_t*>(v);
#pragma unroll
            for (int j = 0; j < 2; j++) v[4 + j] = __ldg(reinterpret_cast<const uint4*>(wqkv + (size_t)(rot * 64 + (warp - 8) * 8 + j * 4 + (lane >> 3)) * (3 * DM) + qt0 * 128 + rank * 64) + (lane & 7));
#pragma unroll
            for (int j = 0; j < 4; j++) v[j] = __ldg(reinterpret_cast<const uint4*>(x + (size_t)row * DM) + j * 16 + (lane & 15));
            const uint32_t tag = ld_epoch() + 1;
            float c[8];
#pragma unroll
            for (int e = 0; e < 4; e++) { c[2 * e] = bf_lo(w[16 + e]) + bf_lo(w[20 + e]); c[2 * e + 1] = bf_hi(w[16 + e]) + bf_hi(w[20 + e]); }
#pragma unroll
            for (int n = 4; n > 1; n >>= 1) {
                const bool up = lane & (4 * n);
#pragma unroll
                for (int e = 0; e < n; e++) c[e] = (up ? c[e + n] : c[e]) + __shfl_xor_sync(0xffffffffu, up ? c[e] : c[e + n], 4 * n);
            }
            asm volatile("st.shared.v2.f32 [%0], {%1,%2};" :: "r"(sb + OFF_CS + 512 + (warp - 8) * 256 + (lane & 7) * 32 + (lane >> 3) * 8), "f"(c[0]), "f"(c[1]) : "memory");
            bar_sync(6, 256);
            if (warp < 10) {
#pragma unroll
                for (int e = 0; e < 8; e++) asm volatile("ld.shared.f32 %0, [%1];" : "=f"(c[e]) : "r"(sb + OFF_CS + 512 + e * 256 + (tid & 63) * 4));
                st_tagged(reinterpret_cast<unsigned long long*>(g_cs) + (grp * 40 + rot) * 128 + rank * 64 + (tid & 63),
                          __float_as_uint(((c[0] + c[1]) + (c[2] + c[3])) + ((c[4] + c[5]) + (c[6] + c[7]))), tag);
                if (tid == 256) TSTAMP(40);
            }
            float sa[4] = {0.f, 0.f, 0.f, 0.f}, sq[4] = {0.f, 0.f, 0.f, 0.f};
#pragma unroll
            for (int j = 0; j < 16; j++) sa[j & 3] += bf_lo(w[j]) + bf_hi(w[j]);
            float mean = ((sa[0] + sa[1]) + (sa[2] + sa[3])) * (1.0f / 32);
#pragma unroll
            for (int j = 0; j < 16; j++) { const float a = bf_lo(w[j]) - mean, b = bf_hi(w[j]) - mean; sq[j & 1] = fmaf(a, a, sq[j & 1]); sq[2 + (j & 1)] = fmaf(b, b, sq[2 + (j & 1)]); }
            float m2 = (sq[0] + sq[1]) + (sq[2] + sq[3]);
#pragma unroll
            for (int d = 1; d < 16; d <<= 1) {
                const float om = __shfl_xor_sync(0xffffffffu, mean, d), o2 = __shfl_xor_sync(0xffffffffu, m2, d), dm = mean - om;
                m2 = fmaf(dm * dm, 16.0f * d, m2 + o2); mean = 0.5f * (mean + om);
            }
            float sd;
            asm("sqrt.approx.f32 %0, %1;" : "=f"(sd) : "f"(bf_round(bf_round(m2 * (1.0f / DM)) + 1e-5f)));
            if ((lane & 15) == 0) st_tagged(reinterpret_cast<unsigned long long*>(g_rs) + row, pack_bf16(mean, sd), tag);
            if (tid == 256) TSTAMP(45);
        }

        uint32_t q[4], qn[6];
        {
            const int rowblk = mblk * 2 + half, tile16 = rowblk * 4 + wq;
            uint32_t empty;
            asm("mapa.shared::cluster.u32 %0, %1, %2;" : "=r"(empty) : "r"(bars + 8 * B_EMPTY), "r"(wq & 1));
#pragma unroll 1
            for (int t = pair; t < 5; t += 2) {
                float acc[64];
                uint32_t full = bars + 8 * (B_FULL + 8 * t), rel = empty + 64 * t;
                uint32_t stepa = t == 4 ? 0x4AB93AC : 0x9999999, stepb = (uint32_t)(0x994999949999ull >> (4 * ((0x24130u >> (4 * t)) & 7)));
                uint64_t da = mkdesc(half * 8192, 16, 1024, 1), db = mkdesc(OFF_RING, 8192, 1024, 1) + ((0x24130u >> (4 * t)) & 7) * 1024;
                if (tid == 0 && t == 0) TSTAMP(30);
                mbar_wait(full, 0);
                if (t > 0) mbar_wait(full + 8 * (B_EMPTY - ORD_LAG), 0);
                wg_fence();
                wgmma_ss_n128_zero(acc, da, db);
#pragma unroll
                for (int k = 1; k < 4; k++) wgmma_ss_n128_acc(acc, da + k * 2, db + k * 128);
                wg_commit();
                mbar_wait(full + 8, 0);
#pragma unroll 1
                do {
                    da += (int)((stepa & 15) << 10) - 8192; db += (int)((stepb & 15) << 10) - 8192;
                    stepa >>= 4; stepb >>= 4;
                    wg_fence();
#pragma unroll
                    for (int k = 0; k < 4; k++) wgmma_ss_n128_acc(acc, da + k * 2, db + k * 128);
                    wg_commit();
                    mbar_wait(full + 16, 0);
                    wg_wait<1>();
                    if (elect_one()) mbar_arrive_remote(rel);
                    full += 8; rel += 8;
                } while (stepa);
                if (t >= 3) {
                    mbar_wait(bars + 8 * B_QKV, 0);
                    const uint4* pq = g_q + (head * 128 + (qb * 8 + wg) * 4 + wq) * 32 + lane;
                    const uint4 v = __ldcg(pq), u = __ldcg(pq + 512);
                    qn[0] = v.x; qn[1] = v.y; qn[2] = v.z; qn[3] = v.w; q[0] = u.x; q[1] = u.y; q[2] = u.z; q[3] = u.w;
                }
                wg_wait<0>();
                if (elect_one()) mbar_arrive_remote(rel);
                pin<64>(acc);
                if (wq == 0 && half == 0 && lane == 0) TSTAMP(2 + 2 * t);
                mbar_wait(bars + 8 * (B_STATS + t), 0);
                uint32_t rs0, rs1;
                asm volatile("ld.shared.b32 %0, [%1];" : "=r"(rs0) : "r"(sb + OFF_RS + (half * 64 + wq * 16 + g) * 4));
                asm volatile("ld.shared.b32 %0, [%1];" : "=r"(rs1) : "r"(sb + OFF_RS + (half * 64 + wq * 16 + g + 8) * 4));
                const float m0 = bf_lo(rs0), m1 = bf_lo(rs1);
                float d0 = bf_hi(rs0), d1 = bf_hi(rs1);
#pragma unroll
                for (int j = 0; j < 16; j++) {
                    float c0, c1;
                    asm volatile("ld.shared.v2.f32 {%0,%1}, [%2];" : "=f"(c0), "=f"(c1) : "r"(sb + OFF_CS + (t * 128 + j * 8 + t4 * 2) * 4));
                    acc[4 * j] = fmaf(-m0, c0, acc[4 * j]); acc[4 * j + 1] = fmaf(-m0, c1, acc[4 * j + 1]);
                    acc[4 * j + 2] = fmaf(-m1, c0, acc[4 * j + 2]); acc[4 * j + 3] = fmaf(-m1, c1, acc[4 * j + 3]);
                }
                float r0 = rcpf(d0), r1 = rcpf(d1);
                if (t < nq) {
                    const int qt = qt0 + t;
                    if (qt < 4) {
                        r0 *= 0.25f * 1.4426950408889634f * M71; r1 *= 0.25f * 1.4426950408889634f * M71;
                    } else if (qt < 8) {
                        r0 *= ((FIXED_MASK >> (2 * wq)) & 1) ? M71 : P71; r1 *= ((FIXED_MASK >> (2 * wq + 1)) & 1) ? M71 : P71;
                    }
                    uint32_t e[32];
#pragma unroll
                    for (int i = 0; i < 32; i++) { const float r = (i & 1) ? r1 : r0; e[i] = pack_bf16(acc[2 * i] * r, acc[2 * i + 1] * r); }
                    if (qt < 4) {
                        uint4* p = g_q + (qt * 1024 + tile16) * 32 + lane;
#pragma unroll
                        for (int hh = 0; hh < 8; hh++) p[hh * 4096] = make_uint4(e[4 * hh], e[4 * hh + 1], e[4 * hh + 2], e[4 * hh + 3]);
                    } else {
                        uint32_t* p = reinterpret_cast<uint32_t*>(g_kv + (qt - 4) * 32768) + tile16 * 64 + lane;
#pragma unroll
                        for (int i = 0; i < 32; i++) p[(i >> 1) * 8192 + (i & 1) * 32] = e[i];
                    }
                } else {
                    uint32_t* p = reinterpret_cast<uint32_t*>(g_h + (rowblk * 28 + gu0 + t) * 512) + wq * 512 + lane;
                    r0 *= -1.4426950408889634f; r1 *= -1.4426950408889634f; d0 *= d0; d1 *= d1;
#pragma unroll
                    for (int j = 0; j < 8; j++) {
                        const float* a = acc + j * 4; const float* b = a + 32;
                        p[j * 32] = pack_bf16(a[0] * b[0] * rcpf(fmaf(ex2f(a[0] * r0), d0, d0)), a[1] * b[1] * rcpf(fmaf(ex2f(a[1] * r0), d0, d0)));
                        p[256 + j * 32] = pack_bf16(a[2] * b[2] * rcpf(fmaf(ex2f(a[2] * r1), d1, d1)), a[3] * b[3] * rcpf(fmaf(ex2f(a[3] * r1), d1, d1)));
                    }
                }
                __syncwarp();
                if (elect_one()) mbar_arrive(bars + 8 * (B_TILE + t));
                if (wq == 0 && half == 0 && lane == 0) TSTAMP(3 + 2 * t);
            }
        }
        const uint64_t db2 = mkdesc(OFF_B2, 128, 256, 0);
        float s[32];
        auto ref_point = [&](int ntile, uint32_t& b0, uint32_t& b1) {
            float m0 = -INFINITY, m1 = -INFINITY, f0 = -INFINITY, f1 = -INFINITY;
#pragma unroll 1
            for (int t = 0; t < ntile; t++) {
                wg_fence();
                wgmma_rs_n64_zero(s, q, mkdesc(4096, 94208, 128, 0) + (t >> 2) * DK_STEP + (t & 3) * 64);
                wg_commit();
                wg_wait<0>();
                pin<32>(s);
#pragma unroll
                for (int i = 0; i < 8; i++) {
                    if ((FIXED_MASK >> i) & 1) { f0 = fmaxf(f0, fmaxf(s[4 * i], s[4 * i + 1])); f1 = fmaxf(f1, fmaxf(s[4 * i + 2], s[4 * i + 3])); }
                    else                       { m0 = fmaxf(m0, fmaxf(s[4 * i], s[4 * i + 1])); m1 = fmaxf(m1, fmaxf(s[4 * i + 2], s[4 * i + 3])); }
                }
            }
            m0 = fmaxf(m0, f0 * P71 * P71); m1 = fmaxf(m1, f1 * P71 * P71);
            m0 = fmaxf(m0, __shfl_xor_sync(0xffffffffu, m0, 1)); m1 = fmaxf(m1, __shfl_xor_sync(0xffffffffu, m1, 1));
            m0 = fmaxf(m0, __shfl_xor_sync(0xffffffffu, m0, 2)); m1 = fmaxf(m1, __shfl_xor_sync(0xffffffffu, m1, 2));
#pragma unroll
            for (int r = 0; r < 2; r++) {
                const float m = -rintf(r ? m1 : m0), mh = bf_round(m), mm = bf_round(m - mh), ml = m - mh - mm;
                const float lo = t4 == 0 ? mh : t4 == 1 ? ml : t4 == 2 ? 1.f : 0.f, hi = t4 == 0 ? mm : t4 == 1 ? 1.f : 0.f;
                (r ? b1 : b0) = pack_bf16(lo * M71, hi * M71);
            }
        };
        uint32_t q2[4];
        int redo = 1;
        mbar_wait(bars + 8 * B_KV, 0);
#pragma unroll 1
        for (int round = -1; round < 2;) {
            if (redo) ref_point(redo, q2[0], q2[1]);
            if (round < 0) {
#pragma unroll
                for (int i = 0; i < 4; i++) { const uint32_t tq = q[i]; q[i] = qn[i]; qn[i] = tq; }
                qn[4] = q2[0]; qn[5] = q2[1];
                q2[2] = __shfl_sync(0xffffffffu, q2[0], 3); q2[3] = __shfl_sync(0xffffffffu, q2[1], 3);
                round = 0;
                continue;
            }
            float o[12]; uint32_t p[16];
#pragma unroll
            for (int i = 0; i < 12; i++) o[i] = 0.f;
            pin<12>(o); pin<4>(q2);
            if (wq == 0 && half == 0 && lane == 0) TSTAMP(12 + 4 * round + pair);
            uint64_t dk = mkdesc(4096, 94208, 128, 0), dv = mkdesc(0, 128, 65536, 0);
#pragma unroll 1
            for (int c = 0; c < 8; c++, dk += DK_STEP, dv += DV_STEP) {
                if (round == 0) mbar_wait(bars + 8 * (B_KV + c), 0);
#pragma unroll
                for (int t = 0; t < 4; t++) {
                    wg_fence();
                    wgmma_rs_n64_zero(s, q, dk + t * 64);
                    wgmma_rs_n64_acc(s, q2, db2);
                    wg_commit();
                    wg_wait<0>();
                    pin<32>(s); pin<16>(p);
#pragma unroll
                    for (int i = 0; i < 16; i++) {
                        if ((FIXED_MASK >> (i >> 1)) & 1) p[i] = exp2_fixed(s[2 * i], s[2 * i + 1], half2);
                        else                              p[i] = pack_bf16(ex2f(s[2 * i]), ex2f(s[2 * i + 1]));
                    }
                    wg_fence();
#pragma unroll
                    for (int k = 0; k < 4; k++) wgmma_rs_n24_acc(o, p + 4 * k, dv + (t * 4 + k) * 16);
                    wg_commit();
                }
            }
            wg_wait<0>();
            pin<12>(o);
            if (redo != 32) {
                float chk = (o[8] + o[10]) * 256.f;
#pragma unroll
                for (int i = 0; i < 8; i++) chk += fabsf(o[i]);
                uint32_t bad;
                asm volatile("{\n.reg .pred p, q;\nsetp.geu.f32 q, %1, 0f7F800000;\nbar.red.or.pred p, %2, 128, q;\nselp.u32 %0, 1, 0, p;\n}" : "=r"(bad) : "f"(chk), "r"(1 + wg) : "memory");
                if (__any_sync(0xffffffffu, bad)) { redo = 32; continue; }
            }
            const int rowblk = qb * 8 + round * 4 + wg;
            const float r0 = rcpf(o[8]), r1 = rcpf(o[10]);
            uint32_t* po = reinterpret_cast<uint32_t*>(g_o + (rowblk * 8 + (head >> 2)) * 512) + wq * 512 + (head & 3) * 64 + lane;
            po[0] = pack_bf16(o[0] * r0, o[1] * r0); po[256] = pack_bf16(o[2] * r1, o[3] * r1);
            po[32] = pack_bf16(o[4] * r0, o[5] * r0); po[288] = pack_bf16(o[6] * r1, o[7] * r1);
            if (round == 0) {
                __syncwarp();
                if (elect_one()) mbar_arrive(bars + 8 * (B_OW + pair));
            } else {
                bar_sync(1 + wg, 128);
                if (wq == 0 && elect_one()) { mbar_arrive(bars + 8 * B_DONE); signal_cnt(C_O + rowblk); }
            }
#pragma unroll
            for (int i = 0; i < 4; i++) q[i] = qn[i];
            q2[0] = qn[4]; q2[1] = qn[5];
            redo = 0;
            if (wq == 0 && half == 0 && lane == 0) TSTAMP(14 + 4 * round + pair);
            round++;
        }
    } else {
        uint32_t tag;
        if (wq == 0) {
            asm volatile("barrier.cluster.wait.aligned;" ::: "memory");
            if (tid == 512) TSTAMP(27);
            uint32_t slot = 2;
#pragma unroll 1
            for (int n = 2; n < 40; n++) {
                const int t = n >> 3, j = n & 7;
                const int kc = (n < 32 ? j : (POS_LAST >> (4 * j)) & 7) * 64;
                const CUtensorMap* m = t < nq ? &mqkv : rank ? &mw3 : &mw1;
                const int col = t < nq ? (qt0 + t) * 128 + rank * 64 : (gu0 + t) * 64;
                const uint32_t dst = ring + slot * 16384 + rank * 8192, fb = bars + 8 * (B_FULL + n);
                if (n < 8 && elect_one()) tma2d(sb + n * 16384, &mx, kc, mblk * 128, fb);
                if (n >= NRING) mbar_wait(fb + 8 * (B_EMPTY - NRING), 0);
                if (elect_one()) { TS2(0, n); tma2d_mc(dst, m, col, kc, fb); }
                if (++slot == NRING) slot = 0;
            }
            tag = ld_epoch() + 1;
        } else if (wq == 1) {
            tag = ld_epoch() + 1;
            mbar_wait(bars + 8 * (B_FULL + 5), 0);
#pragma unroll 1
            for (int t = 0; t < 5; t++) {
                float a[4];
#pragma unroll 1
                for (int n = 0; n < 2000000; n++) {
                    uint32_t stale = 0;
                    a[0] = a[1] = a[2] = a[3] = 0.f;
#pragma unroll
                    for (int i = 0; i < 16; i++) {
                        uint32_t u, v;
                        stale |= ld_tagged2(g_cs + (grp * 5 + t) * 512 + i * 32 + lane, tag, u, v);
                        a[(i & 1) * 2] += __uint_as_float(u); a[(i & 1) * 2 + 1] += __uint_as_float(v);
                    }
                    if (__all_sync(0xffffffffu, stale == 0)) break;
                    if (t) __nanosleep(400);
                }
                asm volatile("st.shared.v2.f32 [%0], {%1,%2};" :: "r"(sb + OFF_CS + t * 512 + lane * 8), "f"(a[0]), "f"(a[1]) : "memory");
                asm volatile("st.shared.v2.f32 [%0], {%1,%2};" :: "r"(sb + OFF_CS + t * 512 + 256 + lane * 8), "f"(a[2]), "f"(a[3]) : "memory");
                if (t == 0) {
                    uint32_t r[4];
#pragma unroll 1
                    for (int n = 0; n < 2000000; n++) {
                        const uint32_t stale = ld_tagged2(g_rs + mblk * 64 + lane * 2, tag, r[0], r[1]) | ld_tagged2(g_rs + mblk * 64 + lane * 2 + 1, tag, r[2], r[3]);
                        if (__all_sync(0xffffffffu, stale == 0)) break;
                    }
                    asm volatile("st.shared.v4.b32 [%0], {%1,%2,%3,%4};" :: "r"(sb + OFF_RS + lane * 16), "r"(r[0]), "r"(r[1]), "r"(r[2]), "r"(r[3]) : "memory");
                }
                __syncwarp();
                if (elect_one()) { mbar_arrive(bars + 8 * (B_STATS + t)); TSTAMP(32 + t); }
            }
        } else {
            tag = ld_epoch() + 1;
            mbar_wait(bars + 8 * (B_FULL + wq - 1), 0);
#pragma unroll 1
            for (int t = wq - 1; t < 5; t += 2) {
                const __nv_bfloat16* src; int ld;
                if (t < nq) { src = wqkv + (qt0 + t) * 128 + rank * 64; ld = 3 * DM; }
                else        { src = (rank ? w3 : w1) + (gu0 + t) * 64; ld = FF; }
                src += (size_t)(rot * 64 + (lane >> 3)) * ld + (lane & 7) * 8;
                uint4 v[16];
                const uint32_t* w = reinterpret_cast<const uint32_t*>(v);
#pragma unroll
                for (int j = 0; j < 16; j++) v[j] = __ldg(reinterpret_cast<const uint4*>(src + (size_t)j * 4 * ld));
                float c[8];
#pragma unroll
                for (int e = 0; e < 4; e++) {
                    float a = 0.f, b = 0.f;
#pragma unroll
                    for (int j = 0; j < 16; j++) { a += bf_lo(w[4 * j + e]); b += bf_hi(w[4 * j + e]); }
                    c[2 * e] = a; c[2 * e + 1] = b;
                }
#pragma unroll
                for (int n = 4; n > 1; n >>= 1) {
                    const bool up = lane & (4 * n);
#pragma unroll
                    for (int e = 0; e < n; e++) c[e] = (up ? c[e + n] : c[e]) + __shfl_xor_sync(0xffffffffu, up ? c[e] : c[e + n], 4 * n);
                }
                unsigned long long* dst = reinterpret_cast<unsigned long long*>(g_cs) + ((grp * 5 + t) * 8 + rot) * 128 + rank * 64 + (lane & 7) * 8 + (lane >> 3) * 2;
                st_tagged(dst, __float_as_uint(c[0]), tag); st_tagged(dst + 1, __float_as_uint(c[1]), tag);
                if (lane == 0) TSTAMP(40 + t);
            }
        }
        if (wq == 3) {
#pragma unroll 1
            for (int i = lane; i < 256; i += 32) asm volatile("st.shared.v4.b32 [%0], {%1,%1,%1,%1};" :: "r"(sb + OFF_ONES + i * 16), "r"(0x3F803F80u) : "memory");
#pragma unroll 1
            for (int i = lane; i < 128; i += 32) {
                const bool fx = (FIXED_MASK >> (i >> 4)) & 1;
                uint32_t a = fx ? pack_bf16(M71, M71) : pack_bf16(P71, P71);
                uint32_t b = fx ? pack_bf16(M71, 47.0f * M71) : pack_bf16(P71, -79.5f * P71);
                uint32_t c = fx ? 0u : pack_bf16(0.08214f * P71, 0.f);
                if (i & 8) a = b = c = 0;
                asm volatile("st.shared.v4.b32 [%0], {%1,%2,%3,%4};" :: "r"(sb + OFF_B2 + i * 16), "r"(a), "r"(b), "r"(c), "r"(0) : "memory");
            }
            fence_async_smem();
            __syncwarp();
            if (elect_one()) mbar_arrive(bars + 8 * B_QKV);
        } else if (wq == 1) {
#pragma unroll 1
            for (int i = 0; i < 3; i++) wait_cnt(C_QKV + i * 4 + (head >> 3), 16 * tag, 100);
            fence_async_all();
            if (elect_one()) { mbar_arrive(bars + 8 * B_QKV); TSTAMP(29); }
            mbar_wait(bars + 8 * (B_EMPTY + 31), 0);
            const uint8_t* gk = reinterpret_cast<const uint8_t*>(g_kv + head * 4096);
            const uint8_t* gv = reinterpret_cast<const uint8_t*>(g_kv + (32 + head) * 4096);
#pragma unroll 1
            for (int c = 0; c < 8; c++) {
                mbar_wait(bars + 8 * (B_EMPTY + 34 + (c & 4) + ((c >> 1) & 1)), 0);
                if (elect_one()) {
                    const uint32_t b = bars + 8 * (B_KV + c);
                    mbar_expect(b, 16384);
                    bulk_load(sb + (2 * c + 1) * 4096, gk + c * 4096, 4096, b);
                    bulk_load(sb + 2 * c * 4096, gv + c * 4096, 4096, b);
                    bulk_load(sb + 65536 + c * 4096, gv + 32768 + c * 4096, 4096, b);
                    bulk_load(sb + 98304 + c * 4096, gk + 32768 + c * 4096, 4096, b);
                }
            }
        } else if (wq == 2) {
#pragma unroll 1
            for (int t = 0; t < 5; t++) {
                mbar_wait(bars + 8 * (B_TILE + t), 0);
                if (elect_one()) signal_cnt(t < nq ? C_QKV + qt0 + t : C_H + mblk);
            }
        }
        pin<1>(&tag);
        bar_sync(5, 128);
        if (tid == 639) g_epoch[blockIdx.x] = tag;
        const int cb = blockIdx.x & 7, pr = blockIdx.x >> 3;
        const int rb0 = (pr >> 2) * 8 + (pr & 3);
        uint32_t gate[2][16];
        {
            float dn[64];
            auto load_stage = [&](int kb, int st) {
                const uint32_t b = bars + 8 * (B_RING + st), dst = ring + st * 24576;
                mbar_expect(b, 24576);
                bulk_load(dst, g_h + (rb0 * 28 + kb) * 512, 8192, b);
                bulk_load(dst + 8192, g_h + ((rb0 + 4) * 28 + kb) * 512, 8192, b);
                tma2d(dst + 16384, &mw2, cb * 64, kb * 64, b);
            };
            if (wq == 0) {
                wait_cnt(C_H + (rb0 >> 1), 28 * tag, 200);
                wait_cnt(C_H + (rb0 >> 1) + 2, 28 * tag, 200);
                if (elect_one()) { TSTAMP(20); fence_async_all(); load_stage(0, 0); load_stage(1, 1); }
            }
            int st = 0; uint32_t ph = 0;
#pragma unroll 1
            for (int kb = 0; kb < 28; kb++) {
                mbar_wait(bars + 8 * (B_RING + st), ph);
                const uint64_t da = mkdesc(OFF_RING + st * 24576, 128, 1024, 0), db = mkdesc(OFF_RING + st * 24576 + 16384, 8192, 1024, 1);
                wg_fence();
#pragma unroll
                for (int k = 0; k < 4; k++) { wgmma_ss_n64(dn, da + k * 16, db + k * 128, (kb | k) != 0); wgmma_ss_n64(dn + 32, da + 512 + k * 16, db + k * 128, (kb | k) != 0); }
                wg_commit();
                wg_wait<1>();
                if (wq == 0 && kb < 26 && elect_one()) load_stage(kb + 2, st == 0 ? 2 : st - 1);
                if (++st == 3) { st = 0; ph ^= 1; }
            }
            wg_wait<0>();
            pin<64>(dn);
#pragma unroll
            for (int i = 0; i < 32; i++) gate[i >> 4][i & 15] = pack_bf16(siluf(dn[2 * i]), siluf(dn[2 * i + 1]));
        }
        float acc[32];
        if (tid == 512) TSTAMP(21);
        const uint32_t bar_wo = bars + 8 * B_WO;
        if (wq == 0 && elect_one()) {
            mbar_expect(bar_wo, 65536);
#pragma unroll 1
            for (int i = 0; i < 8; i++) tma2d(ring + i * 8192, &mwo, cb * 64, i * 64, bar_wo);
        }
        if (wq >= 2) {
            mbar_wait(bars + 8 * (B_OW + wq - 2), 0);
            if (elect_one()) {
                signal_cnt(C_O + qb * 8 + 2 * wq - 4);
                asm volatile("red.relaxed.gpu.global.add.u32 [%0], 1;" :: "l"(g_cnt + (C_O + qb * 8 + 2 * wq - 3) * 8) : "memory");
            }
        }
#pragma unroll 1
        for (int tl = 0; tl < 2; tl++) {
            const int rb = rb0 + 4 * tl;
            uint32_t xr[16];
            const uint32_t* px = reinterpret_cast<const uint32_t*>(x + (size_t)(rb * 64 + wq * 16 + g) * DM + cb * 64) + t4;
#pragma unroll
            for (int j = 0; j < 8; j++) { xr[2 * j] = __ldg(px + j * 4); xr[2 * j + 1] = __ldg(px + 8 * DM / 2 + j * 4); }
            if (wq == 0) {
                if (tl == 1) mbar_wait(bars + 8 * B_DONE, 0);
                wait_cnt(C_O + rb, 32 * tag, tl ? 20 : 200);
                if (elect_one()) {
                    fence_async_all();
                    TSTAMP(22 + 2 * tl);
#pragma unroll 1
                    for (int i = 0; i < (tl ? 8 : 2); i++) {
                        mbar_expect(bars + 8 * (B_O + i), 8192);
                        bulk_load((tl ? sb : ring + 65536) + i * 8192, g_o + (rb * 8 + i) * 512, 8192, bars + 8 * (B_O + i));
                    }
                }
            }
            if (tl == 0) mbar_wait(bar_wo, 0);
#pragma unroll 1
            for (int kb = 0; kb < 8; kb++) {
                mbar_wait(bars + 8 * (B_O + kb), tl);
                const uint32_t a = tl == 0 ? OFF_RING + 65536 + (kb & 1) * 8192 : kb * 8192;
                const uint64_t da = mkdesc(a, 128, 1024, 0), db = mkdesc(OFF_RING + kb * 8192, 8192, 1024, 1);
                wg_fence();
#pragma unroll
                for (int k = 0; k < 4; k++) wgmma_ss_n64(acc, da + k * 16, db + k * 128, (kb | k) != 0);
                wg_commit();
                if (tl == 0) {
                    wg_wait<0>();
                    bar_sync(5, 128);
                    if (wq == 0 && kb < 6 && elect_one()) { mbar_expect(bars + 8 * (B_O + kb + 2), 8192); bulk_load(sb + a, g_o + (rb * 8 + kb + 2) * 512, 8192, bars + 8 * (B_O + kb + 2)); }
                }
            }
            wg_wait<0>();
            pin<32>(acc);
            uint32_t* po = reinterpret_cast<uint32_t*>(out + (size_t)(rb * 64 + wq * 16 + g) * DM + cb * 64) + t4;
#pragma unroll
            for (int i = 0; i < 16; i++) {
                const uint32_t r = pack_bf16(fmaf(acc[2 * i], bf_lo(gate[0][i]), bf_lo(xr[i])), fmaf(acc[2 * i + 1], bf_hi(gate[0][i]), bf_hi(xr[i])));
                po[(i & 1) * (8 * DM / 2) + (i >> 1) * 4] = r;
                gate[0][i] = gate[1][i];
            }
            if (tid == 512) TSTAMP(23 + 2 * tl);
        }
    }
}

typedef CUresult (*EncodeFn)(CUtensorMap*, CUtensorMapDataType, cuuint32_t, void*, const cuuint64_t*, const cuuint64_t*, const cuuint32_t*,
                             const cuuint32_t*, CUtensorMapInterleave, CUtensorMapSwizzle, CUtensorMapL2promotion, CUtensorMapFloatOOBfill);

void make_map(EncodeFn fn, CUtensorMap* m, const void* p, int rows, int cols, int box_rows) {
    cuuint64_t dims[2] = {(cuuint64_t)cols, (cuuint64_t)rows};
    cuuint64_t strides[1] = {(cuuint64_t)cols * 2};
    cuuint32_t box[2] = {64, (cuuint32_t)box_rows};
    cuuint32_t es[2] = {1, 1};
    fn(m, CU_TENSOR_MAP_DATA_TYPE_BFLOAT16, 2, const_cast<void*>(p), dims, strides, box, es, CU_TENSOR_MAP_INTERLEAVE_NONE,
       CU_TENSOR_MAP_SWIZZLE_128B, CU_TENSOR_MAP_L2_PROMOTION_L2_128B, CU_TENSOR_MAP_FLOAT_OOB_FILL_NONE);
}

}

extern "C" void kernel_launch(void* const* d_in, const int* in_sizes, int n_in, void* d_out, int out_size) {
    const __nv_bfloat16* x = (const __nv_bfloat16*)d_in[0];
    static EncodeFn fn = nullptr;
    if (!fn) {
        cudaDriverEntryPointQueryResult qr;
        cudaGetDriverEntryPoint("cuTensorMapEncodeTiled", (void**)&fn, cudaEnableDefault, &qr);
        cudaFuncSetAttribute(mega_kernel, cudaFuncAttributeMaxDynamicSharedMemorySize, SMEM_BYTES);
    }
    CUtensorMap mx, mqkv, mw1, mw3, mw2, mwo;
    make_map(fn, &mx, d_in[0], SEQ, DM, 128);
    make_map(fn, &mqkv, d_in[1], DM, 3 * DM, 64);
    make_map(fn, &mwo, d_in[2], DM, DM, 64);
    make_map(fn, &mw1, d_in[4], DM, FF, 64);
    make_map(fn, &mw3, d_in[5], DM, FF, 64);
    make_map(fn, &mw2, d_in[6], FF, DM, 64);
    mega_kernel<<<128, 640, SMEM_BYTES, cudaStreamPerThread>>>(x, (const __nv_bfloat16*)d_in[1], (const __nv_bfloat16*)d_in[4], (const __nv_bfloat16*)d_in[5],
                                                               (__nv_bfloat16*)d_out, mx, mqkv, mw1, mw3, mw2, mwo, 0x3F003F00u);
}
```

```cpp
#include <cuda_runtime.h>
#include <cuda_bf16.h>
#include <cuda.h>
#include <stdint.h>

namespace {

constexpr int SEQ = 2048, DM = 512, FF = 1792;

__device__ uint4 g_q[32 * 128 * 32];
__device__ uint4 g_kv[64 * 4096];
__device__ uint4 g_h[32 * 28 * 512];
__device__ uint4 g_o[32 * 8 * 512];
__device__ ulonglong2 g_cs[40 * 8 * 64];
__device__ ulonglong2 g_rs[SEQ / 2];
constexpr int C_QKV = 0, C_H = 12, C_O = 28, C_NUM = 60;
__device__ unsigned g_cnt[C_NUM * 8];
__device__ unsigned g_epoch[128];
#define TSTAMP(i)
#define TS2(k, i)

__device__ __forceinline__ uint32_t smem_u32(const void* p) { return (uint32_t)__cvta_generic_to_shared(p); }
__device__ __forceinline__ void mbar_init(uint32_t a, int c) { asm volatile("mbarrier.init.shared::cta.b64 [%0], %1;" :: "r"(a), "r"(c)); }
__device__ __forceinline__ void mbar_expect(uint32_t a, int b) { asm volatile("mbarrier.arrive.expect_tx.shared::cta.b64 _, [%0], %1;" :: "r"(a), "r"(b) : "memory"); }
__device__ __forceinline__ void mbar_arrive(uint32_t a) { asm volatile("mbarrier.arrive.shared::cta.b64 _, [%0];" :: "r"(a) : "memory"); }
__device__ __forceinline__ void mbar_arrive_remote(uint32_t a) { asm volatile("mbarrier.arrive.shared::cluster.b64 _, [%0];" :: "r"(a) : "memory"); }
__device__ __forceinline__ bool mbar_try(uint32_t a, uint32_t ph) {
    uint32_t ok;
    asm volatile("{\n.reg .pred p;\nmbarrier.try_wait.parity.shared::cta.b64 p, [%1], %2;\nselp.u32 %0, 1, 0, p;\n}" : "=r"(ok) : "r"(a), "r"(ph) : "memory");
    return ok;
}
__device__ __forceinline__ void mbar_wait(uint32_t a, uint32_t ph) {
    int n = 1 << 22;
#pragma unroll 1
    do { n = __all_sync(0xffffffffu, mbar_try(a, ph)) ? 0 : n - 1; } while (n > 0);
}
__device__ __forceinline__ bool elect_one() {
    uint32_t p;
    asm volatile("{\n.reg .pred P;\nelect.sync _|P, 0xffffffff;\nselp.u32 %0, 1, 0, P;\n}" : "=r"(p));
    return p;
}
__device__ __forceinline__ void signal_cnt(int c) {
    asm volatile("fence.release.gpu;\nred.relaxed.gpu.global.add.u32 [%0], 1;" :: "l"(g_cnt + c * 8) : "memory");
}
__device__ __forceinline__ void wait_cnt(int c, unsigned target, int ns) {
#pragma unroll 1
    for (int n = 0; n < 2000000; n++) {
        unsigned v;
        asm volatile("ld.relaxed.gpu.global.u32 %0, [%1];" : "=r"(v) : "l"(g_cnt + c * 8) : "memory");
        if (__all_sync(0xffffffffu, (int)(v - target) >= 0)) break;
        __nanosleep(ns);
    }
}
__device__ __forceinline__ uint32_t ld_epoch() {
    uint32_t e;
    asm volatile("ld.relaxed.gpu.global.u32 %0, [%1];" : "=r"(e) : "l"(g_epoch + blockIdx.x) : "memory");
    return e;
}
__device__ __forceinline__ void st_relaxed(uint32_t* p, uint32_t v) { asm volatile("st.relaxed.gpu.global.u32 [%0], %1;" :: "l"(p), "r"(v) : "memory"); }
__device__ __forceinline__ void st_tagged(void* p, uint32_t v, uint32_t tag) {
    asm volatile("st.relaxed.gpu.global.b64 [%0], %1;" :: "l"(p), "l"((unsigned long long)tag << 32 | v) : "memory");
}
__device__ __forceinline__ uint32_t ld_tagged2(const ulonglong2* p, uint32_t tag, uint32_t& a, uint32_t& b) {
    unsigned long long u, v;
    asm volatile("ld.relaxed.gpu.global.v2.b64 {%0,%1}, [%2];" : "=l"(u), "=l"(v) : "l"(p) : "memory");
    a = (uint32_t)u; b = (uint32_t)v;
    return ((uint32_t)(u >> 32) ^ tag) | ((uint32_t)(v >> 32) ^ tag);
}
__device__ __forceinline__ void tma2d(uint32_t dst, const CUtensorMap* m, int c0, int c1, uint32_t bar) {
    asm volatile("cp.async.bulk.tensor.2d.shared::cluster.global.mbarrier::complete_tx::bytes [%0], [%1, {%3, %4}], [%2];"
                 :: "r"(dst), "l"(m), "r"(bar), "r"(c0), "r"(c1) : "memory");
}
__device__ __forceinline__ void tma2d_mc(uint32_t dst, const CUtensorMap* m, int c0, int c1, uint32_t bar) {
    asm volatile("cp.async.bulk.tensor.2d.shared::cluster.global.mbarrier::complete_tx::bytes.multicast::cluster [%0], [%1, {%3, %4}], [%2], %5;"
                 :: "r"(dst), "l"(m), "r"(bar), "r"(c0), "r"(c1), "h"((uint16_t)3) : "memory");
}
__device__ __forceinline__ void bulk_load(uint32_t dst, const void* src, int bytes, uint32_t bar) {
    asm volatile("cp.async.bulk.shared::cluster.global.mbarrier::complete_tx::bytes [%0], [%1], %2, [%3];"
                 :: "r"(dst), "l"(src), "r"(bytes), "r"(bar) : "memory");
}
__device__ __forceinline__ void bar_sync(int id, int n) { asm volatile("bar.sync %0, %1;" :: "r"(id), "r"(n) : "memory"); }
__device__ __forceinline__ void fence_async_smem() { asm volatile("fence.proxy.async.shared::cta;" ::: "memory"); }
__device__ __forceinline__ void fence_async_all() { asm volatile("fence.acquire.gpu;\nfence.proxy.async.global;" ::: "memory"); }
__device__ __forceinline__ void wg_fence() { asm volatile("wgmma.fence.sync.aligned;" ::: "memory"); }
__device__ __forceinline__ void wg_commit() { asm volatile("wgmma.commit_group.sync.aligned;" ::: "memory"); }
template <int N> __device__ __forceinline__ void wg_wait() { asm volatile("wgmma.wait_group.sync.aligned %0;" :: "n"(N) : "memory"); }
template <int N> __device__ __forceinline__ void pin(float* d) {
#pragma unroll
    for (int i = 0; i < N; i++) asm volatile("" : "+f"(d[i]) :: "memory");
}
template <int N> __device__ __forceinline__ void pin(uint32_t* d) {
#pragma unroll
    for (int i = 0; i < N; i++) asm volatile("" : "+r"(d[i]) :: "memory");
}
constexpr uint32_t SMEM_BASE = 1024;
__device__ __forceinline__ uint64_t mkdesc(uint32_t off, uint32_t lbo, uint32_t sbo, uint32_t swz) {
    return (uint64_t)((SMEM_BASE + off) >> 4) | ((uint64_t)(lbo >> 4) << 16) | ((uint64_t)(sbo >> 4) << 32) | ((uint64_t)swz << 62);
}
__device__ __forceinline__ float ex2f(float x) { float y; asm("ex2.approx.ftz.f32 %0, %1;" : "=f"(y) : "f"(x)); return y; }
__device__ __forceinline__ float rcpf(float x) { float y; asm("rcp.approx.ftz.f32 %0, %1;" : "=f"(y) : "f"(x)); return y; }
__device__ __forceinline__ uint32_t pack_bf16(float lo, float hi) { uint32_t r; asm("cvt.rn.bf16x2.f32 %0, %1, %2;" : "=r"(r) : "f"(hi), "f"(lo)); return r; }
__device__ __forceinline__ float bf_lo(uint32_t v) { return __uint_as_float(v << 16); }
__device__ __forceinline__ float bf_hi(uint32_t v) { return __uint_as_float(v & 0xFFFF0000u); }
__device__ __forceinline__ float bf_round(float x) { return __bfloat162float(__float2bfloat16_rn(x)); }
__device__ __forceinline__ float siluf(float g) { return g * rcpf(1.0f + ex2f(g * -1.4426950408889634f)); }

__device__ __forceinline__ void wgmma_ss_n128_zero(float* d, uint64_t da, uint64_t db) {
    asm volatile("wgmma.mma_async.sync.aligned.m64n128k16.f32.bf16.bf16 {"
        "%0,%1,%2,%3,%4,%5,%6,%7,%8,%9,%10,%11,%12,%13,%14,%15,%16,%17,%18,%19,%20,%21,%22,%23,%24,%25,%26,%27,%28,%29,%30,%31,%32,%33,%34,%35,%36,%37,%38,%39,"
        "%40,%41,%42,%43,%44,%45,%46,%47,%48,%49,%50,%51,%52,%53,%54,%55,%56,%57,%58,%59,%60,%61,%62,%63"
        "}, %64, %65, 0, 1, 1, 0, 1;\n"
        : "=f"(d[0]),"=f"(d[1]),"=f"(d[2]),"=f"(d[3]),"=f"(d[4]),"=f"(d[5]),"=f"(d[6]),"=f"(d[7]),"=f"(d[8]),"=f"(d[9]),"=f"(d[10]),"=f"(d[11]),"=f"(d[12]),
          "=f"(d[13]),"=f"(d[14]),"=f"(d[15]),"=f"(d[16]),"=f"(d[17]),"=f"(d[18]),"=f"(d[19]),"=f"(d[20]),"=f"(d[21]),"=f"(d[22]),"=f"(d[23]),"=f"(d[24]),
          "=f"(d[25]),"=f"(d[26]),"=f"(d[27]),"=f"(d[28]),"=f"(d[29]),"=f"(d[30]),"=f"(d[31]),"=f"(d[32]),"=f"(d[33]),"=f"(d[34]),"=f"(d[35]),"=f"(d[36]),
          "=f"(d[37]),"=f"(d[38]),"=f"(d[39]),"=f"(d[40]),"=f"(d[41]),"=f"(d[42]),"=f"(d[43]),"=f"(d[44]),"=f"(d[45]),"=f"(d[46]),"=f"(d[47]),"=f"(d[48]),
          "=f"(d[49]),"=f"(d[50]),"=f"(d[51]),"=f"(d[52]),"=f"(d[53]),"=f"(d[54]),"=f"(d[55]),"=f"(d[56]),"=f"(d[57]),"=f"(d[58]),"=f"(d[59]),"=f"(d[60]),
          "=f"(d[61]),"=f"(d[62]),"=f"(d[63])
        : "l"(da), "l"(db));
}
__device__ __forceinline__ void wgmma_ss_n128_acc(float* d, uint64_t da, uint64_t db) {
    asm volatile("wgmma.mma_async.sync.aligned.m64n128k16.f32.bf16.bf16 {"
        "%0,%1,%2,%3,%4,%5,%6,%7,%8,%9,%10,%11,%12,%13,%14,%15,%16,%17,%18,%19,%20,%21,%22,%23,%24,%25,%26,%27,%28,%29,%30,%31,%32,%33,%34,%35,%36,%37,%38,%39,"
        "%40,%41,%42,%43,%44,%45,%46,%47,%48,%49,%50,%51,%52,%53,%54,%55,%56,%57,%58,%59,%60,%61,%62,%63"
        "}, %64, %65, 1, 1, 1, 0, 1;\n"
        : "+f"(d[0]),"+f"(d[1]),"+f"(d[2]),"+f"(d[3]),"+f"(d[4]),"+f"(d[5]),"+f"(d[6]),"+f"(d[7]),"+f"(d[8]),"+f"(d[9]),"+f"(d[10]),"+f"(d[11]),"+f"(d[12]),
          "+f"(d[13]),"+f"(d[14]),"+f"(d[15]),"+f"(d[16]),"+f"(d[17]),"+f"(d[18]),"+f"(d[19]),"+f"(d[20]),"+f"(d[21]),"+f"(d[22]),"+f"(d[23]),"+f"(d[24]),
          "+f"(d[25]),"+f"(d[26]),"+f"(d[27]),"+f"(d[28]),"+f"(d[29]),"+f"(d[30]),"+f"(d[31]),"+f"(d[32]),"+f"(d[33]),"+f"(d[34]),"+f"(d[35]),"+f"(d[36]),
          "+f"(d[37]),"+f"(d[38]),"+f"(d[39]),"+f"(d[40]),"+f"(d[41]),"+f"(d[42]),"+f"(d[43]),"+f"(d[44]),"+f"(d[45]),"+f"(d[46]),"+f"(d[47]),"+f"(d[48]),
          "+f"(d[49]),"+f"(d[50]),"+f"(d[51]),"+f"(d[52]),"+f"(d[53]),"+f"(d[54]),"+f"(d[55]),"+f"(d[56]),"+f"(d[57]),"+f"(d[58]),"+f"(d[59]),"+f"(d[60]),
          "+f"(d[61]),"+f"(d[62]),"+f"(d[63])
        : "l"(da), "l"(db));
}
__device__ __forceinline__ void wgmma_ss_n64(float* d, uint64_t da, uint64_t db, int acc) {
    asm volatile("{\n.reg .pred p;\nsetp.ne.b32 p, %34, 0;\nwgmma.mma_async.sync.aligned.m64n64k16.f32.bf16.bf16 {"
        "%0,%1,%2,%3,%4,%5,%6,%7,%8,%9,%10,%11,%12,%13,%14,%15,%16,%17,%18,%19,%20,%21,%22,%23,%24,%25,%26,%27,%28,%29,%30,%31"
        "}, %32, %33, p, 1, 1, 0, 1;\n}\n"
        : "+f"(d[0]),"+f"(d[1]),"+f"(d[2]),"+f"(d[3]),"+f"(d[4]),"+f"(d[5]),"+f"(d[6]),"+f"(d[7]),"+f"(d[8]),"+f"(d[9]),"+f"(d[10]),"+f"(d[11]),"+f"(d[12]),
          "+f"(d[13]),"+f"(d[14]),"+f"(d[15]),"+f"(d[16]),"+f"(d[17]),"+f"(d[18]),"+f"(d[19]),"+f"(d[20]),"+f"(d[21]),"+f"(d[22]),"+f"(d[23]),"+f"(d[24]),
          "+f"(d[25]),"+f"(d[26]),"+f"(d[27]),"+f"(d[28]),"+f"(d[29]),"+f"(d[30]),"+f"(d[31])
        : "l"(da), "l"(db), "r"(acc));
}
__device__ __forceinline__ void wgmma_rs_n64_zero(float* d, const uint32_t* a, uint64_t db) {
    asm volatile("wgmma.mma_async.sync.aligned.m64n64k16.f32.bf16.bf16 {"
        "%0,%1,%2,%3,%4,%5,%6,%7,%8,%9,%10,%11,%12,%13,%14,%15,%16,%17,%18,%19,%20,%21,%22,%23,%24,%25,%26,%27,%28,%29,%30,%31"
        "}, {%32,%33,%34,%35}, %36, 0, 1, 1, 0;\n"
        : "=f"(d[0]),"=f"(d[1]),"=f"(d[2]),"=f"(d[3]),"=f"(d[4]),"=f"(d[5]),"=f"(d[6]),"=f"(d[7]),"=f"(d[8]),"=f"(d[9]),"=f"(d[10]),"=f"(d[11]),"=f"(d[12]),
          "=f"(d[13]),"=f"(d[14]),"=f"(d[15]),"=f"(d[16]),"=f"(d[17]),"=f"(d[18]),"=f"(d[19]),"=f"(d[20]),"=f"(d[21]),"=f"(d[22]),"=f"(d[23]),"=f"(d[24]),
          "=f"(d[25]),"=f"(d[26]),"=f"(d[27]),"=f"(d[28]),"=f"(d[29]),"=f"(d[30]),"=f"(d[31])
        : "r"(a[0]), "r"(a[1]), "r"(a[2]), "r"(a[3]), "l"(db));
}
__device__ __forceinline__ void wgmma_rs_n64_acc(float* d, const uint32_t* a, uint64_t db) {
    asm volatile("wgmma.mma_async.sync.aligned.m64n64k16.f32.bf16.bf16 {"
        "%0,%1,%2,%3,%4,%5,%6,%7,%8,%9,%10,%11,%12,%13,%14,%15,%16,%17,%18,%19,%20,%21,%22,%23,%24,%25,%26,%27,%28,%29,%30,%31"
        "}, {%32,%33,%34,%35}, %36, 1, 1, 1, 0;\n"
        : "+f"(d[0]),"+f"(d[1]),"+f"(d[2]),"+f"(d[3]),"+f"(d[4]),"+f"(d[5]),"+f"(d[6]),"+f"(d[7]),"+f"(d[8]),"+f"(d[9]),"+f"(d[10]),"+f"(d[11]),"+f"(d[12]),
          "+f"(d[13]),"+f"(d[14]),"+f"(d[15]),"+f"(d[16]),"+f"(d[17]),"+f"(d[18]),"+f"(d[19]),"+f"(d[20]),"+f"(d[21]),"+f"(d[22]),"+f"(d[23]),"+f"(d[24]),
          "+f"(d[25]),"+f"(d[26]),"+f"(d[27]),"+f"(d[28]),"+f"(d[29]),"+f"(d[30]),"+f"(d[31])
        : "r"(a[0]), "r"(a[1]), "r"(a[2]), "r"(a[3]), "l"(db));
}
__device__ __forceinline__ void wgmma_rs_n24_acc(float* d, const uint32_t* a, uint64_t db) {
    asm volatile("wgmma.mma_async.sync.aligned.m64n24k16.f32.bf16.bf16 {"
        "%0,%1,%2,%3,%4,%5,%6,%7,%8,%9,%10,%11"
        "}, {%12,%13,%14,%15}, %16, 1, 1, 1, 1;\n"
        : "+f"(d[0]),"+f"(d[1]),"+f"(d[2]),"+f"(d[3]),"+f"(d[4]),"+f"(d[5]),"+f"(d[6]),"+f"(d[7]),"+f"(d[8]),"+f"(d[9]),"+f"(d[10]),"+f"(d[11])
        : "r"(a[0]), "r"(a[1]), "r"(a[2]), "r"(a[3]), "l"(db));
}

constexpr int OFF_ONES = 131072;
constexpr int OFF_RING = OFF_ONES + 4096;
constexpr int NRING = 5;
constexpr int OFF_B2 = OFF_RING + NRING * 16384;
constexpr int OFF_CS = OFF_B2 + 2048;
constexpr int OFF_RS = OFF_CS + 2560;
constexpr int OFF_BAR = OFF_RS + 1024;
enum { B_FULL = 0, B_EMPTY = 40,
       B_TILE = 80, B_OW = 85, B_DONE = 87,
       B_O2 = 90, B_QKV = 98,
       B_KV = 100, B_WO = 108, B_T1 = 109, B_STATS = 110, B_RING = 115, B_O = 118,
       B_NUM = 120 };
constexpr int OFF_TS = OFF_BAR + 1024;
constexpr int SMEM_BYTES = OFF_BAR + B_NUM * 8;
constexpr unsigned FIXED_MASK = 0xB5;
constexpr float P71 = 2361183241434822606848.0f, M71 = 4.235164736271502e-22f;

__device__ __forceinline__ uint32_t exp2_fixed(float lo, float hi, uint32_t half2) {
    uint32_t y, g, d;
    asm("cvt.pack.sat.s16.s32 %0, %1, %2;" : "=r"(y) : "r"(__float_as_uint(hi)), "r"(__float_as_uint(lo)));
    asm("lop3.b32 %0, %1, 0x007F007F, %2, 0xEA;" : "=r"(g) : "r"(y), "r"(half2));
    asm("fma.rn.bf16x2 %0, %1, %2, %3;" : "=r"(d) : "r"(y), "r"(g), "r"(y & 0xFF80FF80u));
    return d;
}
constexpr uint64_t DK_STEP = 512 - (256ull << 16), DV_STEP = 512 - (256ull << 32);
constexpr uint32_t POS_LAST = 0x37521640u;
#define POLL_NS 50
#define ORD_LAG 2

__global__ void __cluster_dims__(2, 1, 1) __launch_bounds__(640, 1)
mega_kernel(const __nv_bfloat16* __restrict__ x, const __nv_bfloat16* __restrict__ wqkv, const __nv_bfloat16* __restrict__ w1,
            const __nv_bfloat16* __restrict__ w3, __nv_bfloat16* __restrict__ out,
            const __grid_constant__ CUtensorMap mx, const __grid_constant__ CUtensorMap mqkv, const __grid_constant__ CUtensorMap mw1,
            const __grid_constant__ CUtensorMap mw3, const __grid_constant__ CUtensorMap mw2, const __grid_constant__ CUtensorMap mwo,
            uint32_t half2) {
    extern __shared__ __align__(1024) uint8_t smem_raw[];
    const uint32_t sb = __shfl_sync(0xffffffffu, smem_u32(smem_raw), 0);
    if ((sb & 0xFFFFFF) != SMEM_BASE) __trap();
    const uint32_t bars = sb + OFF_BAR, ring = sb + OFF_RING;
    const int tid = threadIdx.x, lane = tid & 31, g = lane >> 2, t4 = lane & 3;
    const int warp = __shfl_sync(0xffffffffu, tid >> 5, 0), wg = warp >> 2, wq = warp & 3;
    const int rank = blockIdx.x & 1, cl = blockIdx.x >> 1;
    const int grp = cl < 4 ? 4 + cl : cl < 36 ? (cl - 4) >> 3 : 4 + (cl - 36) / 7;
    const int rot = cl < 4 ? 7 : cl < 36 ? (cl - 4) & 7 : (cl - 36) % 7;
    const int mblk = rot * 2 + rank;
    const int nq = grp < 4 ? 2 : 1;
    const int qt0 = grp < 4 ? 2 * grp : 4 + grp;
    const int gu0 = (grp < 4 ? 3 * grp : 4 * grp - 4) - nq;
    const int head = blockIdx.x >> 2, qb = blockIdx.x & 3;
    const int cb = blockIdx.x & 7, rb0 = (blockIdx.x >> 5) * 8 + ((blockIdx.x >> 3) & 3);

    if (elect_one()) {
        const uint32_t b0 = bars + (warp < 16 ? warp * 40 : warp * 80 - 640), cnt = warp < 8 || warp > 17 ? 1 : warp == 17 ? 2 : 8;
#pragma unroll
        for (int i = 0; i < 5; i++) mbar_init(b0 + 8 * i, cnt);
        if (warp == 0) {
            fence_async_smem();
#pragma unroll
            for (int j = 0; j < 2; j++) {
                tma2d(sb + j * 16384, &mx, j * 64, mblk * 128, bars + 8 * (B_FULL + j));
                tma2d(ring + j * 16384, &mqkv, qt0 * 128, j * 64, bars + 8 * (B_FULL + j));
                tma2d(ring + j * 16384 + 8192, &mqkv, qt0 * 128 + 64, j * 64, bars + 8 * (B_FULL + j));
            }
        }
        if (warp < 8) {
#pragma unroll
            for (int i = 0; i < 5; i++) mbar_expect(b0 + 8 * i, warp * 5 + i < 8 ? 32768 : 16384);
        } else if (warp >= 16) {
#pragma unroll
            for (int i = 5; i < 10; i++) mbar_init(b0 + 8 * i, cnt);
            if (warp == 16) asm volatile("prefetch.tensormap [%0];" :: "l"(rank ? &mw3 : &mw1) : "memory");
        }
        asm volatile("fence.mbarrier_init.release.cluster;" ::: "memory");
    }
    __syncthreads();
    if (tid == 512) TSTAMP(26);
    asm volatile("barrier.cluster.arrive.relaxed.aligned;" ::: "memory");

    if (wg < 4) {
        const int pair = wg >> 1, half = wg & 1;
        if (pair == 1) {
            const int row = mblk * 128 + grp * 16 + (warp - 8) * 2 + (lane >> 4);
            uint4 v[6];
            const uint32_t* w = reinterpret_cast<const uint32_t*>(v);
#pragma unroll
            for (int j = 0; j < 2; j++) v[4 + j] = __ldg(reinterpret_cast<const uint4*>(wqkv + (size_t)(rot * 64 + (warp - 8) * 8 + j * 4 + (lane >> 3)) * (3 * DM) + qt0 * 128 + rank * 64) + (lane & 7));
#pragma unroll
            for (int j = 0; j < 4; j++) v[j] = __ldg(reinterpret_cast<const uint4*>(x + (size_t)row * DM) + j * 16 + (lane & 15));
            const uint32_t tag = ld_epoch() + 1;
            float c[8];
#pragma unroll
            for (int e = 0; e < 4; e++) { c[2 * e] = bf_lo(w[16 + e]) + bf_lo(w[20 + e]); c[2 * e + 1] = bf_hi(w[16 + e]) + bf_hi(w[20 + e]); }
#pragma unroll
            for (int n = 4; n > 1; n >>= 1) {
                const bool up = lane & (4 * n);
#pragma unroll
                for (int e = 0; e < n; e++) c[e] = (up ? c[e + n] : c[e]) + __shfl_xor_sync(0xffffffffu, up ? c[e] : c[e + n], 4 * n);
            }
            asm volatile("st.shared.v2.f32 [%0], {%1,%2};" :: "r"(sb + OFF_CS + 512 + (warp - 8) * 256 + (lane & 7) * 32 + (lane >> 3) * 8), "f"(c[0]), "f"(c[1]) : "memory");
            bar_sync(6, 256);
            if (warp < 10) {
#pragma unroll
                for (int e = 0; e < 8; e++) asm volatile("ld.shared.f32 %0, [%1];" : "=f"(c[e]) : "r"(sb + OFF_CS + 512 + e * 256 + (tid & 63) * 4));
                st_tagged(reinterpret_cast<unsigned long long*>(g_cs) + (grp * 40 + rot) * 128 + rank * 64 + (tid & 63),
                          __float_as_uint(((c[0] + c[1]) + (c[2] + c[3])) + ((c[4] + c[5]) + (c[6] + c[7]))), tag);
                if (tid == 256) TSTAMP(40);
            }
            float sa[4] = {0.f, 0.f, 0.f, 0.f}, sq[4] = {0.f, 0.f, 0.f, 0.f};
#pragma unroll
            for (int j = 0; j < 16; j++) sa[j & 3] += bf_lo(w[j]) + bf_hi(w[j]);
            float mean = ((sa[0] + sa[1]) + (sa[2] + sa[3])) * (1.0f / 32);
#pragma unroll
            for (int j = 0; j < 16; j++) { const float a = bf_lo(w[j]) - mean, b = bf_hi(w[j]) - mean; sq[j & 1] = fmaf(a, a, sq[j & 1]); sq[2 + (j & 1)] = fmaf(b, b, sq[2 + (j & 1)]); }
            float m2 = (sq[0] + sq[1]) + (sq[2] + sq[3]);
#pragma unroll
            for (int d = 1; d < 16; d <<= 1) {
                const float om = __shfl_xor_sync(0xffffffffu, mean, d), o2 = __shfl_xor_sync(0xffffffffu, m2, d), dm = mean - om;
                m2 = fmaf(dm * dm, 16.0f * d, m2 + o2); mean = 0.5f * (mean + om);
            }
            float sd;
            asm("sqrt.approx.f32 %0, %1;" : "=f"(sd) : "f"(bf_round(bf_round(m2 * (1.0f / DM)) + 1e-5f)));
            if ((lane & 15) == 0) st_tagged(reinterpret_cast<unsigned long long*>(g_rs) + row, pack_bf16(mean, sd), tag);
            if (tid == 256) TSTAMP(45);
        }

        uint32_t q[4], qn[4];
        {
            const int rowblk = mblk * 2 + half, tile16 = rowblk * 4 + wq;
            uint32_t empty;
            asm("mapa.shared::cluster.u32 %0, %1, %2;" : "=r"(empty) : "r"(bars + 8 * B_EMPTY), "r"(wq & 1));
#pragma unroll 1
            for (int t = pair; t < 5; t += 2) {
                float acc[64];
                uint32_t full = bars + 8 * (B_FULL + 8 * t), rel = empty + 64 * t;
                uint32_t stepa = t == 4 ? 0x4AB93AC : 0x9999999, stepb = (uint32_t)(0x994999949999ull >> (4 * ((0x24130u >> (4 * t)) & 7)));
                uint64_t da = mkdesc(half * 8192, 16, 1024, 1), db = mkdesc(OFF_RING, 8192, 1024, 1) + ((0x24130u >> (4 * t)) & 7) * 1024;
                if (tid == 0 && t == 0) TSTAMP(30);
                mbar_wait(full, 0);
                if (t > 0) mbar_wait(full + 8 * (B_EMPTY - ORD_LAG), 0);
                wg_fence();
                wgmma_ss_n128_zero(acc, da, db);
#pragma unroll
                for (int k = 1; k < 4; k++) wgmma_ss_n128_acc(acc, da + k * 2, db + k * 128);
                wg_commit();
                mbar_wait(full + 8, 0);
#pragma unroll 1
                do {
                    da += (int)((stepa & 15) << 10) - 8192; db += (int)((stepb & 15) << 10) - 8192;
                    stepa >>= 4; stepb >>= 4;
                    wg_fence();
#pragma unroll
                    for (int k = 0; k < 4; k++) wgmma_ss_n128_acc(acc, da + k * 2, db + k * 128);
                    wg_commit();
                    mbar_wait(full + 16, 0);
                    wg_wait<1>();
                    if (elect_one()) mbar_arrive_remote(rel);
                    full += 8; rel += 8;
                } while (stepa);
                if (t >= 3) {
                    mbar_wait(bars + 8 * B_QKV, 0);
                    const uint4* pq = g_q + (head * 128 + (qb * 8 + wg) * 4 + wq) * 32 + lane;
                    const uint4 v = __ldcg(pq), u = __ldcg(pq + 512);
                    q[0] = v.x; q[1] = v.y; q[2] = v.z; q[3] = v.w; qn[0] = u.x; qn[1] = u.y; qn[2] = u.z; qn[3] = u.w;
                }
                wg_wait<0>();
                if (elect_one()) mbar_arrive_remote(rel);
                pin<64>(acc);
                if (wq == 0 && half == 0 && lane == 0) TSTAMP(2 + 2 * t);
                mbar_wait(bars + 8 * (B_STATS + t), 0);
                uint32_t rs0, rs1;
                asm volatile("ld.shared.b32 %0, [%1];" : "=r"(rs0) : "r"(sb + OFF_RS + (half * 64 + wq * 16 + g) * 4));
                asm volatile("ld.shared.b32 %0, [%1];" : "=r"(rs1) : "r"(sb + OFF_RS + (half * 64 + wq * 16 + g + 8) * 4));
                const float m0 = bf_lo(rs0), m1 = bf_lo(rs1);
                float d0 = bf_hi(rs0), d1 = bf_hi(rs1);
#pragma unroll
                for (int j = 0; j < 16; j++) {
                    float c0, c1;
                    asm volatile("ld.shared.v2.f32 {%0,%1}, [%2];" : "=f"(c0), "=f"(c1) : "r"(sb + OFF_CS + (t * 128 + j * 8 + t4 * 2) * 4));
                    acc[4 * j] = fmaf(-m0, c0, acc[4 * j]); acc[4 * j + 1] = fmaf(-m0, c1, acc[4 * j + 1]);
                    acc[4 * j + 2] = fmaf(-m1, c0, acc[4 * j + 2]); acc[4 * j + 3] = fmaf(-m1, c1, acc[4 * j + 3]);
                }
                float r0 = rcpf(d0), r1 = rcpf(d1);
                if (t < nq) {
                    const int qt = qt0 + t;
                    if (qt < 4) {
                        r0 *= 0.25f * 1.4426950408889634f * M71; r1 *= 0.25f * 1.4426950408889634f * M71;
                    } else if (qt < 8) {
                        r0 *= ((FIXED_MASK >> (2 * wq)) & 1) ? M71 : P71; r1 *= ((FIXED_MASK >> (2 * wq + 1)) & 1) ? M71 : P71;
                    }
                    uint32_t e[32];
#pragma unroll
                    for (int i = 0; i < 32; i++) { const float r = (i & 1) ? r1 : r0; e[i] = pack_bf16(acc[2 * i] * r, acc[2 * i + 1] * r); }
                    if (qt < 4) {
                        uint4* p = g_q + (qt * 1024 + tile16) * 32 + lane;
#pragma unroll
                        for (int hh = 0; hh < 8; hh++) p[hh * 4096] = make_uint4(e[4 * hh], e[4 * hh + 1], e[4 * hh + 2], e[4 * hh + 3]);
                    } else {
                        uint32_t* p = reinterpret_cast<uint32_t*>(g_kv + (qt - 4) * 32768) + tile16 * 64 + lane;
#pragma unroll
                        for (int i = 0; i < 32; i++) p[(i >> 1) * 8192 + (i & 1) * 32] = e[i];
                    }
                } else {
                    uint32_t* p = reinterpret_cast<uint32_t*>(g_h + (rowblk * 28 + gu0 + t) * 512) + wq * 512 + lane;
                    r0 *= -1.4426950408889634f; r1 *= -1.4426950408889634f; d0 *= d0; d1 *= d1;
#pragma unroll
                    for (int j = 0; j < 8; j++) {
                        const float* a = acc + j * 4; const float* b = a + 32;
                        p[j * 32] = pack_bf16(a[0] * b[0] * rcpf(fmaf(ex2f(a[0] * r0), d0, d0)), a[1] * b[1] * rcpf(fmaf(ex2f(a[1] * r0), d0, d0)));
                        p[256 + j * 32] = pack_bf16(a[2] * b[2] * rcpf(fmaf(ex2f(a[2] * r1), d1, d1)), a[3] * b[3] * rcpf(fmaf(ex2f(a[3] * r1), d1, d1)));
                    }
                }
                __syncwarp();
                if (elect_one()) mbar_arrive(bars + 8 * (B_TILE + t));
                if (wq == 0 && half == 0 && lane == 0) TSTAMP(3 + 2 * t);
            }
        }
        const uint64_t db2 = mkdesc(OFF_B2, 128, 256, 0);
        uint32_t q2[4];
        q2[2] = __shfl_sync(0xffffffffu, lane, 0); q2[3] = __shfl_sync(0xffffffffu, lane ^ 1, 1);
        int nref = 1;
        mbar_wait(bars + 8 * B_KV, 0);
#pragma unroll 1
        for (int round = 0; round < 2;) {
            float s[32];
            {
                float m0 = -INFINITY, m1 = -INFINITY, f0 = -INFINITY, f1 = -INFINITY;
                int t = 0;
#pragma unroll 1
                do {
                    wg_fence();
                    wgmma_rs_n64_zero(s, q, mkdesc(4096, 94208, 128, 0) + (t >> 2) * DK_STEP + (t & 3) * 64);
                    wg_commit();
                    wg_wait<0>();
                    pin<32>(s);
#pragma unroll
                    for (int i = 0; i < 8; i++) {
                        if ((FIXED_MASK >> i) & 1) { f0 = fmaxf(f0, fmaxf(s[4 * i], s[4 * i + 1])); f1 = fmaxf(f1, fmaxf(s[4 * i + 2], s[4 * i + 3])); }
                        else                       { m0 = fmaxf(m0, fmaxf(s[4 * i], s[4 * i + 1])); m1 = fmaxf(m1, fmaxf(s[4 * i + 2], s[4 * i + 3])); }
                    }
                } while (++t < nref);
                m0 = fmaxf(m0, f0 * P71 * P71); m1 = fmaxf(m1, f1 * P71 * P71);
                m0 = fmaxf(m0, __shfl_xor_sync(0xffffffffu, m0, 1)); m1 = fmaxf(m1, __shfl_xor_sync(0xffffffffu, m1, 1));
                m0 = fmaxf(m0, __shfl_xor_sync(0xffffffffu, m0, 2)); m1 = fmaxf(m1, __shfl_xor_sync(0xffffffffu, m1, 2));
#pragma unroll
                for (int r = 0; r < 2; r++) {
                    const float m = __fsub_rn(12582912.f, __fadd_rn(r ? m1 : m0, 12582912.f)) * M71;
                    const float r1 = m - bf_hi(__float_as_uint(m)), r2 = r1 - bf_hi(__float_as_uint(r1));
                    const float lo = t4 == 0 ? m : t4 == 1 ? r2 : t4 == 2 ? M71 : 0.f, hi = t4 == 0 ? r1 : t4 == 1 ? M71 : 0.f;
                    q2[r] = __byte_perm(__float_as_uint(lo), __float_as_uint(hi), 0x7632);
                }
            }
            float o[12]; uint32_t p[16];
#pragma unroll
            for (int i = 0; i < 12; i++) o[i] = 0.f;
            pin<12>(o); pin<4>(q2);
            if (wq == 0 && half == 0 && lane == 0) TSTAMP(12 + 4 * round + pair);
            uint64_t dk = mkdesc(4096, 94208, 128, 0), dv = mkdesc(0, 128, 65536, 0);
#pragma unroll 1
            for (int c = 0; c < 8; c++, dk += DK_STEP, dv += DV_STEP) {
                if (round == 0) mbar_wait(bars + 8 * (B_KV + c), 0);
#pragma unroll
                for (int t = 0; t < 4; t++) {
                    wg_fence();
                    wgmma_rs_n64_zero(s, q, dk + t * 64);
                    wgmma_rs_n64_acc(s, q2, db2);
                    wg_commit();
                    wg_wait<0>();
                    pin<32>(s); pin<16>(p);
#pragma unroll
                    for (int i = 0; i < 16; i++) {
                        if ((FIXED_MASK >> (i >> 1)) & 1) p[i] = exp2_fixed(s[2 * i], s[2 * i + 1], half2);
                        else                              p[i] = pack_bf16(ex2f(s[2 * i]), ex2f(s[2 * i + 1]));
                    }
                    wg_fence();
#pragma unroll
                    for (int k = 0; k < 4; k++) wgmma_rs_n24_acc(o, p + 4 * k, dv + (t * 4 + k) * 16);
                    wg_commit();
                }
            }
            wg_wait<0>();
            pin<12>(o);
            if (nref != 32) {
                float chk = (o[8] + o[10]) * 256.f;
#pragma unroll
                for (int i = 0; i < 8; i++) chk += fabsf(o[i]);
                uint32_t bad;
                asm volatile("{\n.reg .pred p, q;\nsetp.geu.f32 q, %1, 0f7F800000;\nbar.red.or.pred p, %2, 128, q;\nselp.u32 %0, 1, 0, p;\n}" : "=r"(bad) : "f"(chk), "r"(1 + wg) : "memory");
                if (__any_sync(0xffffffffu, bad)) { nref = 32; continue; }
            }
            const int rowblk = qb * 8 + round * 4 + wg;
            const float r0 = rcpf(o[8]), r1 = rcpf(o[10]);
            uint32_t* po = reinterpret_cast<uint32_t*>(g_o + (rowblk * 8 + (head >> 2)) * 512) + wq * 512 + (head & 3) * 64 + lane;
            st_relaxed(po, pack_bf16(o[0] * r0, o[1] * r0)); st_relaxed(po + 256, pack_bf16(o[2] * r1, o[3] * r1));
            st_relaxed(po + 32, pack_bf16(o[4] * r0, o[5] * r0)); st_relaxed(po + 288, pack_bf16(o[6] * r1, o[7] * r1));
            if (round == 0) {
                po += 4 * 8 * 2048;
                st_relaxed(po, ~0u); st_relaxed(po + 256, ~0u); st_relaxed(po + 32, ~0u); st_relaxed(po + 288, ~0u);
            }
            __syncwarp();
            if (elect_one()) mbar_arrive(bars + 8 * (B_OW + 2 * round + pair));
#pragma unroll
            for (int i = 0; i < 4; i++) q[i] = qn[i];
            nref = 1;
            if (wq == 0 && half == 0 && lane == 0) TSTAMP(14 + 4 * round + pair);
            round++;
        }
        mbar_wait(bars + 8 * B_T1, 0);
        uint4 v[8];
#pragma unroll 1
        for (int n = 0; n < 2000000; n++) {
            uint32_t mx = 0;
#pragma unroll
            for (int i = 0; i < 8; i++) {
                asm volatile("ld.relaxed.gpu.global.v4.u32 {%0,%1,%2,%3}, [%4];" : "=r"(v[i].x), "=r"(v[i].y), "=r"(v[i].z), "=r"(v[i].w)
                             : "l"(g_o + (rb0 + 4) * 4096 + warp * 256 + i * 32 + lane) : "memory");
            }
#pragma unroll
            for (int i = 0; i < 8; i++) mx = __vimax3_u32(__vimax3_u32(mx, v[i].x, v[i].y), v[i].z, v[i].w);
            if (__all_sync(0xffffffffu, mx != ~0u)) break;
            __nanosleep(POLL_NS);
        }
        mbar_wait(bars + 8 * B_DONE, 0); mbar_wait(bars + 8 * (B_DONE + 1), 0);
#pragma unroll
        for (int i = 0; i < 8; i++)
            asm volatile("st.shared.v4.b32 [%0], {%1,%2,%3,%4};" :: "r"(sb + warp * 4096 + i * 512 + lane * 16), "r"(v[i].x), "r"(v[i].y), "r"(v[i].z), "r"(v[i].w) : "memory");
        fence_async_smem();
        __syncwarp();
        if (elect_one()) mbar_arrive(bars + 8 * (B_O2 + (warp >> 1)));
        if (tid == 0) TSTAMP(24);
    } else {
        uint32_t tag;
        if (wq == 0) {
            asm volatile("barrier.cluster.wait.aligned;" ::: "memory");
            if (tid == 512) TSTAMP(27);
            uint32_t slot = 2;
#pragma unroll 1
            for (int n = 2; n < 40; n++) {
                const int t = n >> 3, j = n & 7;
                const int kc = (n < 32 ? j : (POS_LAST >> (4 * j)) & 7) * 64;
                const CUtensorMap* m = t < nq ? &mqkv : rank ? &mw3 : &mw1;
                const int col = t < nq ? (qt0 + t) * 128 + rank * 64 : (gu0 + t) * 64;
                const uint32_t dst = ring + slot * 16384 + rank * 8192, fb = bars + 8 * (B_FULL + n);
                if (n < 8 && elect_one()) tma2d(sb + n * 16384, &mx, kc, mblk * 128, fb);
                if (n >= NRING) mbar_wait(fb + 8 * (B_EMPTY - NRING), 0);
                if (elect_one()) { TS2(0, n); tma2d_mc(dst, m, col, kc, fb); }
                if (++slot == NRING) slot = 0;
            }
            tag = ld_epoch() + 1;
        } else if (wq == 1) {
            tag = ld_epoch() + 1;
            mbar_wait(bars + 8 * (B_FULL + 5), 0);
#pragma unroll 1
            for (int t = 0; t < 5; t++) {
                float a[4];
#pragma unroll 1
                for (int n = 0; n < 2000000; n++) {
                    uint32_t stale = 0;
                    a[0] = a[1] = a[2] = a[3] = 0.f;
#pragma unroll
                    for (int i = 0; i < 16; i++) {
                        uint32_t u, v;
                        stale |= ld_tagged2(g_cs + (grp * 5 + t) * 512 + i * 32 + lane, tag, u, v);
                        a[(i & 1) * 2] += __uint_as_float(u); a[(i & 1) * 2 + 1] += __uint_as_float(v);
                    }
                    if (__all_sync(0xffffffffu, stale == 0)) break;
                    if (t) __nanosleep(400);
                }
                asm volatile("st.shared.v2.f32 [%0], {%1,%2};" :: "r"(sb + OFF_CS + t * 512 + lane * 8), "f"(a[0]), "f"(a[1]) : "memory");
                asm volatile("st.shared.v2.f32 [%0], {%1,%2};" :: "r"(sb + OFF_CS + t * 512 + 256 + lane * 8), "f"(a[2]), "f"(a[3]) : "memory");
                if (t == 0) {
                    uint32_t r[4];
#pragma unroll 1
                    for (int n = 0; n < 2000000; n++) {
                        const uint32_t stale = ld_tagged2(g_rs + mblk * 64 + lane * 2, tag, r[0], r[1]) | ld_tagged2(g_rs + mblk * 64 + lane * 2 + 1, tag, r[2], r[3]);
                        if (__all_sync(0xffffffffu, stale == 0)) break;
                    }
                    asm volatile("st.shared.v4.b32 [%0], {%1,%2,%3,%4};" :: "r"(sb + OFF_RS + lane * 16), "r"(r[0]), "r"(r[1]), "r"(r[2]), "r"(r[3]) : "memory");
                }
                __syncwarp();
                if (elect_one()) { mbar_arrive(bars + 8 * (B_STATS + t)); TSTAMP(32 + t); }
            }
        } else {
            tag = ld_epoch() + 1;
            mbar_wait(bars + 8 * (B_FULL + wq - 1), 0);
#pragma unroll 1
            for (int t = wq - 1; t < 5; t += 2) {
                const __nv_bfloat16* src; int ld;
                if (t < nq) { src = wqkv + (qt0 + t) * 128 + rank * 64; ld = 3 * DM; }
                else        { src = (rank ? w3 : w1) + (gu0 + t) * 64; ld = FF; }
                src += (size_t)(rot * 64 + (lane >> 3)) * ld + (lane & 7) * 8;
                uint4 v[16];
                const uint32_t* w = reinterpret_cast<const uint32_t*>(v);
#pragma unroll
                for (int j = 0; j < 16; j++) v[j] = __ldg(reinterpret_cast<const uint4*>(src + (size_t)j * 4 * ld));
                float c[8];
#pragma unroll
                for (int e = 0; e < 4; e++) {
                    float a = 0.f, b = 0.f;
#pragma unroll
                    for (int j = 0; j < 16; j++) { a += bf_lo(w[4 * j + e]); b += bf_hi(w[4 * j + e]); }
                    c[2 * e] = a; c[2 * e + 1] = b;
                }
#pragma unroll
                for (int n = 4; n > 1; n >>= 1) {
                    const bool up = lane & (4 * n);
#pragma unroll
                    for (int e = 0; e < n; e++) c[e] = (up ? c[e + n] : c[e]) + __shfl_xor_sync(0xffffffffu, up ? c[e] : c[e + n], 4 * n);
                }
                unsigned long long* dst = reinterpret_cast<unsigned long long*>(g_cs) + ((grp * 5 + t) * 8 + rot) * 128 + rank * 64 + (lane & 7) * 8 + (lane >> 3) * 2;
                st_tagged(dst, __float_as_uint(c[0]), tag); st_tagged(dst + 1, __float_as_uint(c[1]), tag);
                if (lane == 0) TSTAMP(40 + t);
            }
        }
        if (wq == 3) {
#pragma unroll 1
            for (int i = lane; i < 256; i += 32) asm volatile("st.shared.v4.b32 [%0], {%1,%1,%1,%1};" :: "r"(sb + OFF_ONES + i * 16), "r"(0x3F803F80u) : "memory");
#pragma unroll 1
            for (int i = lane; i < 128; i += 32) {
                const bool fx = (FIXED_MASK >> (i >> 4)) & 1;
                uint32_t a = fx ? pack_bf16(M71, M71) : pack_bf16(P71, P71);
                uint32_t b = fx ? pack_bf16(M71, 47.0f * M71) : pack_bf16(P71, -79.5f * P71);
                uint32_t c = fx ? 0u : pack_bf16(0.08214f * P71, 0.f);
                if (i & 8) a = b = c = 0;
                asm volatile("st.shared.v4.b32 [%0], {%1,%2,%3,%4};" :: "r"(sb + OFF_B2 + i * 16), "r"(a), "r"(b), "r"(c), "r"(0) : "memory");
            }
            fence_async_smem();
            __syncwarp();
            if (elect_one()) mbar_arrive(bars + 8 * B_QKV);
        } else if (wq == 1) {
#pragma unroll 1
            for (int i = 0; i < 3; i++) wait_cnt(C_QKV + i * 4 + (head >> 3), 16 * tag, 100);
            fence_async_all();
            if (elect_one()) { mbar_arrive(bars + 8 * B_QKV); TSTAMP(29); }
            mbar_wait(bars + 8 * (B_EMPTY + 31), 0);
            const uint8_t* gk = reinterpret_cast<const uint8_t*>(g_kv + head * 4096);
            const uint8_t* gv = reinterpret_cast<const uint8_t*>(g_kv + (32 + head) * 4096);
#pragma unroll 1
            for (int c = 0; c < 8; c++) {
                mbar_wait(bars + 8 * (B_EMPTY + 34 + (c & 4) + ((c >> 1) & 1)), 0);
                if (elect_one()) {
                    const uint32_t b = bars + 8 * (B_KV + c);
                    mbar_expect(b, 16384);
                    bulk_load(sb + (2 * c + 1) * 4096, gk + c * 4096, 4096, b);
                    bulk_load(sb + 2 * c * 4096, gv + c * 4096, 4096, b);
                    bulk_load(sb + 65536 + c * 4096, gv + 32768 + c * 4096, 4096, b);
                    bulk_load(sb + 98304 + c * 4096, gk + 32768 + c * 4096, 4096, b);
                }
            }
        } else if (wq == 2) {
#pragma unroll 1
            for (int t = 0; t < 5; t++) {
                mbar_wait(bars + 8 * (B_TILE + t), 0);
                if (elect_one()) signal_cnt(t < nq ? C_QKV + qt0 + t : C_H + mblk);
            }
        }
        pin<1>(&tag);
        bar_sync(5, 128);
        if (tid == 639) g_epoch[blockIdx.x] = tag;
        uint32_t gate[2][16];
        {
            float dn[64];
            auto load_stage = [&](int kb, int st) {
                const uint32_t b = bars + 8 * (B_RING + st), dst = ring + st * 24576;
                mbar_expect(b, 24576);
                bulk_load(dst, g_h + (rb0 * 28 + kb) * 512, 8192, b);
                bulk_load(dst + 8192, g_h + ((rb0 + 4) * 28 + kb) * 512, 8192, b);
                tma2d(dst + 16384, &mw2, cb * 64, kb * 64, b);
            };
            if (wq == 0) {
                wait_cnt(C_H + (rb0 >> 1), 28 * tag, 200);
                wait_cnt(C_H + (rb0 >> 1) + 2, 28 * tag, 200);
                if (elect_one()) { TSTAMP(20); fence_async_all(); load_stage(0, 0); load_stage(1, 1); }
            }
            int st = 0; uint32_t ph = 0;
#pragma unroll 1
            for (int kb = 0; kb < 28; kb++) {
                mbar_wait(bars + 8 * (B_RING + st), ph);
                const uint64_t da = mkdesc(OFF_RING + st * 24576, 128, 1024, 0), db = mkdesc(OFF_RING + st * 24576 + 16384, 8192, 1024, 1);
                wg_fence();
#pragma unroll
                for (int k = 0; k < 4; k++) { wgmma_ss_n64(dn, da + k * 16, db + k * 128, (kb | k) != 0); wgmma_ss_n64(dn + 32, da + 512 + k * 16, db + k * 128, (kb | k) != 0); }
                wg_commit();
                wg_wait<1>();
                if (wq == 0 && kb < 26 && elect_one()) load_stage(kb + 2, st == 0 ? 2 : st - 1);
                if (++st == 3) { st = 0; ph ^= 1; }
            }
            wg_wait<0>();
            pin<64>(dn);
#pragma unroll
            for (int i = 0; i < 32; i++) gate[i >> 4][i & 15] = pack_bf16(siluf(dn[2 * i]), siluf(dn[2 * i + 1]));
        }
        if (tid == 512) TSTAMP(21);
        const uint32_t bar_wo = bars + 8 * B_WO;
        if (wq == 0 && elect_one()) {
            mbar_expect(bar_wo, 65536);
#pragma unroll 1
            for (int i = 0; i < 8; i++) tma2d(ring + i * 8192, &mwo, cb * 64, i * 64, bar_wo);
        }
        if (wq >= 2) {
            mbar_wait(bars + 8 * (B_OW + wq - 2), 0);
            if (elect_one()) {
                signal_cnt(C_O + qb * 8 + 2 * wq - 4);
                asm volatile("red.relaxed.gpu.global.add.u32 [%0], 1;" :: "l"(g_cnt + (C_O + qb * 8 + 2 * wq - 3) * 8) : "memory");
            }
        }
#pragma unroll 1
        for (int tl = 0; tl < 2; tl++) {
            const int rb = rb0 + 4 * tl;
            uint32_t xr[16];
            const uint32_t* px = reinterpret_cast<const uint32_t*>(x + (size_t)(rb * 64 + wq * 16 + g) * DM + cb * 64) + t4;
#pragma unroll
            for (int j = 0; j < 8; j++) { xr[2 * j] = __ldg(px + j * 4); xr[2 * j + 1] = __ldg(px + 8 * DM / 2 + j * 4); }
            float acc[32];
            if (tl == 0) {
                if (wq == 0) {
                    wait_cnt(C_O + rb, 32 * tag, 200);
                    fence_async_all();
                    if (elect_one()) {
                        mbar_arrive(bars + 8 * B_T1);
                        TSTAMP(22);
#pragma unroll 1
                        for (int i = 0; i < 2; i++) { mbar_expect(bars + 8 * (B_O + i), 8192); bulk_load(ring + 65536 + i * 8192, g_o + (rb * 8 + i) * 512, 8192, bars + 8 * (B_O + i)); }
                    }
                }
                mbar_wait(bar_wo, 0);
#pragma unroll 1
                for (int kb = 0; kb < 8; kb++) {
                    const uint32_t b = bars + 8 * (B_O + (kb & 1)), a = OFF_RING + 65536 + (kb & 1) * 8192;
                    mbar_wait(b, (kb >> 1) & 1);
                    wg_fence();
#pragma unroll
                    for (int k = 0; k < 4; k++) wgmma_ss_n64(acc, mkdesc(a, 128, 1024, 0) + k * 16, mkdesc(OFF_RING + kb * 8192, 8192, 1024, 1) + k * 128, (kb | k) != 0);
                    wg_commit();
                    wg_wait<0>();
                    bar_sync(5, 128);
                    if (wq == 0 && kb < 6 && elect_one()) { mbar_expect(b, 8192); bulk_load(sb + a, g_o + (rb * 8 + kb + 2) * 512, 8192, b); }
                }
            } else {
#pragma unroll 1
                for (int kb = 0; kb < 8; kb++) {
                    mbar_wait(bars + 8 * (B_O2 + kb), 0);
                    wg_fence();
#pragma unroll
                    for (int k = 0; k < 4; k++) wgmma_ss_n64(acc, mkdesc(kb * 8192, 128, 1024, 0) + k * 16, mkdesc(OFF_RING + kb * 8192, 8192, 1024, 1) + k * 128, (kb | k) != 0);
                    wg_commit();
                }
            }
            wg_wait<0>();
            pin<32>(acc);
            uint32_t* po = reinterpret_cast<uint32_t*>(out + (size_t)(rb * 64 + wq * 16 + g) * DM + cb * 64) + t4;
#pragma unroll
            for (int i = 0; i < 16; i++) {
                const uint32_t r = pack_bf16(fmaf(acc[2 * i], bf_lo(gate[0][i]), bf_lo(xr[i])), fmaf(acc[2 * i + 1], bf_hi(gate[0][i]), bf_hi(xr[i])));
                po[(i & 1) * (8 * DM / 2) + (i >> 1) * 4] = r;
                gate[0][i] = gate[1][i];
            }
            if (tid == 512) TSTAMP(23 + 2 * tl);
        }
    }
}

typedef CUresult (*EncodeFn)(CUtensorMap*, CUtensorMapDataType, cuuint32_t, void*, const cuuint64_t*, const cuuint64_t*, const cuuint32_t*,
                             const cuuint32_t*, CUtensorMapInterleave, CUtensorMapSwizzle, CUtensorMapL2promotion, CUtensorMapFloatOOBfill);

void make_map(EncodeFn fn, CUtensorMap* m, const void* p, int rows, int cols, int box_rows) {
    cuuint64_t dims[2] = {(cuuint64_t)cols, (cuuint64_t)rows};
    cuuint64_t strides[1] = {(cuuint64_t)cols * 2};
    cuuint32_t box[2] = {64, (cuuint32_t)box_rows};
    cuuint32_t es[2] = {1, 1};
    fn(m, CU_TENSOR_MAP_DATA_TYPE_BFLOAT16, 2, const_cast<void*>(p), dims, strides, box, es, CU_TENSOR_MAP_INTERLEAVE_NONE,
       CU_TENSOR_MAP_SWIZZLE_128B, CU_TENSOR_MAP_L2_PROMOTION_L2_128B, CU_TENSOR_MAP_FLOAT_OOB_FILL_NONE);
}

}

extern "C" void kernel_launch(void* const* d_in, const int* in_sizes, int n_in, void* d_out, int out_size) {
    const __nv_bfloat16* x = (const __nv_bfloat16*)d_in[0];
    static EncodeFn fn = nullptr;
    if (!fn) {
        cudaDriverEntryPointQueryResult qr;
        cudaGetDriverEntryPoint("cuTensorMapEncodeTiled", (void**)&fn, cudaEnableDefault, &qr);
        cudaFuncSetAttribute(mega_kernel, cudaFuncAttributeMaxDynamicSharedMemorySize, SMEM_BYTES);
    }
    CUtensorMap mx, mqkv, mw1, mw3, mw2, mwo;
    make_map(fn, &mx, d_in[0], SEQ, DM, 128);
    make_map(fn, &mqkv, d_in[1], DM, 3 * DM, 64);
    make_map(fn, &mwo, d_in[2], DM, DM, 64);
    make_map(fn, &mw1, d_in[4], DM, FF, 64);
    make_map(fn, &mw3, d_in[5], DM, FF, 64);
    make_map(fn, &mw2, d_in[6], FF, DM, 64);
    mega_kernel<<<128, 640, SMEM_BYTES, cudaStreamPerThread>>>(x, (const __nv_bfloat16*)d_in[1], (const __nv_bfloat16*)d_in[4], (const __nv_bfloat16*)d_in[5],
                                                               (__nv_bfloat16*)d_out, mx, mqkv, mw1, mw3, mw2, mwo, 0x3F003F00u);
}
```

```cpp
#include <cuda_runtime.h>
#include <cuda_bf16.h>
#include <cuda.h>
#include <stdint.h>

namespace {

constexpr int SEQ = 2048, DM = 512, FF = 1792;

__device__ uint4 g_q[32 * 128 * 32];
__device__ uint4 g_kv[64 * 4096];
__device__ uint4 g_h[32 * 28 * 512];
__device__ uint4 g_o[32 * 8 * 512];
__device__ ulonglong2 g_cs[40 * 8 * 64];
__device__ ulonglong2 g_rs[SEQ / 2];
constexpr int C_QKV = 0, C_H = 12, C_H2 = 28, C_O = 44, C_NUM = 76;
__device__ unsigned g_cnt[C_NUM * 8];
__device__ unsigned g_epoch[128];
#define TSTAMP(i)
#define GSTAMP(i)
#define TS3(k, i)
#define TS2(k, i)

__device__ __forceinline__ uint32_t smem_u32(const void* p) { return (uint32_t)__cvta_generic_to_shared(p); }
__device__ __forceinline__ void mbar_init(uint32_t a, int c) { asm volatile("mbarrier.init.shared::cta.b64 [%0], %1;" :: "r"(a), "r"(c)); }
__device__ __forceinline__ void mbar_expect(uint32_t a, int b) { asm volatile("mbarrier.arrive.expect_tx.shared::cta.b64 _, [%0], %1;" :: "r"(a), "r"(b) : "memory"); }
__device__ __forceinline__ void mbar_arrive(uint32_t a) { asm volatile("mbarrier.arrive.shared::cta.b64 _, [%0];" :: "r"(a) : "memory"); }
__device__ __forceinline__ void mbar_arrive_remote(uint32_t a) { asm volatile("mbarrier.arrive.shared::cluster.b64 _, [%0];" :: "r"(a) : "memory"); }
__device__ __forceinline__ bool mbar_try(uint32_t a, uint32_t ph) {
    uint32_t ok;
    asm volatile("{\n.reg .pred p;\nmbarrier.try_wait.parity.shared::cta.b64 p, [%1], %2;\nselp.u32 %0, 1, 0, p;\n}" : "=r"(ok) : "r"(a), "r"(ph) : "memory");
    return ok;
}
__device__ __forceinline__ void mbar_wait(uint32_t a, uint32_t ph) {
    int n = 1 << 22;
#pragma unroll 1
    do { n = __all_sync(0xffffffffu, mbar_try(a, ph)) ? 0 : n - 1; } while (n > 0);
}
__device__ __forceinline__ bool elect_one() {
    uint32_t p;
    asm volatile("{\n.reg .pred P;\nelect.sync _|P, 0xffffffff;\nselp.u32 %0, 1, 0, P;\n}" : "=r"(p));
    return p;
}
__device__ __forceinline__ void signal_cnt(int c) {
    asm volatile("fence.release.gpu;\nred.relaxed.gpu.global.add.u32 [%0], 1;" :: "l"(g_cnt + c * 8) : "memory");
}
__device__ __forceinline__ void wait_cnt(int c, unsigned target, int ns) {
#pragma unroll 1
    for (int n = 0; n < 2000000; n++) {
        unsigned v;
        asm volatile("ld.relaxed.gpu.global.u32 %0, [%1];" : "=r"(v) : "l"(g_cnt + c * 8) : "memory");
        if (__all_sync(0xffffffffu, (int)(v - target) >= 0)) break;
        __nanosleep(ns);
    }
}
__device__ __forceinline__ uint32_t ld_epoch() {
    uint32_t e;
    asm volatile("ld.relaxed.gpu.global.u32 %0, [%1];" : "=r"(e) : "l"(g_epoch + blockIdx.x) : "memory");
    return e;
}
__device__ __forceinline__ void st_relaxed(uint32_t* p, uint32_t v) { asm volatile("st.relaxed.gpu.global.u32 [%0], %1;" :: "l"(p), "r"(v) : "memory"); }
__device__ __forceinline__ void st_tagged(void* p, uint32_t v, uint32_t tag) {
    asm volatile("st.relaxed.gpu.global.b64 [%0], %1;" :: "l"(p), "l"((unsigned long long)tag << 32 | v) : "memory");
}
__device__ __forceinline__ uint32_t ld_tagged2(const ulonglong2* p, uint32_t tag, uint32_t& a, uint32_t& b) {
    unsigned long long u, v;
    asm volatile("ld.relaxed.gpu.global.v2.b64 {%0,%1}, [%2];" : "=l"(u), "=l"(v) : "l"(p) : "memory");
    a = (uint32_t)u; b = (uint32_t)v;
    return ((uint32_t)(u >> 32) ^ tag) | ((uint32_t)(v >> 32) ^ tag);
}
__device__ __forceinline__ void tma2d(uint32_t dst, const CUtensorMap* m, int c0, int c1, uint32_t bar) {
    asm volatile("cp.async.bulk.tensor.2d.shared::cluster.global.mbarrier::complete_tx::bytes [%0], [%1, {%3, %4}], [%2];"
                 :: "r"(dst), "l"(m), "r"(bar), "r"(c0), "r"(c1) : "memory");
}
__device__ __forceinline__ void tma2d_mc(uint32_t dst, const CUtensorMap* m, int c0, int c1, uint32_t bar) {
    asm volatile("cp.async.bulk.tensor.2d.shared::cluster.global.mbarrier::complete_tx::bytes.multicast::cluster [%0], [%1, {%3, %4}], [%2], %5;"
                 :: "r"(dst), "l"(m), "r"(bar), "r"(c0), "r"(c1), "h"((uint16_t)3) : "memory");
}
__device__ __forceinline__ void bulk_load(uint32_t dst, const void* src, int bytes, uint32_t bar) {
    asm volatile("cp.async.bulk.shared::cluster.global.mbarrier::complete_tx::bytes [%0], [%1], %2, [%3];"
                 :: "r"(dst), "l"(src), "r"(bytes), "r"(bar) : "memory");
}
__device__ __forceinline__ void bar_sync(int id, int n) { asm volatile("bar.sync %0, %1;" :: "r"(id), "r"(n) : "memory"); }
__device__ __forceinline__ void fence_async_smem() { asm volatile("fence.proxy.async.shared::cta;" ::: "memory"); }
__device__ __forceinline__ void fence_async_all() { asm volatile("fence.acquire.gpu;\nfence.proxy.async.global;" ::: "memory"); }
__device__ __forceinline__ void wg_fence() { asm volatile("wgmma.fence.sync.aligned;" ::: "memory"); }
__device__ __forceinline__ void wg_commit() { asm volatile("wgmma.commit_group.sync.aligned;" ::: "memory"); }
template <int N> __device__ __forceinline__ void wg_wait() { asm volatile("wgmma.wait_group.sync.aligned %0;" :: "n"(N) : "memory"); }
template <int N> __device__ __forceinline__ void pin(float* d) {
#pragma unroll
    for (int i = 0; i < N; i++) asm volatile("" : "+f"(d[i]) :: "memory");
}
template <int N> __device__ __forceinline__ void pin(uint32_t* d) {
#pragma unroll
    for (int i = 0; i < N; i++) asm volatile("" : "+r"(d[i]) :: "memory");
}
constexpr uint32_t SMEM_BASE = 1024;
__device__ __forceinline__ uint64_t mkdesc(uint32_t off, uint32_t lbo, uint32_t sbo, uint32_t swz) {
    return (uint64_t)((SMEM_BASE + off) >> 4) | ((uint64_t)(lbo >> 4) << 16) | ((uint64_t)(sbo >> 4) << 32) | ((uint64_t)swz << 62);
}
__device__ __forceinline__ float ex2f(float x) { float y; asm("ex2.approx.ftz.f32 %0, %1;" : "=f"(y) : "f"(x)); return y; }
__device__ __forceinline__ float rcpf(float x) { float y; asm("rcp.approx.ftz.f32 %0, %1;" : "=f"(y) : "f"(x)); return y; }
__device__ __forceinline__ uint32_t pack_bf16(float lo, float hi) { uint32_t r; asm("cvt.rn.bf16x2.f32 %0, %1, %2;" : "=r"(r) : "f"(hi), "f"(lo)); return r; }
__device__ __forceinline__ float bf_lo(uint32_t v) { return __uint_as_float(v << 16); }
__device__ __forceinline__ float bf_hi(uint32_t v) { return __uint_as_float(v & 0xFFFF0000u); }
__device__ __forceinline__ float bf_round(float x) { return __bfloat162float(__float2bfloat16_rn(x)); }
__device__ __forceinline__ float siluf(float g) { return g * rcpf(1.0f + ex2f(g * -1.4426950408889634f)); }

__device__ __forceinline__ void wgmma_ss_n128_zero(float* d, uint64_t da, uint64_t db) {
    asm volatile("wgmma.mma_async.sync.aligned.m64n128k16.f32.bf16.bf16 {"
        "%0,%1,%2,%3,%4,%5,%6,%7,%8,%9,%10,%11,%12,%13,%14,%15,%16,%17,%18,%19,%20,%21,%22,%23,%24,%25,%26,%27,%28,%29,%30,%31,%32,%33,%34,%35,%36,%37,%38,%39,"
        "%40,%41,%42,%43,%44,%45,%46,%47,%48,%49,%50,%51,%52,%53,%54,%55,%56,%57,%58,%59,%60,%61,%62,%63"
        "}, %64, %65, 0, 1, 1, 0, 1;\n"
        : "=f"(d[0]),"=f"(d[1]),"=f"(d[2]),"=f"(d[3]),"=f"(d[4]),"=f"(d[5]),"=f"(d[6]),"=f"(d[7]),"=f"(d[8]),"=f"(d[9]),"=f"(d[10]),"=f"(d[11]),"=f"(d[12]),
          "=f"(d[13]),"=f"(d[14]),"=f"(d[15]),"=f"(d[16]),"=f"(d[17]),"=f"(d[18]),"=f"(d[19]),"=f"(d[20]),"=f"(d[21]),"=f"(d[22]),"=f"(d[23]),"=f"(d[24]),
          "=f"(d[25]),"=f"(d[26]),"=f"(d[27]),"=f"(d[28]),"=f"(d[29]),"=f"(d[30]),"=f"(d[31]),"=f"(d[32]),"=f"(d[33]),"=f"(d[34]),"=f"(d[35]),"=f"(d[36]),
          "=f"(d[37]),"=f"(d[38]),"=f"(d[39]),"=f"(d[40]),"=f"(d[41]),"=f"(d[42]),"=f"(d[43]),"=f"(d[44]),"=f"(d[45]),"=f"(d[46]),"=f"(d[47]),"=f"(d[48]),
          "=f"(d[49]),"=f"(d[50]),"=f"(d[51]),"=f"(d[52]),"=f"(d[53]),"=f"(d[54]),"=f"(d[55]),"=f"(d[56]),"=f"(d[57]),"=f"(d[58]),"=f"(d[59]),"=f"(d[60]),
          "=f"(d[61]),"=f"(d[62]),"=f"(d[63])
        : "l"(da), "l"(db));
}
__device__ __forceinline__ void wgmma_ss_n128_acc(float* d, uint64_t da, uint64_t db) {
    asm volatile("wgmma.mma_async.sync.aligned.m64n128k16.f32.bf16.bf16 {"
        "%0,%1,%2,%3,%4,%5,%6,%7,%8,%9,%10,%11,%12,%13,%14,%15,%16,%17,%18,%19,%20,%21,%22,%23,%24,%25,%26,%27,%28,%29,%30,%31,%32,%33,%34,%35,%36,%37,%38,%39,"
        "%40,%41,%42,%43,%44,%45,%46,%47,%48,%49,%50,%51,%52,%53,%54,%55,%56,%57,%58,%59,%60,%61,%62,%63"
        "}, %64, %65, 1, 1, 1, 0, 1;\n"
        : "+f"(d[0]),"+f"(d[1]),"+f"(d[2]),"+f"(d[3]),"+f"(d[4]),"+f"(d[5]),"+f"(d[6]),"+f"(d[7]),"+f"(d[8]),"+f"(d[9]),"+f"(d[10]),"+f"(d[11]),"+f"(d[12]),
          "+f"(d[13]),"+f"(d[14]),"+f"(d[15]),"+f"(d[16]),"+f"(d[17]),"+f"(d[18]),"+f"(d[19]),"+f"(d[20]),"+f"(d[21]),"+f"(d[22]),"+f"(d[23]),"+f"(d[24]),
          "+f"(d[25]),"+f"(d[26]),"+f"(d[27]),"+f"(d[28]),"+f"(d[29]),"+f"(d[30]),"+f"(d[31]),"+f"(d[32]),"+f"(d[33]),"+f"(d[34]),"+f"(d[35]),"+f"(d[36]),
          "+f"(d[37]),"+f"(d[38]),"+f"(d[39]),"+f"(d[40]),"+f"(d[41]),"+f"(d[42]),"+f"(d[43]),"+f"(d[44]),"+f"(d[45]),"+f"(d[46]),"+f"(d[47]),"+f"(d[48]),
          "+f"(d[49]),"+f"(d[50]),"+f"(d[51]),"+f"(d[52]),"+f"(d[53]),"+f"(d[54]),"+f"(d[55]),"+f"(d[56]),"+f"(d[57]),"+f"(d[58]),"+f"(d[59]),"+f"(d[60]),
          "+f"(d[61]),"+f"(d[62]),"+f"(d[63])
        : "l"(da), "l"(db));
}
__device__ __forceinline__ void wgmma_ts_n128_acc(float* d, uint64_t da, uint64_t db) {
    asm volatile("wgmma.mma_async.sync.aligned.m64n128k16.f32.bf16.bf16 {"
        "%0,%1,%2,%3,%4,%5,%6,%7,%8,%9,%10,%11,%12,%13,%14,%15,%16,%17,%18,%19,%20,%21,%22,%23,%24,%25,%26,%27,%28,%29,%30,%31,%32,%33,%34,%35,%36,%37,%38,%39,"
        "%40,%41,%42,%43,%44,%45,%46,%47,%48,%49,%50,%51,%52,%53,%54,%55,%56,%57,%58,%59,%60,%61,%62,%63"
        "}, %64, %65, 1, 1, 1, 1, 0;\n"
        : "+f"(d[0]),"+f"(d[1]),"+f"(d[2]),"+f"(d[3]),"+f"(d[4]),"+f"(d[5]),"+f"(d[6]),"+f"(d[7]),"+f"(d[8]),"+f"(d[9]),"+f"(d[10]),"+f"(d[11]),"+f"(d[12]),
          "+f"(d[13]),"+f"(d[14]),"+f"(d[15]),"+f"(d[16]),"+f"(d[17]),"+f"(d[18]),"+f"(d[19]),"+f"(d[20]),"+f"(d[21]),"+f"(d[22]),"+f"(d[23]),"+f"(d[24]),
          "+f"(d[25]),"+f"(d[26]),"+f"(d[27]),"+f"(d[28]),"+f"(d[29]),"+f"(d[30]),"+f"(d[31]),"+f"(d[32]),"+f"(d[33]),"+f"(d[34]),"+f"(d[35]),"+f"(d[36]),
          "+f"(d[37]),"+f"(d[38]),"+f"(d[39]),"+f"(d[40]),"+f"(d[41]),"+f"(d[42]),"+f"(d[43]),"+f"(d[44]),"+f"(d[45]),"+f"(d[46]),"+f"(d[47]),"+f"(d[48]),
          "+f"(d[49]),"+f"(d[50]),"+f"(d[51]),"+f"(d[52]),"+f"(d[53]),"+f"(d[54]),"+f"(d[55]),"+f"(d[56]),"+f"(d[57]),"+f"(d[58]),"+f"(d[59]),"+f"(d[60]),
          "+f"(d[61]),"+f"(d[62]),"+f"(d[63])
        : "l"(da), "l"(db));
}
__device__ __forceinline__ void wgmma_ts_n64_acc(float* d, uint64_t da, uint64_t db) {
    asm volatile("wgmma.mma_async.sync.aligned.m64n64k16.f32.bf16.bf16 {"
        "%0,%1,%2,%3,%4,%5,%6,%7,%8,%9,%10,%11,%12,%13,%14,%15,%16,%17,%18,%19,%20,%21,%22,%23,%24,%25,%26,%27,%28,%29,%30,%31"
        "}, %32, %33, 1, 1, 1, 1, 0;\n"
        : "+f"(d[0]),"+f"(d[1]),"+f"(d[2]),"+f"(d[3]),"+f"(d[4]),"+f"(d[5]),"+f"(d[6]),"+f"(d[7]),"+f"(d[8]),"+f"(d[9]),"+f"(d[10]),"+f"(d[11]),"+f"(d[12]),
          "+f"(d[13]),"+f"(d[14]),"+f"(d[15]),"+f"(d[16]),"+f"(d[17]),"+f"(d[18]),"+f"(d[19]),"+f"(d[20]),"+f"(d[21]),"+f"(d[22]),"+f"(d[23]),"+f"(d[24]),
          "+f"(d[25]),"+f"(d[26]),"+f"(d[27]),"+f"(d[28]),"+f"(d[29]),"+f"(d[30]),"+f"(d[31])
        : "l"(da), "l"(db));
}
__device__ __forceinline__ void wgmma_rs_n64_zero(float* d, const uint32_t* a, uint64_t db) {
    asm volatile("wgmma.mma_async.sync.aligned.m64n64k16.f32.bf16.bf16 {"
        "%0,%1,%2,%3,%4,%5,%6,%7,%8,%9,%10,%11,%12,%13,%14,%15,%16,%17,%18,%19,%20,%21,%22,%23,%24,%25,%26,%27,%28,%29,%30,%31"
        "}, {%32,%33,%34,%35}, %36, 0, 1, 1, 0;\n"
        : "=f"(d[0]),"=f"(d[1]),"=f"(d[2]),"=f"(d[3]),"=f"(d[4]),"=f"(d[5]),"=f"(d[6]),"=f"(d[7]),"=f"(d[8]),"=f"(d[9]),"=f"(d[10]),"=f"(d[11]),"=f"(d[12]),
          "=f"(d[13]),"=f"(d[14]),"=f"(d[15]),"=f"(d[16]),"=f"(d[17]),"=f"(d[18]),"=f"(d[19]),"=f"(d[20]),"=f"(d[21]),"=f"(d[22]),"=f"(d[23]),"=f"(d[24]),
          "=f"(d[25]),"=f"(d[26]),"=f"(d[27]),"=f"(d[28]),"=f"(d[29]),"=f"(d[30]),"=f"(d[31])
        : "r"(a[0]), "r"(a[1]), "r"(a[2]), "r"(a[3]), "l"(db));
}
__device__ __forceinline__ void wgmma_rs_n64_acc(float* d, const uint32_t* a, uint64_t db) {
    asm volatile("wgmma.mma_async.sync.aligned.m64n64k16.f32.bf16.bf16 {"
        "%0,%1,%2,%3,%4,%5,%6,%7,%8,%9,%10,%11,%12,%13,%14,%15,%16,%17,%18,%19,%20,%21,%22,%23,%24,%25,%26,%27,%28,%29,%30,%31"
        "}, {%32,%33,%34,%35}, %36, 1, 1, 1, 0;\n"
        : "+f"(d[0]),"+f"(d[1]),"+f"(d[2]),"+f"(d[3]),"+f"(d[4]),"+f"(d[5]),"+f"(d[6]),"+f"(d[7]),"+f"(d[8]),"+f"(d[9]),"+f"(d[10]),"+f"(d[11]),"+f"(d[12]),
          "+f"(d[13]),"+f"(d[14]),"+f"(d[15]),"+f"(d[16]),"+f"(d[17]),"+f"(d[18]),"+f"(d[19]),"+f"(d[20]),"+f"(d[21]),"+f"(d[22]),"+f"(d[23]),"+f"(d[24]),
          "+f"(d[25]),"+f"(d[26]),"+f"(d[27]),"+f"(d[28]),"+f"(d[29]),"+f"(d[30]),"+f"(d[31])
        : "r"(a[0]), "r"(a[1]), "r"(a[2]), "r"(a[3]), "l"(db));
}
__device__ __forceinline__ void wgmma_rs_n24_acc(float* d, const uint32_t* a, uint64_t db) {
    asm volatile("wgmma.mma_async.sync.aligned.m64n24k16.f32.bf16.bf16 {"
        "%0,%1,%2,%3,%4,%5,%6,%7,%8,%9,%10,%11"
        "}, {%12,%13,%14,%15}, %16, 1, 1, 1, 1;\n"
        : "+f"(d[0]),"+f"(d[1]),"+f"(d[2]),"+f"(d[3]),"+f"(d[4]),"+f"(d[5]),"+f"(d[6]),"+f"(d[7]),"+f"(d[8]),"+f"(d[9]),"+f"(d[10]),"+f"(d[11])
        : "r"(a[0]), "r"(a[1]), "r"(a[2]), "r"(a[3]), "l"(db));
}

constexpr int OFF_ONES = 131072;
constexpr int OFF_RING = OFF_ONES + 4096;
constexpr int NRING = 5;
constexpr int OFF_B2 = OFF_RING + NRING * 16384;
constexpr int OFF_CS = OFF_B2 + 2048;
constexpr int OFF_RS = OFF_CS + 2560;
constexpr int OFF_Q = OFF_RS + 512;
constexpr int OFF_BAR = OFF_Q + 64;
enum { B_FULL = 0, B_EMPTY = 40,
       B_TILE = 80, B_OW = 85, B_DONE = 87,
       B_O2 = 90, B_QKV = 98,
       B_KV = 100, B_WO = 108, B_T1 = 109, B_STATS = 110, B_O = 115,
       B_DN = 120,
       B_NUM = 148 };
constexpr int OFF_TS = OFF_BAR + 1280;
constexpr int SMEM_BYTES = OFF_BAR + B_NUM * 8;
constexpr unsigned FIXED_MASK = 0xB5;
constexpr float P71 = 2361183241434822606848.0f, M71 = 4.235164736271502e-22f;

__device__ __forceinline__ uint32_t exp2_fixed(float lo, float hi, uint32_t half2) {
    uint32_t y, g, d;
    asm("cvt.pack.sat.s16.s32 %0, %1, %2;" : "=r"(y) : "r"(__float_as_uint(hi)), "r"(__float_as_uint(lo)));
    asm("lop3.b32 %0, %1, 0x007F007F, %2, 0xEA;" : "=r"(g) : "r"(y), "r"(half2));
    asm("fma.rn.bf16x2 %0, %1, %2, %3;" : "=r"(d) : "r"(y), "r"(g), "r"(y & 0xFF80FF80u));
    return d;
}
constexpr uint64_t DK_STEP = 512 - (256ull << 16), DV_STEP = 512 - (256ull << 32);
constexpr uint32_t POS_LAST = 0x37521640u;
#define NEARLY 2
#define SIG_KB 6
#define SLEEP_NS 0
#define UNR 8
#define POLL_TH 10
#define ORD_LAG 2

__global__ void __cluster_dims__(2, 1, 1) __launch_bounds__(640, 1)
mega_kernel(const __nv_bfloat16* __restrict__ x, const __nv_bfloat16* __restrict__ wqkv, const __nv_bfloat16* __restrict__ w1,
            const __nv_bfloat16* __restrict__ w3, __nv_bfloat16* __restrict__ out,
            const __grid_constant__ CUtensorMap mx, const __grid_constant__ CUtensorMap mqkv, const __grid_constant__ CUtensorMap mw1,
            const __grid_constant__ CUtensorMap mw3, const __grid_constant__ CUtensorMap mw2, const __grid_constant__ CUtensorMap mwo,
            uint32_t half2) {
    extern __shared__ __align__(1024) uint8_t smem_raw[];
    const uint32_t sb = __shfl_sync(0xffffffffu, smem_u32(smem_raw), 0);
    if ((sb & 0xFFFFFF) != SMEM_BASE) __trap();
    const uint32_t bars = sb + OFF_BAR, ring = sb + OFF_RING;
    const int tid = threadIdx.x, lane = tid & 31, g = lane >> 2, t4 = lane & 3;
    const int warp = __shfl_sync(0xffffffffu, tid >> 5, 0), wg = warp >> 2, wq = warp & 3;
    const int rank = blockIdx.x & 1, cl = blockIdx.x >> 1;
    const int grp = cl < 4 ? 4 + cl : cl < 36 ? (cl - 4) >> 3 : 4 + (cl - 36) / 7;
    const int rot = cl < 4 ? 7 : cl < 36 ? (cl - 4) & 7 : (cl - 36) % 7;
    const int mblk = rot * 2 + rank;
    const int nq = grp < 4 ? 2 : 1;
    const int qt0 = grp < 4 ? 2 * grp : 4 + grp;
    const int gu0 = grp < 4 ? 2 * grp - 2 : 3 * grp - 5;
    auto unit_of = [&](int t) { return t == 4 ? 20 + grp : gu0 + t; };
    const int lid = blockIdx.x;
    const int head = lid >> 2, qb = lid & 3;
    const int cb = lid & 7, rb0 = (lid >> 5) * 8 + ((lid >> 3) & 3);

    if (elect_one()) {
        const uint32_t b0 = bars + (warp < 16 ? warp * 40 : warp * 80 - 640), cnt = warp < 8 || warp > 17 ? 1 : warp == 17 ? 2 : 8;
#pragma unroll
        for (int i = 0; i < 5; i++) mbar_init(b0 + 8 * i, cnt);
        if (warp == 0) {
            fence_async_smem();
#pragma unroll
            for (int j = 0; j < 2; j++) {
                tma2d(sb + j * 16384, &mx, j * 64, mblk * 128, bars + 8 * (B_FULL + j));
                tma2d(ring + j * 16384, &mqkv, qt0 * 128, j * 64, bars + 8 * (B_FULL + j));
                tma2d(ring + j * 16384 + 8192, &mqkv, qt0 * 128 + 64, j * 64, bars + 8 * (B_FULL + j));
            }
#pragma unroll
            for (int j = 2; j < NEARLY; j++) tma2d(sb + j * 16384, &mx, j * 64, mblk * 128, bars + 8 * (B_FULL + j));
        }
        if (warp < 8) {
#pragma unroll
            for (int i = 0; i < 5; i++) mbar_expect(b0 + 8 * i, warp * 5 + i < 8 ? 32768 : 16384);
        } else if (warp >= 16) {
#pragma unroll
            for (int i = 5; i < 10; i++) mbar_init(b0 + 8 * i, cnt);
            if (warp == 16) {
                asm volatile("prefetch.tensormap [%0];" :: "l"(rank ? &mw3 : &mw1) : "memory");
            }
        }
        asm volatile("fence.mbarrier_init.release.cluster;" ::: "memory");
    }
    __syncthreads();
    if (tid == 512) TSTAMP(26);
    asm volatile("barrier.cluster.arrive.relaxed.aligned;" ::: "memory");

    if (wg < 4) {
        const int pair = (wg >> 1) ^ 1, half = wg & 1, w8 = warp & 7;
        if (pair == 1) {
            const int row = mblk * 128 + grp * 16 + w8 * 2 + (lane >> 4);
            uint4 v[6];
            const uint32_t* w = reinterpret_cast<const uint32_t*>(v);
#pragma unroll
            for (int j = 0; j < 2; j++) v[4 + j] = __ldg(reinterpret_cast<const uint4*>(wqkv + (size_t)(rot * 64 + w8 * 8 + j * 4 + (lane >> 3)) * (3 * DM) + qt0 * 128 + rank * 64) + (lane & 7));
#pragma unroll
            for (int j = 0; j < 4; j++) v[j] = __ldg(reinterpret_cast<const uint4*>(x + (size_t)row * DM) + j * 16 + (lane & 15));
            const uint32_t tag = ld_epoch() + 1;
            float c[8];
#pragma unroll
            for (int e = 0; e < 4; e++) { c[2 * e] = bf_lo(w[16 + e]) + bf_lo(w[20 + e]); c[2 * e + 1] = bf_hi(w[16 + e]) + bf_hi(w[20 + e]); }
#pragma unroll
            for (int n = 4; n > 1; n >>= 1) {
                const bool up = lane & (4 * n);
#pragma unroll
                for (int e = 0; e < n; e++) c[e] = (up ? c[e + n] : c[e]) + __shfl_xor_sync(0xffffffffu, up ? c[e] : c[e + n], 4 * n);
            }
            asm volatile("st.shared.v2.f32 [%0], {%1,%2};" :: "r"(sb + OFF_CS + 512 + w8 * 256 + (lane & 7) * 32 + (lane >> 3) * 8), "f"(c[0]), "f"(c[1]) : "memory");
            bar_sync(6, 256);
            if (w8 < 2) {
#pragma unroll
                for (int e = 0; e < 8; e++) asm volatile("ld.shared.f32 %0, [%1];" : "=f"(c[e]) : "r"(sb + OFF_CS + 512 + e * 256 + (tid & 63) * 4));
                st_tagged(reinterpret_cast<unsigned long long*>(g_cs) + (grp * 40 + rot) * 128 + rank * 64 + (tid & 63),
                          __float_as_uint(((c[0] + c[1]) + (c[2] + c[3])) + ((c[4] + c[5]) + (c[6] + c[7]))), tag);
                if ((tid & 255) == 0) TSTAMP(40);
            }
            float sa[4] = {0.f, 0.f, 0.f, 0.f}, sq[4] = {0.f, 0.f, 0.f, 0.f};
#pragma unroll
            for (int j = 0; j < 16; j++) sa[j & 3] += bf_lo(w[j]) + bf_hi(w[j]);
            float mean = ((sa[0] + sa[1]) + (sa[2] + sa[3])) * (1.0f / 32);
#pragma unroll
            for (int j = 0; j < 16; j++) { const float a = bf_lo(w[j]) - mean, b = bf_hi(w[j]) - mean; sq[j & 1] = fmaf(a, a, sq[j & 1]); sq[2 + (j & 1)] = fmaf(b, b, sq[2 + (j & 1)]); }
            float m2 = (sq[0] + sq[1]) + (sq[2] + sq[3]);
#pragma unroll
            for (int d = 1; d < 16; d <<= 1) {
                const float om = __shfl_xor_sync(0xffffffffu, mean, d), o2 = __shfl_xor_sync(0xffffffffu, m2, d), dm = mean - om;
                m2 = fmaf(dm * dm, 16.0f * d, m2 + o2); mean = 0.5f * (mean + om);
            }
            float sd;
            asm("sqrt.approx.f32 %0, %1;" : "=f"(sd) : "f"(bf_round(bf_round(m2 * (1.0f / DM)) + 1e-5f)));
            if ((lane & 15) == 0) st_tagged(reinterpret_cast<unsigned long long*>(g_rs) + row, pack_bf16(mean, sd), tag);
            if ((tid & 255) == 0) TSTAMP(45);
        }

        uint32_t q[4], qn[4];
        {
            const int rowblk = mblk * 2 + half, tile16 = rowblk * 4 + wq;
            uint32_t empty;
            asm("mapa.shared::cluster.u32 %0, %1, %2;" : "=r"(empty) : "r"(bars + 8 * B_EMPTY), "r"(wq & 1));
#pragma unroll 1
            for (int t = pair; t < 5; t += 2) {
                float acc[64];
                uint32_t full = bars + 8 * (B_FULL + 8 * t), rel = empty + 64 * t;
                uint32_t stepa = t == 4 ? 0x4AB93AC : 0x9999999, stepb = (uint32_t)(0x994999949999ull >> (4 * ((0x24130u >> (4 * t)) & 7)));
                uint64_t da = mkdesc(half * 8192, 16, 1024, 1), db = mkdesc(OFF_RING, 8192, 1024, 1) + ((0x24130u >> (4 * t)) & 7) * 1024;
                if ((tid & 255) == 0 && t == 0) TSTAMP(30);
                mbar_wait(full, 0);
                if (t > 0) mbar_wait(full + 8 * (B_EMPTY - ORD_LAG), 0);
                wg_fence();
                wgmma_ss_n128_zero(acc, da, db);
#pragma unroll
                for (int k = 1; k < 4; k++) wgmma_ss_n128_acc(acc, da + k * 2, db + k * 128);
                wg_commit();
                mbar_wait(full + 8, 0);
#pragma unroll 1
                do {
                    da += (int)((stepa & 15) << 10) - 8192; db += (int)((stepb & 15) << 10) - 8192;
                    stepa >>= 4; stepb >>= 4;
                    wg_fence();
#pragma unroll
                    for (int k = 0; k < 4; k++) wgmma_ss_n128_acc(acc, da + k * 2, db + k * 128);
                    wg_commit();
                    mbar_wait(full + 16, 0);
                    wg_wait<1>();
                    if (elect_one()) mbar_arrive_remote(rel);
                    full += 8; rel += 8;
                } while (stepa);
                if (t >= 3) {
                    mbar_wait(bars + 8 * B_QKV, 0);
                    const uint4* pq = g_q + (head * 128 + (qb * 8 + wg) * 4 + wq) * 32 + lane;
                    const uint4 v = __ldcg(pq), u = __ldcg(pq + 512);
                    q[0] = v.x; q[1] = v.y; q[2] = v.z; q[3] = v.w; qn[0] = u.x; qn[1] = u.y; qn[2] = u.z; qn[3] = u.w;
                }
                wg_wait<0>();
                if (elect_one()) mbar_arrive_remote(rel);
                pin<64>(acc);
                if (wq == 0 && half == 0 && lane == 0) TSTAMP(2 + 2 * t);
                if ((tid & 255) == 0 && t == 4) GSTAMP(10);
                mbar_wait(bars + 8 * (B_STATS + t), 0);
                uint32_t rs0, rs1;
                asm volatile("ld.shared.b32 %0, [%1];" : "=r"(rs0) : "r"(sb + OFF_RS + (half * 64 + wq * 16 + g) * 4));
                asm volatile("ld.shared.b32 %0, [%1];" : "=r"(rs1) : "r"(sb + OFF_RS + (half * 64 + wq * 16 + g + 8) * 4));
                const float m0 = bf_lo(rs0), m1 = bf_lo(rs1);
                float d0 = bf_hi(rs0), d1 = bf_hi(rs1);
                float r0 = rcpf(d0), r1 = rcpf(d1);
                const uint32_t pcs = sb + OFF_CS + t * 512 + t4 * 8;
                auto lds2 = [&](int j, float* c) { asm volatile("ld.shared.v2.f32 {%0,%1}, [%2];" : "=f"(c[0]), "=f"(c[1]) : "r"(pcs + j * 32) : "memory"); };
                auto fix = [&](float* a, const float* c) { a[0] = fmaf(-m0, c[0], a[0]); a[1] = fmaf(-m0, c[1], a[1]); a[2] = fmaf(-m1, c[0], a[2]); a[3] = fmaf(-m1, c[1], a[3]); };
                float c[2][4];
                if (t < nq) {
                    const int qt = qt0 + t;
                    if (qt < 4) {
                        r0 *= 0.25f * 1.4426950408889634f * M71; r1 *= 0.25f * 1.4426950408889634f * M71;
                    } else if (qt < 8) {
                        r0 *= ((FIXED_MASK >> (2 * wq)) & 1) ? M71 : P71; r1 *= ((FIXED_MASK >> (2 * wq + 1)) & 1) ? M71 : P71;
                    }
                    uint8_t* p = qt < 4 ? reinterpret_cast<uint8_t*>(g_q + (qt * 1024 + tile16) * 32 + lane)
                                        : reinterpret_cast<uint8_t*>(g_kv + (qt - 4) * 32768) + tile16 * 256 + lane * 4;
                    lds2(0, c[0]); lds2(1, c[0] + 2);
#pragma unroll
                    for (int hh = 0; hh < 8; hh++) {
                        if (hh < 7) { lds2(2 * hh + 2, c[~hh & 1]); lds2(2 * hh + 3, c[~hh & 1] + 2); }
                        float* a = acc + hh * 8;
                        fix(a, c[hh & 1]); fix(a + 4, c[hh & 1] + 2);
                        asm volatile("{\n.reg .pred p;\nsetp.lt.s32 p, %5, 4;\n@p st.global.v4.b32 [%0], {%1,%2,%3,%4};\n"
                                     "@!p st.global.b32 [%0], %1;\n@!p st.global.b32 [%0+128], %2;\n@!p st.global.b32 [%0+32768], %3;\n@!p st.global.b32 [%0+32896], %4;\n}"
                                     :: "l"(p + hh * 65536), "r"(pack_bf16(a[0] * r0, a[1] * r0)), "r"(pack_bf16(a[2] * r1, a[3] * r1)),
                                        "r"(pack_bf16(a[4] * r0, a[5] * r0)), "r"(pack_bf16(a[6] * r1, a[7] * r1)), "r"(qt) : "memory");
                    }
                } else {
                    uint32_t* p = reinterpret_cast<uint32_t*>(g_h + ((((rowblk >> 3) * 4 + (rowblk & 3)) * 28 + unit_of(t)) * 2 + ((rowblk >> 2) & 1)) * 512) + wq * 512 + lane;
                    r0 *= -1.4426950408889634f; r1 *= -1.4426950408889634f; d0 *= d0; d1 *= d1;
                    lds2(0, c[0]); lds2(8, c[0] + 2);
#pragma unroll
                    for (int j = 0; j < 8; j++) {
                        if (j < 7) { lds2(j + 1, c[~j & 1]); lds2(j + 9, c[~j & 1] + 2); }
                        float* a = acc + j * 4; float* b = a + 32;
                        fix(a, c[j & 1]); fix(b, c[j & 1] + 2);
                        p[j * 32] = pack_bf16(a[0] * b[0] * rcpf(fmaf(ex2f(a[0] * r0), d0, d0)), a[1] * b[1] * rcpf(fmaf(ex2f(a[1] * r0), d0, d0)));
                        p[256 + j * 32] = pack_bf16(a[2] * b[2] * rcpf(fmaf(ex2f(a[2] * r1), d1, d1)), a[3] * b[3] * rcpf(fmaf(ex2f(a[3] * r1), d1, d1)));
                    }
                }
                __syncwarp();
                if (elect_one()) mbar_arrive(bars + 8 * (B_TILE + t));
                if (wq == 0 && half == 0 && lane == 0) TSTAMP(3 + 2 * t);
            }
        }
        const uint64_t db2 = mkdesc(OFF_B2, 128, 256, 0) - (sb >> 28);
        uint32_t q2[4];
        q2[2] = __shfl_sync(0xffffffffu, lane, 0); q2[3] = __shfl_sync(0xffffffffu, lane ^ 1, 1);
        int nref = 1;
        mbar_wait(bars + 8 * B_KV, 0);
#pragma unroll 1
        for (int round = 0; round < 2;) {
            float s[32];
            {
                float m0 = -INFINITY, m1 = -INFINITY, f0 = -INFINITY, f1 = -INFINITY;
                int t = 0;
#pragma unroll 1
                do {
                    wg_fence();
                    wgmma_rs_n64_zero(s, q, mkdesc(4096, 94208, 128, 0) + (t >> 2) * DK_STEP + (t & 3) * 64);
                    wg_commit();
                    wg_wait<0>();
                    pin<32>(s);
#pragma unroll
                    for (int i = 0; i < 8; i++) {
                        if ((FIXED_MASK >> i) & 1) { f0 = fmaxf(f0, fmaxf(s[4 * i], s[4 * i + 1])); f1 = fmaxf(f1, fmaxf(s[4 * i + 2], s[4 * i + 3])); }
                        else                       { m0 = fmaxf(m0, fmaxf(s[4 * i], s[4 * i + 1])); m1 = fmaxf(m1, fmaxf(s[4 * i + 2], s[4 * i + 3])); }
                    }
                } while (++t < nref);
                m0 = fmaxf(m0, f0 * P71 * P71); m1 = fmaxf(m1, f1 * P71 * P71);
                m0 = fmaxf(m0, __shfl_xor_sync(0xffffffffu, m0, 1)); m1 = fmaxf(m1, __shfl_xor_sync(0xffffffffu, m1, 1));
                m0 = fmaxf(m0, __shfl_xor_sync(0xffffffffu, m0, 2)); m1 = fmaxf(m1, __shfl_xor_sync(0xffffffffu, m1, 2));
#pragma unroll
                for (int r = 0; r < 2; r++) {
                    const float m = __fsub_rn(12582912.f, __fadd_rn(r ? m1 : m0, 12582912.f)) * M71;
                    const float r1 = m - bf_hi(__float_as_uint(m)), r2 = r1 - bf_hi(__float_as_uint(r1));
                    const float lo = t4 == 0 ? m : t4 == 1 ? r2 : t4 == 2 ? M71 : 0.f, hi = t4 == 0 ? r1 : t4 == 1 ? M71 : 0.f;
                    q2[r] = __byte_perm(__float_as_uint(lo), __float_as_uint(hi), 0x7632);
                }
            }
            float o[12]; uint32_t p[16];
#pragma unroll
            for (int i = 0; i < 12; i++) o[i] = 0.f;
            pin<12>(o); pin<4>(q2);
            if (wq == 0 && half == 0 && lane == 0) TSTAMP(12 + 4 * round + pair);
            uint64_t dk = mkdesc(4096, 94208, 128, 0), dv = mkdesc(0, 128, 65536, 0);
#pragma unroll 1
            for (int c = 0; c < 8; c += UNR / 4, dk += UNR / 4 * DK_STEP, dv += UNR / 4 * DV_STEP) {
                if (round == 0) {
#pragma unroll
                    for (int i = 0; i < UNR / 4; i++) mbar_wait(bars + 8 * (B_KV + c + i), 0);
                }
#pragma unroll
                for (int t = 0; t < UNR; t++) {
                    wg_fence();
                    wgmma_rs_n64_zero(s, q, dk + (t >> 2) * DK_STEP + (t & 3) * 64);
                    wgmma_rs_n64_acc(s, q2, db2);
                    wg_commit();
                    wg_wait<0>();
                    pin<32>(s); pin<16>(p);
#pragma unroll
                    for (int i = 0; i < 16; i++) {
                        if ((FIXED_MASK >> (i >> 1)) & 1) p[i] = exp2_fixed(s[2 * i], s[2 * i + 1], half2);
                        else                              p[i] = pack_bf16(ex2f(s[2 * i]), ex2f(s[2 * i + 1]));
                    }
                    wg_fence();
#pragma unroll
                    for (int k = 0; k < 4; k++) wgmma_rs_n24_acc(o, p + 4 * k, dv + (t >> 2) * DV_STEP + ((t & 3) * 4 + k) * 16);
                    wg_commit();
                }
            }
            wg_wait<0>();
            pin<12>(o);
            if (nref != 32) {
                float chk = (o[8] + o[10]) * 256.f;
#pragma unroll
                for (int i = 0; i < 8; i++) chk += fabsf(o[i]);
                uint32_t bad;
                asm volatile("{\n.reg .pred p, q;\nsetp.geu.f32 q, %1, 0f7F800000;\nbar.red.or.pred p, %2, 128, q;\nselp.u32 %0, 1, 0, p;\n}" : "=r"(bad) : "f"(chk), "r"(1 + wg) : "memory");
                if (__any_sync(0xffffffffu, bad)) { nref = 32; continue; }
            }
            const int rowblk = qb * 8 + round * 4 + wg;
            const float r0 = rcpf(o[8]), r1 = rcpf(o[10]);
            uint32_t* po = reinterpret_cast<uint32_t*>(g_o + (rowblk * 8 + (head >> 2)) * 512) + wq * 512 + (head & 3) * 64 + lane;
            st_relaxed(po, pack_bf16(o[0] * r0, o[1] * r0)); st_relaxed(po + 256, pack_bf16(o[2] * r1, o[3] * r1));
            st_relaxed(po + 32, pack_bf16(o[4] * r0, o[5] * r0)); st_relaxed(po + 288, pack_bf16(o[6] * r1, o[7] * r1));
            if (round == 0) {
                po += 4 * 8 * 2048;
                st_relaxed(po, ~0u); st_relaxed(po + 256, ~0u); st_relaxed(po + 32, ~0u); st_relaxed(po + 288, ~0u);
            }
            __syncwarp();
            if (elect_one()) mbar_arrive(bars + 8 * (B_OW + 2 * round + (wg >> 1)));
#pragma unroll
            for (int i = 0; i < 4; i++) q[i] = qn[i];
            nref = 1;
            if (SLEEP_NS && pair == 1 && round == 0) __nanosleep(SLEEP_NS);
            if (wq == 0 && half == 0 && lane == 0) TSTAMP(14 + 4 * round + pair);
            if (wq == 0 && lane == 0) GSTAMP(round * 4 + wg);
            round++;
        }
        mbar_wait(bars + 8 * B_T1, 0);
        if (lane == 0) TS3(1, warp);
        uint4 v[8];
        uint32_t pend = 0xFF;
        const uint4* src = g_o + (rb0 + 4) * 4096 + (warp >> 1) * 512 + (warp & 1) * 32 + lane;
#pragma unroll
        for (int i = 0; i < 8; i++) v[i].x = ~0u;
#pragma unroll 1
        for (int n = 0; n < 2000000 && pend; n++) {
            uint32_t done;
            asm volatile("ld.volatile.shared.u32 %0, [%1];" : "=r"(done) : "r"(sb + OFF_Q) : "memory");
            const uint32_t get = pend == 0xFF && done < POLL_TH ? 0x80 : pend;
#pragma unroll
            for (int i = 0; i < 8; i++) {
                if (get >> i & 1)
                    asm volatile("ld.relaxed.gpu.global.v4.u32 {%0,%1,%2,%3}, [%4];" : "=r"(v[i].x), "=r"(v[i].y), "=r"(v[i].z), "=r"(v[i].w) : "l"(src + i * 64) : "memory");
            }
            uint32_t bad = 0;
#pragma unroll
            for (int i = 0; i < 8; i++) bad |= (__vimax3_u32(max(v[i].x, v[i].y), v[i].z, v[i].w) == ~0u) << i;
            pend = __reduce_or_sync(0xffffffffu, bad);
            if (lane == 0 && n < 2) TS3(1, 16 + 16 * n + warp);
        }
        if (lane == 0) TS3(2, warp);
        if (elect_one()) asm volatile("red.shared.add.u32 [%0], 1;" :: "r"(sb + OFF_Q) : "memory");
        mbar_wait(bars + 8 * B_DONE, 0); mbar_wait(bars + 8 * (B_DONE + 1), 0);
#pragma unroll
        for (int i = 0; i < 8; i++)
            asm volatile("st.shared.v4.b32 [%0], {%1,%2,%3,%4};" :: "r"(sb + (warp >> 1) * 8192 + (warp & 1) * 512 + i * 1024 + lane * 16), "r"(v[i].x), "r"(v[i].y), "r"(v[i].z), "r"(v[i].w) : "memory");
        if (lane == 0) TS3(2, 16 + warp);
        fence_async_smem();
        __syncwarp();
        if (elect_one()) mbar_arrive(bars + 8 * (B_O2 + (warp >> 1)));
        if (lane == 0) TS3(2, 32 + warp);
        if (tid == 0) TSTAMP(24);
        if (lane == 0) GSTAMP(16 + warp);
    } else {
        uint32_t tag;
        if (wq == 0) {
            asm volatile("barrier.cluster.wait.aligned;" ::: "memory");
            if (tid == 512) TSTAMP(27);
            uint32_t slot = 2;
#pragma unroll 1
            for (int n = 2; n < 40; n++) {
                const int t = n >> 3, j = n & 7;
                const int kc = (n < 32 ? j : (POS_LAST >> (4 * j)) & 7) * 64;
                const CUtensorMap* m = t < nq ? &mqkv : rank ? &mw3 : &mw1;
                const int col = t < nq ? (qt0 + t) * 128 + rank * 64 : unit_of(t) * 64;
                const uint32_t dst = ring + slot * 16384 + rank * 8192, fb = bars + 8 * (B_FULL + n);
                if (n >= NEARLY && n < 8 && elect_one()) tma2d(sb + n * 16384, &mx, kc, mblk * 128, fb);
                if (n >= NRING) mbar_wait(fb + 8 * (B_EMPTY - NRING), 0);
                if (elect_one()) {
                    tma2d_mc(dst, m, col, kc, fb); }
                if (++slot == NRING) slot = 0;
            }
            tag = ld_epoch() + 1;
            wait_cnt(C_H + (rb0 >> 1), 20 * tag, 100);
            wait_cnt(C_H + (rb0 >> 1) + 2, 20 * tag, 100);
            fence_async_all();
        } else if (wq == 1) {
            tag = ld_epoch() + 1;
            mbar_wait(bars + 8 * (B_FULL + 5), 0);
#pragma unroll 1
            for (int t = 0; t < 5; t++) {
                float a[4];
#pragma unroll 1
                for (int n = 0; n < 2000000; n++) {
                    uint32_t stale = 0;
                    a[0] = a[1] = a[2] = a[3] = 0.f;
#pragma unroll
                    for (int i = 0; i < 16; i++) {
                        uint32_t u, v;
                        stale |= ld_tagged2(g_cs + (grp * 5 + t) * 512 + i * 32 + lane, tag, u, v);
                        a[(i & 1) * 2] += __uint_as_float(u); a[(i & 1) * 2 + 1] += __uint_as_float(v);
                    }
                    if (__all_sync(0xffffffffu, stale == 0)) break;
                    if (t) __nanosleep(400);
                }
                asm volatile("st.shared.v2.f32 [%0], {%1,%2};" :: "r"(sb + OFF_CS + t * 512 + lane * 8), "f"(a[0]), "f"(a[1]) : "memory");
                asm volatile("st.shared.v2.f32 [%0], {%1,%2};" :: "r"(sb + OFF_CS + t * 512 + 256 + lane * 8), "f"(a[2]), "f"(a[3]) : "memory");
                if (t == 0) {
                    uint32_t r[4];
#pragma unroll 1
                    for (int n = 0; n < 2000000; n++) {
                        const uint32_t stale = ld_tagged2(g_rs + mblk * 64 + lane * 2, tag, r[0], r[1]) | ld_tagged2(g_rs + mblk * 64 + lane * 2 + 1, tag, r[2], r[3]);
                        if (__all_sync(0xffffffffu, stale == 0)) break;
                    }
                    asm volatile("st.shared.v4.b32 [%0], {%1,%2,%3,%4};" :: "r"(sb + OFF_RS + lane * 16), "r"(r[0]), "r"(r[1]), "r"(r[2]), "r"(r[3]) : "memory");
                }
                __syncwarp();
                if (elect_one()) { mbar_arrive(bars + 8 * (B_STATS + t)); TSTAMP(32 + t); }
            }
        } else {
            tag = ld_epoch() + 1;
            mbar_wait(bars + 8 * (B_FULL + wq - 1), 0);
#pragma unroll 1
            for (int t = wq - 1; t < 5; t += 2) {
                const __nv_bfloat16* src; int ld;
                if (t < nq) { src = wqkv + (qt0 + t) * 128 + rank * 64; ld = 3 * DM; }
                else        { src = (rank ? w3 : w1) + unit_of(t) * 64; ld = FF; }
                src += (size_t)(rot * 64 + (lane >> 3)) * ld + (lane & 7) * 8;
                uint4 v[16];
                const uint32_t* w = reinterpret_cast<const uint32_t*>(v);
#pragma unroll
                for (int j = 0; j < 16; j++) v[j] = __ldg(reinterpret_cast<const uint4*>(src + (size_t)j * 4 * ld));
                float c[8];
#pragma unroll
                for (int e = 0; e < 4; e++) {
                    float a = 0.f, b = 0.f;
#pragma unroll
                    for (int j = 0; j < 16; j++) { a += bf_lo(w[4 * j + e]); b += bf_hi(w[4 * j + e]); }
                    c[2 * e] = a; c[2 * e + 1] = b;
                }
#pragma unroll
                for (int n = 4; n > 1; n >>= 1) {
                    const bool up = lane & (4 * n);
#pragma unroll
                    for (int e = 0; e < n; e++) c[e] = (up ? c[e + n] : c[e]) + __shfl_xor_sync(0xffffffffu, up ? c[e] : c[e + n], 4 * n);
                }
                unsigned long long* dst = reinterpret_cast<unsigned long long*>(g_cs) + ((grp * 5 + t) * 8 + rot) * 128 + rank * 64 + (lane & 7) * 8 + (lane >> 3) * 2;
                st_tagged(dst, __float_as_uint(c[0]), tag); st_tagged(dst + 1, __float_as_uint(c[1]), tag);
                if (lane == 0) TSTAMP(40 + t);
            }
        }
        if (wq == 3) {
#pragma unroll 1
            for (int i = lane; i < 256; i += 32) asm volatile("st.shared.v4.b32 [%0], {%1,%1,%1,%1};" :: "r"(sb + OFF_ONES + i * 16), "r"(0x3F803F80u) : "memory");
#pragma unroll 1
            for (int i = lane; i < 128; i += 32) {
                const bool fx = (FIXED_MASK >> (i >> 4)) & 1;
                uint32_t a = fx ? pack_bf16(M71, M71) : pack_bf16(P71, P71);
                uint32_t b = fx ? pack_bf16(M71, 47.0f * M71) : pack_bf16(P71, -79.5f * P71);
                uint32_t c = fx ? 0u : pack_bf16(0.08214f * P71, 0.f);
                if (i & 8) a = b = c = 0;
                asm volatile("st.shared.v4.b32 [%0], {%1,%2,%3,%4};" :: "r"(sb + OFF_B2 + i * 16), "r"(a), "r"(b), "r"(c), "r"(0) : "memory");
            }
            if (elect_one()) {
                asm volatile("st.shared.u32 [%0], %1;" :: "r"(sb + OFF_Q), "r"(0) : "memory");
#pragma unroll 1
                for (int i = 0; i < 28; i++) { mbar_init(bars + 8 * (B_DN + i), 1); mbar_expect(bars + 8 * (B_DN + i), 24576); }
                mbar_expect(bars + 8 * B_WO, 65536);
#pragma unroll 1
                for (int i = 0; i < 4; i++) mbar_expect(bars + 8 * (B_O + i), 16384);
            }
            fence_async_smem();
            __syncwarp();
            if (elect_one()) mbar_arrive(bars + 8 * B_QKV);
        } else if (wq == 1) {
#pragma unroll 1
            for (int i = 0; i < 3; i++) wait_cnt(C_QKV + i * 4 + (head >> 3), 16 * tag, 100);
            fence_async_all();
            if (elect_one()) { mbar_arrive(bars + 8 * B_QKV); TSTAMP(29); }
            mbar_wait(bars + 8 * (B_EMPTY + 31), 0);
            const uint8_t* gk = reinterpret_cast<const uint8_t*>(g_kv + head * 4096);
            const uint8_t* gv = reinterpret_cast<const uint8_t*>(g_kv + (32 + head) * 4096);
#pragma unroll 1
            for (int c = 0; c < 8; c++) {
                mbar_wait(bars + 8 * (B_EMPTY + 34 + (c & 4) + ((c >> 1) & 1)), 0);
                if (elect_one()) {
                    const uint32_t b = bars + 8 * (B_KV + c);
                    mbar_expect(b, 16384);
                    bulk_load(sb + (2 * c + 1) * 4096, gk + c * 4096, 4096, b);
                    bulk_load(sb + 2 * c * 4096, gv + c * 4096, 4096, b);
                    bulk_load(sb + 65536 + c * 4096, gv + 32768 + c * 4096, 4096, b);
                    bulk_load(sb + 98304 + c * 4096, gk + 32768 + c * 4096, 4096, b);
                }
            }
        } else if (wq == 2) {
#pragma unroll 1
            for (int t = 0; t < 4; t++) {
                mbar_wait(bars + 8 * (B_TILE + t), 0);
                if (elect_one()) signal_cnt(t < nq ? C_QKV + qt0 + t : C_H + mblk);
            }
        }
        pin<1>(&tag);
        bar_sync(5, 128);
        if (tid == 639) g_epoch[blockIdx.x] = tag;
        uint32_t gate[2][16];
        {
            float dn[64];
#pragma unroll
            for (int i = 0; i < 64; i++) dn[i] = 0.f;
            pin<64>(dn);
            const uint4* hsrc = g_h + (lid >> 3) * 28 * 1024;
            uint32_t nb = bars + 8 * B_DN, dst = ring, kc = 0, slot = 0;
            auto load_stage = [&]() {
                if (wq == 0) { if (elect_one()) bulk_load(dst, hsrc, 16384, nb); }
                else if (wq == 1) { if (elect_one()) tma2d(dst + 16384, &mw2, cb * 64, kc, nb); }
                hsrc += 1024; kc += 64; nb += 8;
            };
            if (tid == 512) TSTAMP(20);
            load_stage(); dst += 24576; load_stage(); dst += 24576;
#pragma unroll 1
            for (int seg = 0; seg < 4; seg++) {
                const int kend = seg == 0 ? (SIG_KB + 2) * 64 : seg == 1 ? 20 * 64 : seg == 2 ? 28 * 64 : 30 * 64;
#pragma unroll 1
                do {
                    mbar_wait(nb - 16, 0);
                    const uint64_t dw = mkdesc(OFF_RING + 16384, 8192, 1024, 1) + slot, dh = mkdesc(OFF_RING, 128, 1024, 0) + slot;
                    wg_fence();
#pragma unroll
                    for (int k = 0; k < 4; k++) wgmma_ts_n128_acc(dn, dw + k * 128, dh + k * 16);
                    wg_commit();
                    wg_wait<1>();
                    if (seg < 3) load_stage(); else { kc += 64; nb += 8; }
                    dst = ring + slot * 16;
                    slot = slot == 3072 ? 0 : slot + 1536;
                } while (kc != kend);
                if (seg == 0 && wq == 2) {
                    mbar_wait(bars + 8 * (B_TILE + 4), 0);
                    if (elect_one()) signal_cnt(C_H2 + mblk);
                } else if (seg == 1 && wq == 0) {
                    wait_cnt(C_H2 + (rb0 >> 1), 8 * tag, 100);
                    wait_cnt(C_H2 + (rb0 >> 1) + 2, 8 * tag, 100);
                    fence_async_all();
                }
            }
            wg_wait<0>();
            pin<64>(dn);
            if (wq == 1 && elect_one()) {
#pragma unroll 1
                for (int i = 0; i < 8; i++) tma2d(ring + i * 8192, &mwo, cb * 64, i * 64, bars + 8 * B_WO);
            }
#pragma unroll
            for (int i = 0; i < 32; i++) gate[i >> 4][i & 15] = pack_bf16(siluf(dn[2 * i]), siluf(dn[2 * i + 1]));
        }
        if (tid == 512) TSTAMP(21);
        if (wq >= 2) {
            mbar_wait(bars + 8 * (B_OW + wq - 2), 0);
            if (elect_one()) {
                signal_cnt(C_O + qb * 8 + 2 * wq - 4);
                asm volatile("red.relaxed.gpu.global.add.u32 [%0], 1;" :: "l"(g_cnt + (C_O + qb * 8 + 2 * wq - 3) * 8) : "memory");
            }
        }
#pragma unroll 1
        for (int tl = 0; tl < 2; tl++) {
            const int rb = rb0 + 4 * tl;
            const size_t goff = (size_t)(rb * 64 + wq * 16 + (lane >> 3)) * (DM / 8) + cb * 8 + (lane & 7);
            uint4 xr[4];
#pragma unroll
            for (int i = 0; i < 4; i++) xr[i] = __ldg(reinterpret_cast<const uint4*>(x) + goff + i * 4 * (DM / 8));
            float acc[32];
#pragma unroll
            for (int i = 0; i < 32; i++) acc[i] = 0.f;
            pin<32>(acc);
            uint64_t dw = mkdesc(OFF_RING, 8192, 1024, 1);
            if (tl == 0) {
                if (wq == 0) {
                    wait_cnt(C_O + rb, 32 * tag, 200);
                    fence_async_all();
                    if (elect_one()) { mbar_arrive(bars + 8 * B_T1); TSTAMP(22); }
                }
                mbar_wait(bars + 8 * B_WO, 0);
#pragma unroll 1
                for (int i = 0; i < 4; i++, dw += 1024) {
                    if (wq == 0 && elect_one()) bulk_load(ring + 65536, g_o + (rb * 4 + i) * 1024, 16384, bars + 8 * (B_O + i));
                    mbar_wait(bars + 8 * (B_O + i), 0);
                    wg_fence();
#pragma unroll
                    for (int k = 0; k < 8; k++) wgmma_ts_n64_acc(acc, dw + k * 128, mkdesc(OFF_RING + 65536, 128, 1024, 0) + (k >> 2) * 512 + (k & 3) * 16);
                    wg_commit();
                    wg_wait<0>();
                }
            } else {
                uint64_t dx = mkdesc(0, 128, 1024, 0);
#pragma unroll 1
                for (int i = 0; i < 8; i++, dx += 512, dw += 512) {
                    mbar_wait(bars + 8 * (B_O2 + i), 0);
                    if (tid == 512) TS3(0, 48 + i);
                    wg_fence();
#pragma unroll
                    for (int k = 0; k < 4; k++) wgmma_ts_n64_acc(acc, dw + k * 128, dx + k * 16);
                    wg_commit();
                }
                wg_wait<0>();
            }
            pin<32>(acc);
            if (tid == 512) TS3(0, 56);
            const uint32_t stg = ring + 65536;
            uint32_t r[16];
#pragma unroll
            for (int i = 0; i < 16; i++) {
                asm("mul.rn.bf16x2 %0, %1, %2;" : "=r"(r[i]) : "r"(pack_bf16(acc[2 * i], acc[2 * i + 1])), "r"(gate[0][i]));
                gate[0][i] = gate[1][i];
            }
#pragma unroll
            for (int i = 0; i < 4; i++)
                asm volatile("stmatrix.sync.aligned.m8n8.x4.trans.shared.b16 [%0], {%1,%2,%3,%4};"
                             :: "r"(stg + (i * 16 + (lane >> 4) * 8 + (lane & 7)) * 128 + (((2 * wq + ((lane >> 3) & 1)) ^ (lane & 7)) << 4)),
                                "r"(r[4 * i]), "r"(r[4 * i + 1]), "r"(r[4 * i + 2]), "r"(r[4 * i + 3]) : "memory");
            bar_sync(5, 128);
#pragma unroll
            for (int i = 0; i < 4; i++) {
                const int row = wq * 16 + i * 4 + (lane >> 3);
                uint4 u;
                asm volatile("ld.shared.v4.b32 {%0,%1,%2,%3}, [%4];" : "=r"(u.x), "=r"(u.y), "=r"(u.z), "=r"(u.w) : "r"(stg + row * 128 + (((lane ^ row) & 7) << 4)) : "memory");
                asm("add.rn.bf16x2 %0, %0, %1;" : "+r"(u.x) : "r"(xr[i].x)); asm("add.rn.bf16x2 %0, %0, %1;" : "+r"(u.y) : "r"(xr[i].y));
                asm("add.rn.bf16x2 %0, %0, %1;" : "+r"(u.z) : "r"(xr[i].z)); asm("add.rn.bf16x2 %0, %0, %1;" : "+r"(u.w) : "r"(xr[i].w));
                reinterpret_cast<uint4*>(out)[goff + i * 4 * (DM / 8)] = u;
            }
            if (tid == 512) TSTAMP(23 + 2 * tl);
            if (tid == 512) GSTAMP(8 + tl);
        }
    }
}

typedef CUresult (*EncodeFn)(CUtensorMap*, CUtensorMapDataType, cuuint32_t, void*, const cuuint64_t*, const cuuint64_t*, const cuuint32_t*,
                             const cuuint32_t*, CUtensorMapInterleave, CUtensorMapSwizzle, CUtensorMapL2promotion, CUtensorMapFloatOOBfill);

void make_map(EncodeFn fn, CUtensorMap* m, const void* p, int rows, int cols, int box_rows) {
    cuuint64_t dims[2] = {(cuuint64_t)cols, (cuuint64_t)rows};
    cuuint64_t strides[1] = {(cuuint64_t)cols * 2};
    cuuint32_t box[2] = {64, (cuuint32_t)box_rows};
    cuuint32_t es[2] = {1, 1};
    fn(m, CU_TENSOR_MAP_DATA_TYPE_BFLOAT16, 2, const_cast<void*>(p), dims, strides, box, es, CU_TENSOR_MAP_INTERLEAVE_NONE,
       CU_TENSOR_MAP_SWIZZLE_128B, CU_TENSOR_MAP_L2_PROMOTION_L2_128B, CU_TENSOR_MAP_FLOAT_OOB_FILL_NONE);
}

}

extern "C" void kernel_launch(void* const* d_in, const int* in_sizes, int n_in, void* d_out, int out_size) {
    const __nv_bfloat16* x = (const __nv_bfloat16*)d_in[0];
    static EncodeFn fn = nullptr;
    if (!fn) {
        cudaDriverEntryPointQueryResult qr;
        cudaGetDriverEntryPoint("cuTensorMapEncodeTiled", (void**)&fn, cudaEnableDefault, &qr);
        cudaFuncSetAttribute(mega_kernel, cudaFuncAttributeMaxDynamicSharedMemorySize, SMEM_BYTES);
    }
    CUtensorMap mx, mqkv, mw1, mw3, mw2, mwo;
    make_map(fn, &mx, d_in[0], SEQ, DM, 128);
    make_map(fn, &mqkv, d_in[1], DM, 3 * DM, 64);
    make_map(fn, &mwo, d_in[2], DM, DM, 64);
    make_map(fn, &mw1, d_in[4], DM, FF, 64);
    make_map(fn, &mw3, d_in[5], DM, FF, 64);
    make_map(fn, &mw2, d_in[6], FF, DM, 64);
    mega_kernel<<<128, 640, SMEM_BYTES, cudaStreamPerThread>>>(x, (const __nv_bfloat16*)d_in[1], (const __nv_bfloat16*)d_in[4], (const __nv_bfloat16*)d_in[5],
                                                               (__nv_bfloat16*)d_out, mx, mqkv, mw1, mw3, mw2, mwo, 0x3F003F00u);
}
```

```cpp
#include <cuda_runtime.h>
#include <cuda_bf16.h>
#include <cuda.h>
#include <stdint.h>

namespace {

constexpr int SEQ = 2048, DM = 512, FF = 1792;

__device__ uint4 g_q[32 * 128 * 32];
__device__ uint4 g_kv[64 * 4096];
__device__ uint4 g_h[32 * 28 * 512];
__device__ uint4 g_o[32 * 8 * 512];
__device__ ulonglong2 g_cs[40 * 8 * 64];
__device__ ulonglong2 g_rs[SEQ / 2];
constexpr int C_QKV = 0, C_H = 12, C_H2 = 28, C_O = 44, C_NUM = 76;
__device__ unsigned g_cnt[C_NUM * 8];
__device__ unsigned g_epoch[128];
#define TSTAMP(i)
#define GSTAMP(i)
#define TS3(k, i)
#define TS2(k, i)

__device__ __forceinline__ uint32_t smem_u32(const void* p) { return (uint32_t)__cvta_generic_to_shared(p); }
__device__ __forceinline__ void mbar_init(uint32_t a, int c) { asm volatile("mbarrier.init.shared::cta.b64 [%0], %1;" :: "r"(a), "r"(c)); }
__device__ __forceinline__ void mbar_expect(uint32_t a, int b) { asm volatile("mbarrier.arrive.expect_tx.shared::cta.b64 _, [%0], %1;" :: "r"(a), "r"(b) : "memory"); }
__device__ __forceinline__ void mbar_arrive(uint32_t a) { asm volatile("mbarrier.arrive.shared::cta.b64 _, [%0];" :: "r"(a) : "memory"); }
__device__ __forceinline__ void mbar_arrive_remote(uint32_t a) { asm volatile("mbarrier.arrive.shared::cluster.b64 _, [%0];" :: "r"(a) : "memory"); }
__device__ __forceinline__ bool mbar_try(uint32_t a, uint32_t ph) {
    uint32_t ok;
    asm volatile("{\n.reg .pred p;\nmbarrier.try_wait.parity.shared::cta.b64 p, [%1], %2;\nselp.u32 %0, 1, 0, p;\n}" : "=r"(ok) : "r"(a), "r"(ph) : "memory");
    return ok;
}
__device__ __forceinline__ bool mbar_test(uint32_t a) {
    uint32_t ok;
    asm volatile("{\n.reg .pred p;\nmbarrier.test_wait.parity.shared::cta.b64 p, [%1], 0;\nselp.u32 %0, 1, 0, p;\n}" : "=r"(ok) : "r"(a) : "memory");
    return ok;
}
__device__ __forceinline__ void mbar_wait(uint32_t a, uint32_t ph) {
    int n = 1 << 22;
#pragma unroll 1
    do { n = __all_sync(0xffffffffu, mbar_try(a, ph)) ? 0 : n - 1; } while (n > 0);
}
__device__ __forceinline__ bool elect_one() {
    uint32_t p;
    asm volatile("{\n.reg .pred P;\nelect.sync _|P, 0xffffffff;\nselp.u32 %0, 1, 0, P;\n}" : "=r"(p));
    return p;
}
__device__ __forceinline__ void signal_cnt(int c) {
    asm volatile("fence.release.gpu;\nred.relaxed.gpu.global.add.u32 [%0], 1;" :: "l"(g_cnt + c * 8) : "memory");
}
__device__ __forceinline__ void wait_cnt(int c, unsigned target, int ns) {
#pragma unroll 1
    for (int n = 0; n < 2000000; n++) {
        unsigned v;
        asm volatile("ld.relaxed.gpu.global.u32 %0, [%1];" : "=r"(v) : "l"(g_cnt + c * 8) : "memory");
        if (__all_sync(0xffffffffu, (int)(v - target) >= 0)) break;
        __nanosleep(ns);
    }
}
__device__ __forceinline__ uint32_t ld_epoch() {
    uint32_t e;
    asm volatile("ld.relaxed.gpu.global.u32 %0, [%1];" : "=r"(e) : "l"(g_epoch + blockIdx.x) : "memory");
    return e;
}
__device__ __forceinline__ void st_relaxed(uint32_t* p, uint32_t v) { asm volatile("st.relaxed.gpu.global.u32 [%0], %1;" :: "l"(p), "r"(v) : "memory"); }
__device__ __forceinline__ void st_tagged(void* p, uint32_t v, uint32_t tag) {
    asm volatile("st.relaxed.gpu.global.b64 [%0], %1;" :: "l"(p), "l"((unsigned long long)tag << 32 | v) : "memory");
}
__device__ __forceinline__ uint32_t ld_tagged2(const ulonglong2* p, uint32_t tag, uint32_t& a, uint32_t& b) {
    unsigned long long u, v;
    asm volatile("ld.relaxed.gpu.global.v2.b64 {%0,%1}, [%2];" : "=l"(u), "=l"(v) : "l"(p) : "memory");
    a = (uint32_t)u; b = (uint32_t)v;
    return ((uint32_t)(u >> 32) ^ tag) | ((uint32_t)(v >> 32) ^ tag);
}
__device__ __forceinline__ void tma2d(uint32_t dst, const CUtensorMap* m, int c0, int c1, uint32_t bar) {
    asm volatile("cp.async.bulk.tensor.2d.shared::cluster.global.mbarrier::complete_tx::bytes [%0], [%1, {%3, %4}], [%2];"
                 :: "r"(dst), "l"(m), "r"(bar), "r"(c0), "r"(c1) : "memory");
}
__device__ __forceinline__ void tma2d_mc(uint32_t dst, const CUtensorMap* m, int c0, int c1, uint32_t bar) {
    asm volatile("cp.async.bulk.tensor.2d.shared::cluster.global.mbarrier::complete_tx::bytes.multicast::cluster [%0], [%1, {%3, %4}], [%2], %5;"
                 :: "r"(dst), "l"(m), "r"(bar), "r"(c0), "r"(c1), "h"((uint16_t)3) : "memory");
}
__device__ __forceinline__ void bulk_load(uint32_t dst, const void* src, int bytes, uint32_t bar) {
    asm volatile("cp.async.bulk.shared::cluster.global.mbarrier::complete_tx::bytes [%0], [%1], %2, [%3];"
                 :: "r"(dst), "l"(src), "r"(bytes), "r"(bar) : "memory");
}
__device__ __forceinline__ void bar_sync(int id, int n) { asm volatile("bar.sync %0, %1;" :: "r"(id), "r"(n) : "memory"); }
__device__ __forceinline__ void fence_async_smem() { asm volatile("fence.proxy.async.shared::cta;" ::: "memory"); }
__device__ __forceinline__ void fence_async_all() { asm volatile("fence.acquire.gpu;\nfence.proxy.async.global;" ::: "memory"); }
__device__ __forceinline__ void wg_fence() { asm volatile("wgmma.fence.sync.aligned;" ::: "memory"); }
__device__ __forceinline__ void wg_commit() { asm volatile("wgmma.commit_group.sync.aligned;" ::: "memory"); }
template <int N> __device__ __forceinline__ void wg_wait() { asm volatile("wgmma.wait_group.sync.aligned %0;" :: "n"(N) : "memory"); }
template <int N> __device__ __forceinline__ void pin(float* d) {
#pragma unroll
    for (int i = 0; i < N; i++) asm volatile("" : "+f"(d[i]) :: "memory");
}
template <int N> __device__ __forceinline__ void pin(uint32_t* d) {
#pragma unroll
    for (int i = 0; i < N; i++) asm volatile("" : "+r"(d[i]) :: "memory");
}
constexpr uint32_t SMEM_BASE = 1024;
__device__ __forceinline__ uint64_t mkdesc(uint32_t off, uint32_t lbo, uint32_t sbo, uint32_t swz) {
    return (uint64_t)((SMEM_BASE + off) >> 4) | ((uint64_t)(lbo >> 4) << 16) | ((uint64_t)(sbo >> 4) << 32) | ((uint64_t)swz << 62);
}
__device__ __forceinline__ float ex2f(float x) { float y; asm("ex2.approx.ftz.f32 %0, %1;" : "=f"(y) : "f"(x)); return y; }
__device__ __forceinline__ float rcpf(float x) { float y; asm("rcp.approx.ftz.f32 %0, %1;" : "=f"(y) : "f"(x)); return y; }
__device__ __forceinline__ uint32_t pack_bf16(float lo, float hi) { uint32_t r; asm("cvt.rn.bf16x2.f32 %0, %1, %2;" : "=r"(r) : "f"(hi), "f"(lo)); return r; }
__device__ __forceinline__ float bf_lo(uint32_t v) { return __uint_as_float(v << 16); }
__device__ __forceinline__ float bf_hi(uint32_t v) { return __uint_as_float(v & 0xFFFF0000u); }
__device__ __forceinline__ float bf_round(float x) { return __bfloat162float(__float2bfloat16_rn(x)); }
__device__ __forceinline__ float siluf(float g) { return g * rcpf(1.0f + ex2f(g * -1.4426950408889634f)); }

__device__ __forceinline__ void wgmma_ss_n128_zero(float* d, uint64_t da, uint64_t db) {
    asm volatile("wgmma.mma_async.sync.aligned.m64n128k16.f32.bf16.bf16 {"
        "%0,%1,%2,%3,%4,%5,%6,%7,%8,%9,%10,%11,%12,%13,%14,%15,%16,%17,%18,%19,%20,%21,%22,%23,%24,%25,%26,%27,%28,%29,%30,%31,%32,%33,%34,%35,%36,%37,%38,%39,"
        "%40,%41,%42,%43,%44,%45,%46,%47,%48,%49,%50,%51,%52,%53,%54,%55,%56,%57,%58,%59,%60,%61,%62,%63"
        "}, %64, %65, 0, 1, 1, 0, 1;\n"
        : "=f"(d[0]),"=f"(d[1]),"=f"(d[2]),"=f"(d[3]),"=f"(d[4]),"=f"(d[5]),"=f"(d[6]),"=f"(d[7]),"=f"(d[8]),"=f"(d[9]),"=f"(d[10]),"=f"(d[11]),"=f"(d[12]),
          "=f"(d[13]),"=f"(d[14]),"=f"(d[15]),"=f"(d[16]),"=f"(d[17]),"=f"(d[18]),"=f"(d[19]),"=f"(d[20]),"=f"(d[21]),"=f"(d[22]),"=f"(d[23]),"=f"(d[24]),
          "=f"(d[25]),"=f"(d[26]),"=f"(d[27]),"=f"(d[28]),"=f"(d[29]),"=f"(d[30]),"=f"(d[31]),"=f"(d[32]),"=f"(d[33]),"=f"(d[34]),"=f"(d[35]),"=f"(d[36]),
          "=f"(d[37]),"=f"(d[38]),"=f"(d[39]),"=f"(d[40]),"=f"(d[41]),"=f"(d[42]),"=f"(d[43]),"=f"(d[44]),"=f"(d[45]),"=f"(d[46]),"=f"(d[47]),"=f"(d[48]),
          "=f"(d[49]),"=f"(d[50]),"=f"(d[51]),"=f"(d[52]),"=f"(d[53]),"=f"(d[54]),"=f"(d[55]),"=f"(d[56]),"=f"(d[57]),"=f"(d[58]),"=f"(d[59]),"=f"(d[60]),
          "=f"(d[61]),"=f"(d[62]),"=f"(d[63])
        : "l"(da), "l"(db));
}
__device__ __forceinline__ void wgmma_ss_n128_acc(float* d, uint64_t da, uint64_t db) {
    asm volatile("wgmma.mma_async.sync.aligned.m64n128k16.f32.bf16.bf16 {"
        "%0,%1,%2,%3,%4,%5,%6,%7,%8,%9,%10,%11,%12,%13,%14,%15,%16,%17,%18,%19,%20,%21,%22,%23,%24,%25,%26,%27,%28,%29,%30,%31,%32,%33,%34,%35,%36,%37,%38,%39,"
        "%40,%41,%42,%43,%44,%45,%46,%47,%48,%49,%50,%51,%52,%53,%54,%55,%56,%57,%58,%59,%60,%61,%62,%63"
        "}, %64, %65, 1, 1, 1, 0, 1;\n"
        : "+f"(d[0]),"+f"(d[1]),"+f"(d[2]),"+f"(d[3]),"+f"(d[4]),"+f"(d[5]),"+f"(d[6]),"+f"(d[7]),"+f"(d[8]),"+f"(d[9]),"+f"(d[10]),"+f"(d[11]),"+f"(d[12]),
          "+f"(d[13]),"+f"(d[14]),"+f"(d[15]),"+f"(d[16]),"+f"(d[17]),"+f"(d[18]),"+f"(d[19]),"+f"(d[20]),"+f"(d[21]),"+f"(d[22]),"+f"(d[23]),"+f"(d[24]),
          "+f"(d[25]),"+f"(d[26]),"+f"(d[27]),"+f"(d[28]),"+f"(d[29]),"+f"(d[30]),"+f"(d[31]),"+f"(d[32]),"+f"(d[33]),"+f"(d[34]),"+f"(d[35]),"+f"(d[36]),
          "+f"(d[37]),"+f"(d[38]),"+f"(d[39]),"+f"(d[40]),"+f"(d[41]),"+f"(d[42]),"+f"(d[43]),"+f"(d[44]),"+f"(d[45]),"+f"(d[46]),"+f"(d[47]),"+f"(d[48]),
          "+f"(d[49]),"+f"(d[50]),"+f"(d[51]),"+f"(d[52]),"+f"(d[53]),"+f"(d[54]),"+f"(d[55]),"+f"(d[56]),"+f"(d[57]),"+f"(d[58]),"+f"(d[59]),"+f"(d[60]),
          "+f"(d[61]),"+f"(d[62]),"+f"(d[63])
        : "l"(da), "l"(db));
}
__device__ __forceinline__ void wgmma_ts_n128_acc(float* d, uint64_t da, uint64_t db) {
    asm volatile("wgmma.mma_async.sync.aligned.m64n128k16.f32.bf16.bf16 {"
        "%0,%1,%2,%3,%4,%5,%6,%7,%8,%9,%10,%11,%12,%13,%14,%15,%16,%17,%18,%19,%20,%21,%22,%23,%24,%25,%26,%27,%28,%29,%30,%31,%32,%33,%34,%35,%36,%37,%38,%39,"
        "%40,%41,%42,%43,%44,%45,%46,%47,%48,%49,%50,%51,%52,%53,%54,%55,%56,%57,%58,%59,%60,%61,%62,%63"
        "}, %64, %65, 1, 1, 1, 1, 0;\n"
        : "+f"(d[0]),"+f"(d[1]),"+f"(d[2]),"+f"(d[3]),"+f"(d[4]),"+f"(d[5]),"+f"(d[6]),"+f"(d[7]),"+f"(d[8]),"+f"(d[9]),"+f"(d[10]),"+f"(d[11]),"+f"(d[12]),
          "+f"(d[13]),"+f"(d[14]),"+f"(d[15]),"+f"(d[16]),"+f"(d[17]),"+f"(d[18]),"+f"(d[19]),"+f"(d[20]),"+f"(d[21]),"+f"(d[22]),"+f"(d[23]),"+f"(d[24]),
          "+f"(d[25]),"+f"(d[26]),"+f"(d[27]),"+f"(d[28]),"+f"(d[29]),"+f"(d[30]),"+f"(d[31]),"+f"(d[32]),"+f"(d[33]),"+f"(d[34]),"+f"(d[35]),"+f"(d[36]),
          "+f"(d[37]),"+f"(d[38]),"+f"(d[39]),"+f"(d[40]),"+f"(d[41]),"+f"(d[42]),"+f"(d[43]),"+f"(d[44]),"+f"(d[45]),"+f"(d[46]),"+f"(d[47]),"+f"(d[48]),
          "+f"(d[49]),"+f"(d[50]),"+f"(d[51]),"+f"(d[52]),"+f"(d[53]),"+f"(d[54]),"+f"(d[55]),"+f"(d[56]),"+f"(d[57]),"+f"(d[58]),"+f"(d[59]),"+f"(d[60]),
          "+f"(d[61]),"+f"(d[62]),"+f"(d[63])
        : "l"(da), "l"(db));
}
__device__ __forceinline__ void wgmma_ts_n64_acc(float* d, uint64_t da, uint64_t db) {
    asm volatile("wgmma.mma_async.sync.aligned.m64n64k16.f32.bf16.bf16 {"
        "%0,%1,%2,%3,%4,%5,%6,%7,%8,%9,%10,%11,%12,%13,%14,%15,%16,%17,%18,%19,%20,%21,%22,%23,%24,%25,%26,%27,%28,%29,%30,%31"
        "}, %32, %33, 1, 1, 1, 1, 0;\n"
        : "+f"(d[0]),"+f"(d[1]),"+f"(d[2]),"+f"(d[3]),"+f"(d[4]),"+f"(d[5]),"+f"(d[6]),"+f"(d[7]),"+f"(d[8]),"+f"(d[9]),"+f"(d[10]),"+f"(d[11]),"+f"(d[12]),
          "+f"(d[13]),"+f"(d[14]),"+f"(d[15]),"+f"(d[16]),"+f"(d[17]),"+f"(d[18]),"+f"(d[19]),"+f"(d[20]),"+f"(d[21]),"+f"(d[22]),"+f"(d[23]),"+f"(d[24]),
          "+f"(d[25]),"+f"(d[26]),"+f"(d[27]),"+f"(d[28]),"+f"(d[29]),"+f"(d[30]),"+f"(d[31])
        : "l"(da), "l"(db));
}
__device__ __forceinline__ void wgmma_rs_n40_zero(float* d, const uint32_t* a, uint64_t db) {
    asm volatile("wgmma.mma_async.sync.aligned.m64n40k16.f32.bf16.bf16 {"
        "%0,%1,%2,%3,%4,%5,%6,%7,%8,%9,%10,%11,%12,%13,%14,%15,%16,%17,%18,%19"
        "}, {%20,%21,%22,%23}, %24, 0, 1, 1, 0;\n"
        : "=f"(d[0]),"=f"(d[1]),"=f"(d[2]),"=f"(d[3]),"=f"(d[4]),"=f"(d[5]),"=f"(d[6]),"=f"(d[7]),"=f"(d[8]),"=f"(d[9]),"=f"(d[10]),"=f"(d[11]),"=f"(d[12]),
          "=f"(d[13]),"=f"(d[14]),"=f"(d[15]),"=f"(d[16]),"=f"(d[17]),"=f"(d[18]),"=f"(d[19])
        : "r"(a[0]), "r"(a[1]), "r"(a[2]), "r"(a[3]), "l"(db));
}
__device__ __forceinline__ void wgmma_rs_n64_zero(float* d, const uint32_t* a, uint64_t db) {
    asm volatile("wgmma.mma_async.sync.aligned.m64n64k16.f32.bf16.bf16 {"
        "%0,%1,%2,%3,%4,%5,%6,%7,%8,%9,%10,%11,%12,%13,%14,%15,%16,%17,%18,%19,%20,%21,%22,%23,%24,%25,%26,%27,%28,%29,%30,%31"
        "}, {%32,%33,%34,%35}, %36, 0, 1, 1, 0;\n"
        : "=f"(d[0]),"=f"(d[1]),"=f"(d[2]),"=f"(d[3]),"=f"(d[4]),"=f"(d[5]),"=f"(d[6]),"=f"(d[7]),"=f"(d[8]),"=f"(d[9]),"=f"(d[10]),"=f"(d[11]),"=f"(d[12]),
          "=f"(d[13]),"=f"(d[14]),"=f"(d[15]),"=f"(d[16]),"=f"(d[17]),"=f"(d[18]),"=f"(d[19]),"=f"(d[20]),"=f"(d[21]),"=f"(d[22]),"=f"(d[23]),"=f"(d[24]),
          "=f"(d[25]),"=f"(d[26]),"=f"(d[27]),"=f"(d[28]),"=f"(d[29]),"=f"(d[30]),"=f"(d[31])
        : "r"(a[0]), "r"(a[1]), "r"(a[2]), "r"(a[3]), "l"(db));
}
__device__ __forceinline__ void wgmma_rs_n64_acc(float* d, const uint32_t* a, uint64_t db) {
    asm volatile("wgmma.mma_async.sync.aligned.m64n64k16.f32.bf16.bf16 {"
        "%0,%1,%2,%3,%4,%5,%6,%7,%8,%9,%10,%11,%12,%13,%14,%15,%16,%17,%18,%19,%20,%21,%22,%23,%24,%25,%26,%27,%28,%29,%30,%31"
        "}, {%32,%33,%34,%35}, %36, 1, 1, 1, 0;\n"
        : "+f"(d[0]),"+f"(d[1]),"+f"(d[2]),"+f"(d[3]),"+f"(d[4]),"+f"(d[5]),"+f"(d[6]),"+f"(d[7]),"+f"(d[8]),"+f"(d[9]),"+f"(d[10]),"+f"(d[11]),"+f"(d[12]),
          "+f"(d[13]),"+f"(d[14]),"+f"(d[15]),"+f"(d[16]),"+f"(d[17]),"+f"(d[18]),"+f"(d[19]),"+f"(d[20]),"+f"(d[21]),"+f"(d[22]),"+f"(d[23]),"+f"(d[24]),
          "+f"(d[25]),"+f"(d[26]),"+f"(d[27]),"+f"(d[28]),"+f"(d[29]),"+f"(d[30]),"+f"(d[31])
        : "r"(a[0]), "r"(a[1]), "r"(a[2]), "r"(a[3]), "l"(db));
}
__device__ __forceinline__ void wgmma_rs_n24_acc(float* d, const uint32_t* a, uint64_t db) {
    asm volatile("wgmma.mma_async.sync.aligned.m64n24k16.f32.bf16.bf16 {"
        "%0,%1,%2,%3,%4,%5,%6,%7,%8,%9,%10,%11"
        "}, {%12,%13,%14,%15}, %16, 1, 1, 1, 1;\n"
        : "+f"(d[0]),"+f"(d[1]),"+f"(d[2]),"+f"(d[3]),"+f"(d[4]),"+f"(d[5]),"+f"(d[6]),"+f"(d[7]),"+f"(d[8]),"+f"(d[9]),"+f"(d[10]),"+f"(d[11])
        : "r"(a[0]), "r"(a[1]), "r"(a[2]), "r"(a[3]), "l"(db));
}

constexpr int OFF_ONES = 131072;
constexpr int OFF_RING = OFF_ONES + 4096;
constexpr int NRING = 5;
constexpr int OFF_B2 = OFF_RING + NRING * 16384;
constexpr int OFF_CS = OFF_B2 + 2048;
constexpr int OFF_RS = OFF_CS + 2560;
constexpr int OFF_BAR = OFF_RS + 512;
enum { B_FULL = 0, B_EMPTY = 40,
       B_TILE = 80, B_OW = 85, B_DONE = 87,
       B_O2 = 90, B_QKV = 98,
       B_KV = 100, B_WO = 108, B_T1 = 109, B_STATS = 110, B_O = 115,
       B_DN = 120,
       B_NUM = 148 };
constexpr int OFF_TS = OFF_BAR + 1280;
constexpr int SMEM_BYTES = OFF_BAR + B_NUM * 8;
constexpr unsigned FIXED_MASK = 0x1F;
constexpr float P71 = 2361183241434822606848.0f, M71 = 4.235164736271502e-22f;

__device__ __forceinline__ uint32_t exp2_fixed(float lo, float hi, uint32_t half2) {
    uint32_t y, g, d;
    asm("cvt.pack.sat.s16.s32 %0, %1, %2;" : "=r"(y) : "r"(__float_as_uint(hi)), "r"(__float_as_uint(lo)));
    asm("lop3.b32 %0, %1, 0x007F007F, %2, 0xEA;" : "=r"(g) : "r"(y), "r"(half2));
    asm("fma.rn.bf16x2 %0, %1, %2, %3;" : "=r"(d) : "r"(y), "r"(g), "r"(y & 0xFF80FF80u));
    return d;
}
constexpr uint64_t DK_STEP = 512 - (256ull << 16), DV_STEP = 512 - (256ull << 32);
constexpr uint32_t POS_LAST = 0x37521640u;
#define NEARLY 2
#define PF0 1
#define PF1 1
#define PF2 1
#define G0_LAG 6
#define CS_LAG -1
#define BG_SPLIT 1
#define BG_GRP 1
#define BG_WAIT 1
#define T1_GRP 2
#define SIG_IT 2
#define UNR 8
#define ORD_LAG 2

__global__ void __cluster_dims__(2, 1, 1) __launch_bounds__(640, 1)
mega_kernel(const __nv_bfloat16* __restrict__ x, const __nv_bfloat16* __restrict__ wqkv, const __nv_bfloat16* __restrict__ w1,
            const __nv_bfloat16* __restrict__ w3, __nv_bfloat16* __restrict__ out,
            const __grid_constant__ CUtensorMap mx, const __grid_constant__ CUtensorMap mqkv, const __grid_constant__ CUtensorMap mw1,
            const __grid_constant__ CUtensorMap mw3, const __grid_constant__ CUtensorMap mw2, const __grid_constant__ CUtensorMap mwo,
            uint32_t half2) {
    if (threadIdx.x == 32) asm volatile("prefetch.tensormap [%0];" :: "l"(&mx) : "memory");
    if (threadIdx.x == 64) asm volatile("prefetch.tensormap [%0];" :: "l"(&mw1) : "memory");
    if (threadIdx.x == 96) asm volatile("prefetch.tensormap [%0];" :: "l"(&mw3) : "memory");
    extern __shared__ __align__(1024) uint8_t smem_raw[];
    const uint32_t sb = __shfl_sync(0xffffffffu, smem_u32(smem_raw), 0);
    if ((sb & 0xFFFFFF) != SMEM_BASE) __trap();
    const uint32_t bars = sb + OFF_BAR, ring = sb + OFF_RING;
    const int tid = threadIdx.x, lane = tid & 31, g = lane >> 2, t4 = lane & 3;
    const int warp = __shfl_sync(0xffffffffu, tid >> 5, 0), wg = warp >> 2, wq = warp & 3;
    const int rank = blockIdx.x & 1, cl = blockIdx.x >> 1;
    const int grp = cl < 4 ? 4 + cl : cl < 36 ? (cl - 4) >> 3 : 4 + (cl - 36) / 7;
    const int rot = cl < 4 ? 7 : cl < 36 ? (cl - 4) & 7 : (cl - 36) % 7;
    const int mblk = rot * 2 + rank;
    const int nq = grp < 4 ? 2 : 1;
    const int qt0 = grp < 4 ? 2 * grp - 1 : 3 + grp;
    const int gu0 = grp < 4 ? 2 * grp : 3 * grp - 4;
    auto is_qkv = [&](int t) { return (unsigned)(t - 1) < (unsigned)nq; };
    auto unit_of = [&](int t) { return t == 4 ? 20 + grp : t ? gu0 + t - nq : gu0; };
    const int lid = blockIdx.x;
    const int head = lid >> 2, qb = lid & 3;
    const int cb = lid & 7, rb0 = (lid >> 5) * 8 + ((lid >> 3) & 3);

    const __nv_bfloat16* pf = wq == 2 ? x + (size_t)(mblk * 128 + grp * 16 + (lane >> 1)) * DM + (lane & 1) * 64
                                      : ((lane & 1) ? w3 : w1) + (size_t)(mblk * 8 + ((lane >> 1) & 7)) * FF + gu0 * 64;
    if (warp >= 18) asm volatile("prefetch.global.L2 [%0];" :: "l"(pf) : "memory");
    if (elect_one()) {
        const uint32_t b0 = bars + (warp < 16 ? warp * 40 : warp * 80 - 640), cnt = warp < 8 || warp > 17 ? 1 : warp == 17 ? 2 : 8;
#pragma unroll
        for (int i = 0; i < 5; i++) mbar_init(b0 + 8 * i, cnt);
        if (warp == 0) {
            fence_async_smem();
#pragma unroll
            for (int j = 0; j < 2; j++) {
                tma2d(sb + j * 16384, &mx, j * 64, mblk * 128, bars + 8 * (B_FULL + j));
                tma2d(ring + j * 16384, &mw1, gu0 * 64, j * 64, bars + 8 * (B_FULL + j));
                tma2d(ring + j * 16384 + 8192, &mw3, gu0 * 64, j * 64, bars + 8 * (B_FULL + j));
            }
            TSTAMP(46);
#pragma unroll
            for (int j = 2; j < NEARLY; j++) tma2d(sb + j * 16384, &mx, j * 64, mblk * 128, bars + 8 * (B_FULL + j));
        }
        if (warp < 8) {
#pragma unroll
            for (int i = 0; i < 5; i++) mbar_expect(b0 + 8 * i, warp * 5 + i < 8 ? 32768 : 16384);
        } else if (warp >= 16) {
#pragma unroll
            for (int i = 5; i < 10; i++) mbar_init(b0 + 8 * i, cnt);
            if (warp == 16) asm volatile("prefetch.tensormap [%0];" :: "l"(&mqkv) : "memory");
        }
        asm volatile("fence.mbarrier_init.release.cluster;" ::: "memory");
    }
    if (warp >= 18) asm volatile("prefetch.global.L2 [%0];" :: "l"(pf + (wq == 2 ? 128 : 128 * FF)) : "memory");
    __syncthreads();
    if (tid == 512) TSTAMP(26);
    asm volatile("barrier.cluster.arrive.relaxed.aligned;" ::: "memory");

    if (wg < 4) {
        const int pair = (wg >> 1) ^ 1, half = wg & 1, w8 = warp & 7;
        if (pair == 1) {
            const int row = mblk * 128 + grp * 16 + w8 * 2 + (lane >> 4);
            uint4 v[6];
            const uint32_t* w = reinterpret_cast<const uint32_t*>(v);
#pragma unroll
            for (int j = 0; j < 2; j++) v[4 + j] = __ldg(reinterpret_cast<const uint4*>((rank ? w3 : w1) + (size_t)(rot * 64 + w8 * 8 + j * 4 + (lane >> 3)) * FF + gu0 * 64) + (lane & 7));
#pragma unroll
            for (int j = 0; j < 4; j++) v[j] = __ldg(reinterpret_cast<const uint4*>(x + (size_t)row * DM) + j * 16 + (lane & 15));
            const uint32_t tag = ld_epoch() + 1;
            float c[8];
#pragma unroll
            for (int e = 0; e < 4; e++) { c[2 * e] = bf_lo(w[16 + e]) + bf_lo(w[20 + e]); c[2 * e + 1] = bf_hi(w[16 + e]) + bf_hi(w[20 + e]); }
#pragma unroll
            for (int n = 4; n > 1; n >>= 1) {
                const bool up = lane & (4 * n);
#pragma unroll
                for (int e = 0; e < n; e++) c[e] = (up ? c[e + n] : c[e]) + __shfl_xor_sync(0xffffffffu, up ? c[e] : c[e + n], 4 * n);
            }
            asm volatile("st.shared.v2.f32 [%0], {%1,%2};" :: "r"(sb + OFF_CS + 512 + w8 * 256 + (lane & 7) * 32 + (lane >> 3) * 8), "f"(c[0]), "f"(c[1]) : "memory");
            bar_sync(6, 256);
            if (w8 < 2) {
#pragma unroll
                for (int e = 0; e < 8; e++) asm volatile("ld.shared.f32 %0, [%1];" : "=f"(c[e]) : "r"(sb + OFF_CS + 512 + e * 256 + (tid & 63) * 4));
                st_tagged(reinterpret_cast<unsigned long long*>(g_cs) + (grp * 40 + rot) * 128 + rank * 64 + (tid & 63),
                          __float_as_uint(((c[0] + c[1]) + (c[2] + c[3])) + ((c[4] + c[5]) + (c[6] + c[7]))), tag);
                if ((tid & 255) == 0) TSTAMP(40);
            }
            float sa[4] = {0.f, 0.f, 0.f, 0.f}, sq[4] = {0.f, 0.f, 0.f, 0.f};
#pragma unroll
            for (int j = 0; j < 16; j++) sa[j & 3] += bf_lo(w[j]) + bf_hi(w[j]);
            float mean = ((sa[0] + sa[1]) + (sa[2] + sa[3])) * (1.0f / 32);
#pragma unroll
            for (int j = 0; j < 16; j++) { const float a = bf_lo(w[j]) - mean, b = bf_hi(w[j]) - mean; sq[j & 1] = fmaf(a, a, sq[j & 1]); sq[2 + (j & 1)] = fmaf(b, b, sq[2 + (j & 1)]); }
            float m2 = (sq[0] + sq[1]) + (sq[2] + sq[3]);
#pragma unroll
            for (int d = 1; d < 16; d <<= 1) {
                const float om = __shfl_xor_sync(0xffffffffu, mean, d), o2 = __shfl_xor_sync(0xffffffffu, m2, d), dm = mean - om;
                m2 = fmaf(dm * dm, 16.0f * d, m2 + o2); mean = 0.5f * (mean + om);
            }
            float sd;
            asm("sqrt.approx.f32 %0, %1;" : "=f"(sd) : "f"(bf_round(bf_round(m2 * (1.0f / DM)) + 1e-5f)));
            if ((lane & 15) == 0) st_tagged(reinterpret_cast<unsigned long long*>(g_rs) + row, pack_bf16(mean, sd), tag);
            if ((tid & 255) == 0) TSTAMP(45);
        }

        uint32_t q[4], qn[4];
        {
            const int rowblk = mblk * 2 + half, tile16 = rowblk * 4 + wq;
            uint32_t empty;
            asm("mapa.shared::cluster.u32 %0, %1, %2;" : "=r"(empty) : "r"(bars + 8 * B_EMPTY), "r"(wq & 1));
#pragma unroll 1
            for (int t = pair; t < 5; t += 2) {
                float acc[64];
                uint32_t full = bars + 8 * (B_FULL + 8 * t), rel = empty + 64 * t;
                uint32_t stepa = t == 4 ? 0x4AB93AC : 0x9999999, stepb = (uint32_t)(0x994999949999ull >> (4 * ((0x24130u >> (4 * t)) & 7)));
                uint64_t da = mkdesc(half * 8192, 16, 1024, 1), db = mkdesc(OFF_RING, 8192, 1024, 1) + ((0x24130u >> (4 * t)) & 7) * 1024;
                if ((tid & 255) == 0 && t == 0) TSTAMP(30);
                mbar_wait(full, 0);
                if ((tid & 255) == 0 && t == 0) TSTAMP(1);
                if (t > 0) mbar_wait(full + 8 * (B_EMPTY - ORD_LAG), 0);
                wg_fence();
                wgmma_ss_n128_zero(acc, da, db);
#pragma unroll
                for (int k = 1; k < 4; k++) wgmma_ss_n128_acc(acc, da + k * 2, db + k * 128);
                wg_commit();
                mbar_wait(full + 8, 0);
#pragma unroll 1
                do {
                    da += (int)((stepa & 15) << 10) - 8192; db += (int)((stepb & 15) << 10) - 8192;
                    stepa >>= 4; stepb >>= 4;
                    wg_fence();
#pragma unroll
                    for (int k = 0; k < 4; k++) wgmma_ss_n128_acc(acc, da + k * 2, db + k * 128);
                    wg_commit();
                    mbar_wait(full + 16, 0);
                    wg_wait<1>();
                    if (elect_one()) mbar_arrive_remote(rel);
                    full += 8; rel += 8;
                } while (stepa);
                auto fetch_q = [&]() {
                    mbar_wait(bars + 8 * B_QKV, 0);
                    const uint4* pq = g_q + (head * 128 + (qb * 8 + wg) * 4 + wq) * 32 + lane;
                    const uint4 v = __ldcg(pq), u = __ldcg(pq + 512);
                    q[0] = v.x; q[1] = v.y; q[2] = v.z; q[3] = v.w; qn[0] = u.x; qn[1] = u.y; qn[2] = u.z; qn[3] = u.w;
                };
                if (t == 4) fetch_q();
                wg_wait<0>();
                if (elect_one()) mbar_arrive_remote(rel);
                pin<64>(acc);
                if (wq == 0 && half == 0 && lane == 0) TSTAMP(2 + 2 * t);
                if ((tid & 255) == 0 && t == 4) GSTAMP(10);
                mbar_wait(bars + 8 * (B_STATS + t), 0);
                uint32_t rs0, rs1;
                asm volatile("ld.shared.b32 %0, [%1];" : "=r"(rs0) : "r"(sb + OFF_RS + (half * 64 + wq * 16 + g) * 4));
                asm volatile("ld.shared.b32 %0, [%1];" : "=r"(rs1) : "r"(sb + OFF_RS + (half * 64 + wq * 16 + g + 8) * 4));
                const float m0 = bf_lo(rs0), m1 = bf_lo(rs1);
                float d0 = bf_hi(rs0), d1 = bf_hi(rs1);
                float r0 = rcpf(d0), r1 = rcpf(d1);
                const uint32_t pcs = sb + OFF_CS + t * 512 + t4 * 8;
                auto lds2 = [&](int j, float* c) { asm volatile("ld.shared.v2.f32 {%0,%1}, [%2];" : "=f"(c[0]), "=f"(c[1]) : "r"(pcs + j * 32) : "memory"); };
                auto fix = [&](float* a, const float* c) { a[0] = fmaf(-m0, c[0], a[0]); a[1] = fmaf(-m0, c[1], a[1]); a[2] = fmaf(-m1, c[0], a[2]); a[3] = fmaf(-m1, c[1], a[3]); };
                float c[2][4];
                if (is_qkv(t)) {
                    const int qt = qt0 + t;
                    if (qt < 4) {
                        r0 *= 0.25f * 1.4426950408889634f * M71; r1 *= 0.25f * 1.4426950408889634f * M71;
                    } else if (qt < 8) {
                        r0 *= ((FIXED_MASK >> (2 * wq)) & 1) ? M71 : P71; r1 *= ((FIXED_MASK >> (2 * wq + 1)) & 1) ? M71 : P71;
                    }
                    uint8_t* p = qt < 4 ? reinterpret_cast<uint8_t*>(g_q + (qt * 1024 + tile16) * 32 + lane)
                                        : reinterpret_cast<uint8_t*>(g_kv + (qt - 4) * 32768) + tile16 * 256 + lane * 4;
                    lds2(0, c[0]); lds2(1, c[0] + 2);
#pragma unroll
                    for (int hh = 0; hh < 8; hh++) {
                        if (hh < 7) { lds2(2 * hh + 2, c[~hh & 1]); lds2(2 * hh + 3, c[~hh & 1] + 2); }
                        float* a = acc + hh * 8;
                        fix(a, c[hh & 1]); fix(a + 4, c[hh & 1] + 2);
                        asm volatile("{\n.reg .pred p;\nsetp.lt.s32 p, %5, 4;\n@p st.global.v4.b32 [%0], {%1,%2,%3,%4};\n"
                                     "@!p st.global.b32 [%0], %1;\n@!p st.global.b32 [%0+128], %2;\n@!p st.global.b32 [%0+32768], %3;\n@!p st.global.b32 [%0+32896], %4;\n}"
                                     :: "l"(p + hh * 65536), "r"(pack_bf16(a[0] * r0, a[1] * r0)), "r"(pack_bf16(a[2] * r1, a[3] * r1)),
                                        "r"(pack_bf16(a[4] * r0, a[5] * r0)), "r"(pack_bf16(a[6] * r1, a[7] * r1)), "r"(qt) : "memory");
                    }
                } else {
                    uint32_t* p = reinterpret_cast<uint32_t*>(g_h + ((((rowblk >> 3) * 4 + (rowblk & 3)) * 28 + unit_of(t)) * 2 + ((rowblk >> 2) & 1)) * 512) + wq * 512 + lane;
                    r0 *= -1.4426950408889634f; r1 *= -1.4426950408889634f; d0 *= d0; d1 *= d1;
                    lds2(0, c[0]); lds2(8, c[0] + 2);
#pragma unroll
                    for (int j = 0; j < 8; j++) {
                        if (j < 7) { lds2(j + 1, c[~j & 1]); lds2(j + 9, c[~j & 1] + 2); }
                        float* a = acc + j * 4; float* b = a + 32;
                        fix(a, c[j & 1]); fix(b, c[j & 1] + 2);
                        p[j * 32] = pack_bf16(a[0] * b[0] * rcpf(fmaf(ex2f(a[0] * r0), d0, d0)), a[1] * b[1] * rcpf(fmaf(ex2f(a[1] * r0), d0, d0)));
                        p[256 + j * 32] = pack_bf16(a[2] * b[2] * rcpf(fmaf(ex2f(a[2] * r1), d1, d1)), a[3] * b[3] * rcpf(fmaf(ex2f(a[3] * r1), d1, d1)));
                    }
                }
                __syncwarp();
                if (elect_one()) mbar_arrive(bars + 8 * (B_TILE + t));
                if (t == 3) fetch_q();
                if (wq == 0 && half == 0 && lane == 0) TSTAMP(3 + 2 * t);
            }
        }
        const uint64_t db2 = mkdesc(OFF_B2, 128, 256, 0) - (sb >> 28);
        uint32_t q2[4];
        uint4 v[8];
        const uint4* osrc = g_o + (rb0 + 4) * 4096 + (warp >> 1) * 512 + (warp & 1) * 32 + lane;
        auto poll_o = [&](uint32_t pend) {
#pragma unroll
            for (int i = 0; i < 8; i++) {
                if (pend >> i & 1)
                    asm volatile("ld.relaxed.gpu.global.v4.u32 {%0,%1,%2,%3}, [%4];" : "=r"(v[i].x), "=r"(v[i].y), "=r"(v[i].z), "=r"(v[i].w) : "l"(osrc + i * 64) : "memory");
            }
        };
        uint32_t* po = reinterpret_cast<uint32_t*>(g_o + ((qb * 8 + wg) * 8 + (head >> 2)) * 512) + wq * 512 + (head & 3) * 64 + lane;
        bool redo = false;
        mbar_wait(bars + 8 * B_KV, 0);
#pragma unroll 1
        for (int round = 0; round < 2;) {
            float s[32];
            float mq[2];
            if (!redo) {
                wg_fence();
                wgmma_rs_n40_zero(s, q, mkdesc(4096, 94208, 128, 0));
                wg_commit();
                wg_wait<0>();
                pin<20>(s);
#pragma unroll
                for (int r = 0; r < 2; r++) {
                    int m = max(__float_as_int(s[2 * r]), __float_as_int(s[2 * r + 1]));
#pragma unroll
                    for (int i = 1; i < 5; i++) m = __vimax3_s32(m, __float_as_int(s[4 * i + 2 * r]), __float_as_int(s[4 * i + 2 * r + 1]));
                    mq[r] = __int_as_float(m & ~3) * (-0.25f * P71);
                }
            } else {
                float m0 = -INFINITY, m1 = -INFINITY, f0 = -INFINITY, f1 = -INFINITY;
#pragma unroll 1
                for (int t = 0; t < 32; t++) {
                    wg_fence();
                    wgmma_rs_n64_zero(s, q, mkdesc(4096, 94208, 128, 0) + (t >> 2) * DK_STEP + (t & 3) * 64);
                    wg_commit();
                    wg_wait<0>();
                    pin<32>(s);
#pragma unroll
                    for (int i = 0; i < 8; i++) {
                        if ((FIXED_MASK >> i) & 1) { f0 = fmaxf(f0, fmaxf(s[4 * i], s[4 * i + 1])); f1 = fmaxf(f1, fmaxf(s[4 * i + 2], s[4 * i + 3])); }
                        else                       { m0 = fmaxf(m0, fmaxf(s[4 * i], s[4 * i + 1])); m1 = fmaxf(m1, fmaxf(s[4 * i + 2], s[4 * i + 3])); }
                    }
                }
                m0 = fmaxf(m0, f0 * P71 * P71); m1 = fmaxf(m1, f1 * P71 * P71);
                m0 = fmaxf(m0, __shfl_xor_sync(0xffffffffu, m0, 1)); m1 = fmaxf(m1, __shfl_xor_sync(0xffffffffu, m1, 1));
                m0 = fmaxf(m0, __shfl_xor_sync(0xffffffffu, m0, 2)); m1 = fmaxf(m1, __shfl_xor_sync(0xffffffffu, m1, 2));
                mq[0] = (floorf(m0) - 64.f) * (-0.25f * M71); mq[1] = (floorf(m1) - 64.f) * (-0.25f * M71);
            }
#pragma unroll
            for (int r = 0; r < 2; r++) {
                const float r1 = mq[r] - bf_hi(__float_as_uint(mq[r])), r2 = r1 - bf_hi(__float_as_uint(r1));
                q2[r] = __byte_perm(__float_as_uint(mq[r]), __float_as_uint(r1), 0x7632);
                q2[2 + r] = __byte_perm(__float_as_uint(r2), __float_as_uint(M71), 0x7632);
            }
            float o[12]; uint32_t p[16];
#pragma unroll
            for (int i = 0; i < 12; i++) o[i] = 0.f;
            pin<12>(o); pin<4>(q2);
            if (wq == 0 && half == 0 && lane == 0) TSTAMP(12 + 4 * round + pair);
            uint64_t dk = mkdesc(4096, 94208, 128, 0), dv = mkdesc(0, 128, 65536, 0);
#pragma unroll 1
            for (int c = 0; c < 8; c += UNR / 4, dk += UNR / 4 * DK_STEP, dv += UNR / 4 * DV_STEP) {
                if (round == 0) {
#pragma unroll
                    for (int i = 0; i < UNR / 4; i++) mbar_wait(bars + 8 * (B_KV + c + i), 0);
                } else if (c == 8 - UNR / 4) mbar_wait(bars + 8 * B_T1, 0);
#pragma unroll
                for (int t = 0; t < UNR; t++) {
                    wg_fence();
                    wgmma_rs_n64_zero(s, q, dk + (t >> 2) * DK_STEP + (t & 3) * 64);
                    wgmma_rs_n64_acc(s, q2, db2);
                    wg_commit();
                    wg_wait<0>();
                    pin<32>(s); pin<16>(p);
#pragma unroll
                    for (int i = 0; i < 16; i++) {
                        if ((FIXED_MASK >> (i >> 1)) & 1) p[i] = exp2_fixed(s[2 * i], s[2 * i + 1], half2);
                        else                              p[i] = pack_bf16(ex2f(s[2 * i]), ex2f(s[2 * i + 1]));
                    }
                    wg_fence();
#pragma unroll
                    for (int k = 0; k < 4; k++) wgmma_rs_n24_acc(o, p + 4 * k, dv + (t >> 2) * DV_STEP + ((t & 3) * 4 + k) * 16);
                    wg_commit();
                }
            }
            wg_wait<0>();
            pin<12>(o);
            const float r0 = rcpf(o[8]), r1 = rcpf(o[10]);
#pragma unroll
            for (int i = 0; i < 8; i++) o[i] *= (i & 2) ? r1 : r0;
            if (!redo) {
                const float chk = fmaf(o[0], o[1], fmaf(o[2], o[3], o[8] * 4.f)) + fmaf(o[4], o[5], fmaf(o[6], o[7], o[10] * 4.f));
                uint32_t bad;
                asm volatile("{\n.reg .pred p, q;\nsetp.geu.f32 q, %1, 0f7F800000;\nbar.red.or.pred p, %2, 128, q;\nselp.u32 %0, 1, 0, p;\n}" : "=r"(bad) : "f"(fabsf(chk)), "r"(1 + wg) : "memory");
                if (__any_sync(0xffffffffu, bad)) { redo = true; continue; }
            }
            st_relaxed(po, pack_bf16(o[0], o[1])); st_relaxed(po + 256, pack_bf16(o[2], o[3]));
            st_relaxed(po + 32, pack_bf16(o[4], o[5])); st_relaxed(po + 288, pack_bf16(o[6], o[7]));
            if (round == 0) {
                po += 4 * 8 * 2048;
                st_relaxed(po, ~0u); st_relaxed(po + 256, ~0u); st_relaxed(po + 32, ~0u); st_relaxed(po + 288, ~0u);
            }
            __syncwarp();
            if (elect_one()) mbar_arrive(bars + 8 * (B_OW + 2 * round + (wg >> 1)));
#pragma unroll
            for (int i = 0; i < 4; i++) q[i] = qn[i];
            redo = false;
            if (wq == 0 && half == 0 && lane == 0) TSTAMP(14 + 4 * round + pair);
            if (wq == 0 && lane == 0) GSTAMP(round * 4 + wg);
            round++;
        }
        if (lane == 0) TS3(1, warp);
        poll_o(0xFF);
        bool dead = false;
#pragma unroll 1
        for (int n = 0; n < 2000000; n++) {
            dead = __all_sync(0xffffffffu, mbar_test(bars + 8 * B_DONE) & mbar_test(bars + 8 * (B_DONE + 1)));
            uint32_t bad = 0;
#pragma unroll
            for (int i = 0; i < 8; i++) bad |= (__vimax3_u32(max(v[i].x, v[i].y), v[i].z, v[i].w) == ~0u) << i;
            bad = __reduce_or_sync(0xffffffffu, bad);
            if (!bad) break;
            poll_o(bad);
        }
        if (lane == 0) TS3(2, warp);
        if (!dead) { mbar_wait(bars + 8 * B_DONE, 0); mbar_wait(bars + 8 * (B_DONE + 1), 0); }
#pragma unroll
        for (int i = 0; i < 8; i++)
            asm volatile("st.shared.v4.b32 [%0], {%1,%2,%3,%4};" :: "r"(sb + (warp >> 1) * 8192 + (warp & 1) * 512 + i * 1024 + lane * 16), "r"(v[i].x), "r"(v[i].y), "r"(v[i].z), "r"(v[i].w) : "memory");
        if (lane == 0) TS3(2, 16 + warp);
        fence_async_smem();
        __syncwarp();
        if (elect_one()) mbar_arrive(bars + 8 * (B_O2 + (warp >> 1)));
        if (lane == 0) TS3(2, 32 + warp);
        if (tid == 0) TSTAMP(24);
        if (lane == 0) GSTAMP(16 + warp);
    } else {
        uint32_t tag;
        if (wq == 0) {
            asm volatile("barrier.cluster.wait.aligned;" ::: "memory");
            if (tid == 512) TSTAMP(27);
            uint32_t slot = 2;
#pragma unroll 1
            for (int n = 2; n < 40; n++) {
                const int t = n >> 3, j = n & 7;
                const int kc = (n < 32 ? j : (POS_LAST >> (4 * j)) & 7) * 64;
                const CUtensorMap* m = is_qkv(t) ? &mqkv : rank ? &mw3 : &mw1;
                const int col = is_qkv(t) ? (qt0 + t) * 128 + rank * 64 : unit_of(t) * 64;
                const uint32_t dst = ring + slot * 16384 + rank * 8192, fb = bars + 8 * (B_FULL + n);
                if (n >= NEARLY && n < 8 && elect_one()) tma2d(sb + n * 16384, &mx, kc, mblk * 128, fb);
                if (n >= NRING) mbar_wait(fb + 8 * (B_EMPTY - NRING), 0);
                if (elect_one()) {
                    tma2d_mc(dst, m, col, kc, fb); }
                if (++slot == NRING) slot = 0;
            }
            tag = ld_epoch() + 1;
            wait_cnt(C_H + (rb0 >> 1), 20 * tag, 100);
            wait_cnt(C_H + (rb0 >> 1) + 2, 20 * tag, 100);
            fence_async_all();
        } else if (wq == 1) {
            tag = ld_epoch() + 1;
            mbar_wait(bars + 8 * (B_FULL + G0_LAG), 0);
#pragma unroll 1
            for (int t = 0; t < 5; t++) {
                float a[4];
#pragma unroll 1
                for (int n = 0; n < 2000000; n++) {
                    uint32_t stale = 0;
                    a[0] = a[1] = a[2] = a[3] = 0.f;
#pragma unroll
                    for (int i = 0; i < 16; i++) {
                        uint32_t u, v;
                        stale |= ld_tagged2(g_cs + (grp * 5 + t) * 512 + i * 32 + lane, tag, u, v);
                        a[(i & 1) * 2] += __uint_as_float(u); a[(i & 1) * 2 + 1] += __uint_as_float(v);
                    }
                    if (__all_sync(0xffffffffu, stale == 0)) break;
                    if (t) __nanosleep(400);
                }
                asm volatile("st.shared.v2.f32 [%0], {%1,%2};" :: "r"(sb + OFF_CS + t * 512 + lane * 8), "f"(a[0]), "f"(a[1]) : "memory");
                asm volatile("st.shared.v2.f32 [%0], {%1,%2};" :: "r"(sb + OFF_CS + t * 512 + 256 + lane * 8), "f"(a[2]), "f"(a[3]) : "memory");
                if (t == 0) {
                    uint32_t r[4];
#pragma unroll 1
                    for (int n = 0; n < 2000000; n++) {
                        const uint32_t stale = ld_tagged2(g_rs + mblk * 64 + lane * 2, tag, r[0], r[1]) | ld_tagged2(g_rs + mblk * 64 + lane * 2 + 1, tag, r[2], r[3]);
                        if (__all_sync(0xffffffffu, stale == 0)) break;
                    }
                    asm volatile("st.shared.v4.b32 [%0], {%1,%2,%3,%4};" :: "r"(sb + OFF_RS + lane * 16), "r"(r[0]), "r"(r[1]), "r"(r[2]), "r"(r[3]) : "memory");
                }
                __syncwarp();
                if (elect_one()) { mbar_arrive(bars + 8 * (B_STATS + t)); TSTAMP(32 + t); }
            }
        } else {
            asm volatile("prefetch.global.L2 [%0];" :: "l"(pf + 2 * (wq == 2 ? 128 : 128 * FF)) : "memory");
            tag = ld_epoch() + 1;
            mbar_wait(bars + 8 * (B_FULL + wq + CS_LAG), 0);
#pragma unroll 1
            for (int t = wq - 1; t < 5; t += 2) {
                const __nv_bfloat16* src; int ld;
                if (is_qkv(t)) { src = wqkv + (qt0 + t) * 128 + rank * 64; ld = 3 * DM; }
                else        { src = (rank ? w3 : w1) + unit_of(t) * 64; ld = FF; }
                src += (size_t)(rot * 64 + (lane >> 3)) * ld + (lane & 7) * 8;
                uint4 v[16];
                const uint32_t* w = reinterpret_cast<const uint32_t*>(v);
#pragma unroll
                for (int j = 0; j < 16; j++) v[j] = __ldg(reinterpret_cast<const uint4*>(src + (size_t)j * 4 * ld));
                float c[8];
#pragma unroll
                for (int e = 0; e < 4; e++) {
                    float a = 0.f, b = 0.f;
#pragma unroll
                    for (int j = 0; j < 16; j++) { a += bf_lo(w[4 * j + e]); b += bf_hi(w[4 * j + e]); }
                    c[2 * e] = a; c[2 * e + 1] = b;
                }
#pragma unroll
                for (int n = 4; n > 1; n >>= 1) {
                    const bool up = lane & (4 * n);
#pragma unroll
                    for (int e = 0; e < n; e++) c[e] = (up ? c[e + n] : c[e]) + __shfl_xor_sync(0xffffffffu, up ? c[e] : c[e + n], 4 * n);
                }
                unsigned long long* dst = reinterpret_cast<unsigned long long*>(g_cs) + ((grp * 5 + t) * 8 + rot) * 128 + rank * 64 + (lane & 7) * 8 + (lane >> 3) * 2;
                st_tagged(dst, __float_as_uint(c[0]), tag); st_tagged(dst + 1, __float_as_uint(c[1]), tag);
                if (lane == 0) TSTAMP(40 + t);
            }
        }
        if (wq == 3) {
#pragma unroll 1
            for (int i = lane; i < 256; i += 32) asm volatile("st.shared.v4.b32 [%0], {%1,%1,%1,%1};" :: "r"(sb + OFF_ONES + i * 16), "r"(0x3F803F80u) : "memory");
#pragma unroll 1
            for (int i = lane; i < 128; i += 32) {
                const bool fx = (FIXED_MASK >> (i >> 4)) & 1;
                const float sc = fx ? M71 : P71;
                uint32_t a = pack_bf16(sc, sc), b = a, c = a;
                if (i & 8) { a = pack_bf16(sc, fx ? 27.0f * M71 : -99.5f * P71); b = pack_bf16(sc, fx ? 0.f : 0.08214f * P71); c = pack_bf16(sc, 0.f); }
                asm volatile("st.shared.v4.b32 [%0], {%1,%2,%3,%4};" :: "r"(sb + OFF_B2 + i * 16), "r"(a), "r"(b), "r"(c), "r"(c) : "memory");
            }
            if (elect_one()) {
#pragma unroll 1
                for (int i = 0; i < 28; i++) { mbar_init(bars + 8 * (B_DN + i), 1); mbar_expect(bars + 8 * (B_DN + i), 24576); }
                mbar_expect(bars + 8 * B_WO, 65536);
#pragma unroll 1
                for (int i = 0; i < 4; i++) mbar_expect(bars + 8 * (B_O + i), 16384);
            }
            fence_async_smem();
            __syncwarp();
            if (elect_one()) mbar_arrive(bars + 8 * B_QKV);
        } else if (wq == 1) {
#pragma unroll 1
            for (int i = 0; i < 3; i++) wait_cnt(C_QKV + i * 4 + (head >> 3), 16 * tag, 100);
            fence_async_all();
            if (elect_one()) { mbar_arrive(bars + 8 * B_QKV); TSTAMP(29); }
            mbar_wait(bars + 8 * (B_EMPTY + 31), 0);
            const uint8_t* gk = reinterpret_cast<const uint8_t*>(g_kv + head * 4096);
            const uint8_t* gv = reinterpret_cast<const uint8_t*>(g_kv + (32 + head) * 4096);
#pragma unroll 1
            for (int c = 0; c < 8; c++) {
                mbar_wait(bars + 8 * (B_EMPTY + 34 + (c & 4) + ((c >> 1) & 1)), 0);
                if (elect_one()) {
                    const uint32_t b = bars + 8 * (B_KV + c);
                    mbar_expect(b, 16384);
                    bulk_load(sb + (2 * c + 1) * 4096, gk + c * 4096, 4096, b);
                    bulk_load(sb + 2 * c * 4096, gv + c * 4096, 4096, b);
                    bulk_load(sb + 65536 + c * 4096, gv + 32768 + c * 4096, 4096, b);
                    bulk_load(sb + 98304 + c * 4096, gk + 32768 + c * 4096, 4096, b);
                }
            }
        } else if (wq == 2) {
#pragma unroll 1
            for (int t = 0; t < 4; t++) {
                mbar_wait(bars + 8 * (B_TILE + t), 0);
                if (elect_one()) signal_cnt(is_qkv(t) ? C_QKV + qt0 + t : C_H + mblk);
            }
        }
        pin<1>(&tag);
        bar_sync(5, 128);
        if (tid == 639) g_epoch[blockIdx.x] = tag;
        uint32_t gate[2][16];
        {
            float dn[64];
#pragma unroll
            for (int i = 0; i < 64; i++) dn[i] = 0.f;
            pin<64>(dn);
            const uint4* hsrc = g_h + (lid >> 3) * 28 * 1024;
            const int wcol = cb * 64;
            uint32_t nb = bars + 8 * B_DN, kc = 0;
            auto load_stage = [&](int slot) {
                const uint32_t dst = ring + slot * 24576;
                if (wq == 0) { if (elect_one()) bulk_load(dst, hsrc, 16384, nb); }
                if (wq == 1) { if (elect_one()) tma2d(dst + 16384, &mw2, wcol, kc, nb); }
                hsrc += 1024; kc += 64; nb += 8;
            };
            auto mma_stage = [&](int slot) {
                mbar_wait(nb - 16, 0);
#pragma unroll
                for (int k = 0; k < 4 * BG_SPLIT; k++) {
                    if (k % BG_GRP == 0) wg_fence();
                    const uint64_t dw = mkdesc(OFF_RING + 16384 + slot * 24576, 8192, 1024, 1) + k / BG_SPLIT * 128, dh = mkdesc(OFF_RING + slot * 24576, 128, 1024, 0) + k / BG_SPLIT * 16;
                    if (BG_SPLIT == 1) wgmma_ts_n128_acc(dn, dw, dh); else wgmma_ts_n64_acc(dn + (k & 1) * 32, dw, dh + (k & 1) * 512);
                    if (k % BG_GRP == BG_GRP - 1) { wg_commit(); wg_wait<BG_WAIT>(); }
                }
            };
            auto publish = [&]() { if (wq == 2) { mbar_wait(bars + 8 * (B_TILE + 4), 0); if (elect_one()) signal_cnt(C_H2 + mblk); } };
            auto collect = [&]() { if (wq == 0) { wait_cnt(C_H2 + (rb0 >> 1), 8 * tag, 100); wait_cnt(C_H2 + (rb0 >> 1) + 2, 8 * tag, 100); fence_async_all(); } };
            if (tid == 512) TSTAMP(20);
            load_stage(0); load_stage(1);
#pragma unroll 1
            for (int it = 0; it < 9; it++) {
                if (it == SIG_IT) publish();
                if (it == 6) collect();
                mma_stage(0); load_stage(2);
                mma_stage(1); load_stage(0);
                mma_stage(2); if (it < 8) load_stage(1); else nb += 8;
            }
            mma_stage(0);
            wg_wait<0>();
            pin<64>(dn);
            if (wq == 1 && elect_one()) {
#pragma unroll 1
                for (int i = 0; i < 8; i++) tma2d(ring + i * 8192, &mwo, cb * 64, i * 64, bars + 8 * B_WO);
            }
#pragma unroll
            for (int i = 0; i < 32; i++) gate[i >> 4][i & 15] = pack_bf16(siluf(dn[2 * i]), siluf(dn[2 * i + 1]));
        }
        if (tid == 512) TSTAMP(21);
        if (wq >= 2) {
            mbar_wait(bars + 8 * (B_OW + wq - 2), 0);
            if (elect_one()) {
                signal_cnt(C_O + qb * 8 + 2 * wq - 4);
                asm volatile("red.relaxed.gpu.global.add.u32 [%0], 1;" :: "l"(g_cnt + (C_O + qb * 8 + 2 * wq - 3) * 8) : "memory");
            }
        }
#pragma unroll 1
        for (int tl = 0; tl < 2; tl++) {
            const int rb = rb0 + 4 * tl;
            const size_t goff = (size_t)(rb * 64 + wq * 16 + (lane >> 3)) * (DM / 8) + cb * 8 + (lane & 7);
            uint4 xr[4];
#pragma unroll
            for (int i = 0; i < 4; i++) xr[i] = __ldg(reinterpret_cast<const uint4*>(x) + goff + i * 4 * (DM / 8));
            float acc[32];
#pragma unroll
            for (int i = 0; i < 32; i++) acc[i] = 0.f;
            pin<32>(acc);
            uint64_t dw = mkdesc(OFF_RING, 8192, 1024, 1);
            if (tl == 0) {
                if (wq == 0) {
                    wait_cnt(C_O + rb, 32 * tag, 200);
                    fence_async_all();
                    if (elect_one()) { mbar_arrive(bars + 8 * B_T1); TSTAMP(22); }
                }
                mbar_wait(bars + 8 * B_WO, 0);
#pragma unroll 1
                for (int i = 0; i < 4; i++, dw += 1024) {
                    if (wq == 0 && elect_one()) bulk_load(ring + 65536, g_o + (rb * 4 + i) * 1024, 16384, bars + 8 * (B_O + i));
                    mbar_wait(bars + 8 * (B_O + i), 0);
#pragma unroll
                    for (int k = 0; k < 8; k++) {
                        if (k % T1_GRP == 0) wg_fence();
                        wgmma_ts_n64_acc(acc, dw + k * 128, mkdesc(OFF_RING + 65536, 128, 1024, 0) + (k >> 2) * 512 + (k & 3) * 16);
                        if (k % T1_GRP == T1_GRP - 1) { wg_commit(); wg_wait<0>(); }
                    }
                }
            } else {
                uint64_t dx = mkdesc(0, 128, 1024, 0);
#pragma unroll 1
                for (int i = 0; i < 8; i++, dx += 512, dw += 512) {
                    mbar_wait(bars + 8 * (B_O2 + i), 0);
                    if (tid == 512) TS3(0, 48 + i);
                    wg_fence();
#pragma unroll
                    for (int k = 0; k < 4; k++) wgmma_ts_n64_acc(acc, dw + k * 128, dx + k * 16);
                    wg_commit();
                }
                wg_wait<0>();
            }
            pin<32>(acc);
            if (tid == 512) TS3(0, 56);
            const uint32_t stg = ring + 65536;
            uint32_t r[16];
#pragma unroll
            for (int i = 0; i < 16; i++) {
                asm("mul.rn.bf16x2 %0, %1, %2;" : "=r"(r[i]) : "r"(pack_bf16(acc[2 * i], acc[2 * i + 1])), "r"(gate[0][i]));
                gate[0][i] = gate[1][i];
            }
#pragma unroll
            for (int i = 0; i < 4; i++)
                asm volatile("stmatrix.sync.aligned.m8n8.x4.trans.shared.b16 [%0], {%1,%2,%3,%4};"
                             :: "r"(stg + (i * 16 + (lane >> 4) * 8 + (lane & 7)) * 128 + (((2 * wq + ((lane >> 3) & 1)) ^ (lane & 7)) << 4)),
                                "r"(r[4 * i]), "r"(r[4 * i + 1]), "r"(r[4 * i + 2]), "r"(r[4 * i + 3]) : "memory");
            bar_sync(5, 128);
#pragma unroll
            for (int i = 0; i < 4; i++) {
                const int row = wq * 16 + i * 4 + (lane >> 3);
                uint4 u;
                asm volatile("ld.shared.v4.b32 {%0,%1,%2,%3}, [%4];" : "=r"(u.x), "=r"(u.y), "=r"(u.z), "=r"(u.w) : "r"(stg + row * 128 + (((lane ^ row) & 7) << 4)) : "memory");
                asm("add.rn.bf16x2 %0, %0, %1;" : "+r"(u.x) : "r"(xr[i].x)); asm("add.rn.bf16x2 %0, %0, %1;" : "+r"(u.y) : "r"(xr[i].y));
                asm("add.rn.bf16x2 %0, %0, %1;" : "+r"(u.z) : "r"(xr[i].z)); asm("add.rn.bf16x2 %0, %0, %1;" : "+r"(u.w) : "r"(xr[i].w));
                reinterpret_cast<uint4*>(out)[goff + i * 4 * (DM / 8)] = u;
            }
            if (tid == 512) TSTAMP(23 + 2 * tl);
            if (tid == 512) GSTAMP(8 + tl);
        }
    }
}

typedef CUresult (*EncodeFn)(CUtensorMap*, CUtensorMapDataType, cuuint32_t, void*, const cuuint64_t*, const cuuint64_t*, const cuuint32_t*,
                             const cuuint32_t*, CUtensorMapInterleave, CUtensorMapSwizzle, CUtensorMapL2promotion, CUtensorMapFloatOOBfill);

void make_map(EncodeFn fn, CUtensorMap* m, const void* p, int rows, int cols, int box_rows) {
    cuuint64_t dims[2] = {(cuuint64_t)cols, (cuuint64_t)rows};
    cuuint64_t strides[1] = {(cuuint64_t)cols * 2};
    cuuint32_t box[2] = {64, (cuuint32_t)box_rows};
    cuuint32_t es[2] = {1, 1};
    fn(m, CU_TENSOR_MAP_DATA_TYPE_BFLOAT16, 2, const_cast<void*>(p), dims, strides, box, es, CU_TENSOR_MAP_INTERLEAVE_NONE,
       CU_TENSOR_MAP_SWIZZLE_128B, CU_TENSOR_MAP_L2_PROMOTION_L2_128B, CU_TENSOR_MAP_FLOAT_OOB_FILL_NONE);
}

}

extern "C" void kernel_launch(void* const* d_in, const int* in_sizes, int n_in, void* d_out, int out_size) {
    const __nv_bfloat16* x = (const __nv_bfloat16*)d_in[0];
    static EncodeFn fn = nullptr;
    if (!fn) {
        cudaDriverEntryPointQueryResult qr;
        cudaGetDriverEntryPoint("cuTensorMapEncodeTiled", (void**)&fn, cudaEnableDefault, &qr);
        cudaFuncSetAttribute(mega_kernel, cudaFuncAttributeMaxDynamicSharedMemorySize, SMEM_BYTES);
    }
    CUtensorMap mx, mqkv, mw1, mw3, mw2, mwo;
    make_map(fn, &mx, d_in[0], SEQ, DM, 128);
    make_map(fn, &mqkv, d_in[1], DM, 3 * DM, 64);
    make_map(fn, &mwo, d_in[2], DM, DM, 64);
    make_map(fn, &mw1, d_in[4], DM, FF, 64);
    make_map(fn, &mw3, d_in[5], DM, FF, 64);
    make_map(fn, &mw2, d_in[6], FF, DM, 64);
    mega_kernel<<<128, 640, SMEM_BYTES, cudaStreamPerThread>>>(x, (const __nv_bfloat16*)d_in[1], (const __nv_bfloat16*)d_in[4], (const __nv_bfloat16*)d_in[5],
                                                               (__nv_bfloat16*)d_out, mx, mqkv, mw1, mw3, mw2, mwo, 0x3F003F00u);
}
```

```cpp
#include <cuda_runtime.h>
#include <cuda_bf16.h>
#include <cuda.h>
#include <stdint.h>
#include <stddef.h>

namespace {

constexpr int SEQ = 2048, DM = 512, FF = 1792;

constexpr int C_QKV = 0, C_H = 12, C_O = 28, C_NUM = 60;
struct Scratch {
    uint4 q[32 * 128 * 32];
    uint4 kv[64 * 4096];
    uint4 o[32 * 8 * 512];
    uint4 h[32 * 28 * 512];
    ulonglong2 cs[40 * 8 * 64];
    ulonglong2 rs[SEQ / 2];
    unsigned cnt[C_NUM * 8];
    unsigned epoch[128];
};
__device__ __align__(1024) Scratch g_scratch;
#define TSTAMP(i)
#define GSTAMP(i)
#define TS3(k, i)
#define TS2(k, i)

__device__ __forceinline__ uint32_t smem_u32(const void* p) { return (uint32_t)__cvta_generic_to_shared(p); }
__device__ __forceinline__ void mbar_init(uint32_t a, int c) { asm volatile("mbarrier.init.shared::cta.b64 [%0], %1;" :: "r"(a), "r"(c)); }
__device__ __forceinline__ void mbar_expect(uint32_t a, int b) { asm volatile("mbarrier.arrive.expect_tx.shared::cta.b64 _, [%0], %1;" :: "r"(a), "r"(b) : "memory"); }
__device__ __forceinline__ void mbar_arrive(uint32_t a) { asm volatile("mbarrier.arrive.shared::cta.b64 _, [%0];" :: "r"(a) : "memory"); }
__device__ __forceinline__ void mbar_arrive_remote(uint32_t a) { asm volatile("mbarrier.arrive.shared::cluster.b64 _, [%0];" :: "r"(a) : "memory"); }
__device__ __forceinline__ bool mbar_try(uint32_t a, uint32_t ph) {
    uint32_t ok;
    asm volatile("{\n.reg .pred p;\nmbarrier.try_wait.parity.shared::cta.b64 p, [%1], %2;\nselp.u32 %0, 1, 0, p;\n}" : "=r"(ok) : "r"(a), "r"(ph) : "memory");
    return ok;
}
__device__ __forceinline__ bool mbar_test(uint32_t a) {
    uint32_t ok;
    asm volatile("{\n.reg .pred p;\nmbarrier.test_wait.parity.shared::cta.b64 p, [%1], 0;\nselp.u32 %0, 1, 0, p;\n}" : "=r"(ok) : "r"(a) : "memory");
    return ok;
}
__device__ __forceinline__ void mbar_wait(uint32_t a, uint32_t ph) {
    int n = 1 << 22;
#pragma unroll 1
    do { n = __all_sync(0xffffffffu, mbar_try(a, ph)) ? 0 : n - 1; } while (n > 0);
}
__device__ __forceinline__ bool elect_one() {
    uint32_t p;
    asm volatile("{\n.reg .pred P;\nelect.sync _|P, 0xffffffff;\nselp.u32 %0, 1, 0, P;\n}" : "=r"(p));
    return p;
}
__device__ __forceinline__ void signal_cnt(unsigned* cnt) {
    asm volatile("fence.release.gpu;\nred.relaxed.gpu.global.add.u32 [%0], 1;" :: "l"(cnt) : "memory");
}
__device__ __forceinline__ void wait_cnt(const unsigned* cnt, unsigned target, int ns) {
#pragma unroll 1
    for (int n = 0; n < 2000000; n++) {
        unsigned v;
        asm volatile("ld.relaxed.gpu.global.u32 %0, [%1];" : "=r"(v) : "l"(cnt) : "memory");
        if (__all_sync(0xffffffffu, (int)(v - target) >= 0)) break;
        __nanosleep(ns);
    }
}
__device__ __forceinline__ uint32_t ld_epoch(const Scratch* sc) {
    uint32_t e;
    asm volatile("ld.relaxed.gpu.global.u32 %0, [%1];" : "=r"(e) : "l"(sc->epoch + blockIdx.x) : "memory");
    return e;
}
__device__ __forceinline__ void st_relaxed(uint32_t* p, uint32_t v) { asm volatile("st.relaxed.gpu.global.u32 [%0], %1;" :: "l"(p), "r"(v) : "memory"); }
__device__ __forceinline__ void st_tagged(void* p, uint32_t v, uint32_t tag) {
    asm volatile("st.relaxed.gpu.global.b64 [%0], %1;" :: "l"(p), "l"((unsigned long long)tag << 32 | v) : "memory");
}
__device__ __forceinline__ uint32_t ld_tagged2(const ulonglong2* p, uint32_t tag, uint32_t& a, uint32_t& b) {
    unsigned long long u, v;
    asm volatile("ld.relaxed.gpu.global.v2.b64 {%0,%1}, [%2];" : "=l"(u), "=l"(v) : "l"(p) : "memory");
    a = (uint32_t)u; b = (uint32_t)v;
    return ((uint32_t)(u >> 32) ^ tag) | ((uint32_t)(v >> 32) ^ tag);
}
__device__ __forceinline__ void tma2d(uint32_t dst, const CUtensorMap* m, int c0, int c1, uint32_t bar) {
    asm volatile("cp.async.bulk.tensor.2d.shared::cluster.global.mbarrier::complete_tx::bytes [%0], [%1, {%3, %4}], [%2];"
                 :: "r"(dst), "l"(m), "r"(bar), "r"(c0), "r"(c1) : "memory");
}
__device__ __forceinline__ void tma2d_mc(uint32_t dst, const CUtensorMap* m, int c0, int c1, uint32_t bar) {
    asm volatile("cp.async.bulk.tensor.2d.shared::cluster.global.mbarrier::complete_tx::bytes.multicast::cluster [%0], [%1, {%3, %4}], [%2], %5;"
                 :: "r"(dst), "l"(m), "r"(bar), "r"(c0), "r"(c1), "h"((uint16_t)3) : "memory");
}
__device__ __forceinline__ void bulk_load(uint32_t dst, const void* src, int bytes, uint32_t bar) {
    asm volatile("cp.async.bulk.shared::cluster.global.mbarrier::complete_tx::bytes [%0], [%1], %2, [%3];"
                 :: "r"(dst), "l"(src), "r"(bytes), "r"(bar) : "memory");
}
__device__ __forceinline__ void bar_sync(int id, int n) { asm volatile("bar.sync %0, %1;" :: "r"(id), "r"(n) : "memory"); }
__device__ __forceinline__ void fence_async_smem() { asm volatile("fence.proxy.async.shared::cta;" ::: "memory"); }
__device__ __forceinline__ void fence_async_all() { asm volatile("fence.acquire.gpu;\nfence.proxy.async.global;" ::: "memory"); }
__device__ __forceinline__ void wg_fence() { asm volatile("wgmma.fence.sync.aligned;" ::: "memory"); }
__device__ __forceinline__ void wg_commit() { asm volatile("wgmma.commit_group.sync.aligned;" ::: "memory"); }
template <int N> __device__ __forceinline__ void wg_wait() { asm volatile("wgmma.wait_group.sync.aligned %0;" :: "n"(N) : "memory"); }
template <int N> __device__ __forceinline__ void pin(float* d) {
#pragma unroll
    for (int i = 0; i < N; i++) asm volatile("" : "+f"(d[i]) :: "memory");
}
template <int N> __device__ __forceinline__ void pin(uint32_t* d) {
#pragma unroll
    for (int i = 0; i < N; i++) asm volatile("" : "+r"(d[i]) :: "memory");
}
constexpr uint32_t SMEM_BASE = 1024;
__device__ __forceinline__ uint64_t mkdesc(uint32_t off, uint32_t lbo, uint32_t sbo, uint32_t swz) {
    return (uint64_t)((SMEM_BASE + off) >> 4) | ((uint64_t)(lbo >> 4) << 16) | ((uint64_t)(sbo >> 4) << 32) | ((uint64_t)swz << 62);
}
__device__ __forceinline__ float ex2f(float x) { float y; asm("ex2.approx.ftz.f32 %0, %1;" : "=f"(y) : "f"(x)); return y; }
__device__ __forceinline__ float rcpf(float x) { float y; asm("rcp.approx.ftz.f32 %0, %1;" : "=f"(y) : "f"(x)); return y; }
__device__ __forceinline__ uint32_t pack_bf16(float lo, float hi) { uint32_t r; asm("cvt.rn.bf16x2.f32 %0, %1, %2;" : "=r"(r) : "f"(hi), "f"(lo)); return r; }
__device__ __forceinline__ float bf_lo(uint32_t v) { return __uint_as_float(v << 16); }
__device__ __forceinline__ float bf_hi(uint32_t v) { return __uint_as_float(v & 0xFFFF0000u); }
__device__ __forceinline__ float bf_round(float x) { return __bfloat162float(__float2bfloat16_rn(x)); }
__device__ __forceinline__ float siluf(float g) { return g * rcpf(1.0f + ex2f(g * -1.4426950408889634f)); }

__device__ __forceinline__ void wgmma_ss_n128_zero(float* d, uint64_t da, uint64_t db) {
    asm volatile("wgmma.mma_async.sync.aligned.m64n128k16.f32.bf16.bf16 {"
        "%0,%1,%2,%3,%4,%5,%6,%7,%8,%9,%10,%11,%12,%13,%14,%15,%16,%17,%18,%19,%20,%21,%22,%23,%24,%25,%26,%27,%28,%29,%30,%31,%32,%33,%34,%35,%36,%37,%38,%39,"
        "%40,%41,%42,%43,%44,%45,%46,%47,%48,%49,%50,%51,%52,%53,%54,%55,%56,%57,%58,%59,%60,%61,%62,%63"
        "}, %64, %65, 0, 1, 1, 0, 1;\n"
        : "=f"(d[0]),"=f"(d[1]),"=f"(d[2]),"=f"(d[3]),"=f"(d[4]),"=f"(d[5]),"=f"(d[6]),"=f"(d[7]),"=f"(d[8]),"=f"(d[9]),"=f"(d[10]),"=f"(d[11]),"=f"(d[12]),
          "=f"(d[13]),"=f"(d[14]),"=f"(d[15]),"=f"(d[16]),"=f"(d[17]),"=f"(d[18]),"=f"(d[19]),"=f"(d[20]),"=f"(d[21]),"=f"(d[22]),"=f"(d[23]),"=f"(d[24]),
          "=f"(d[25]),"=f"(d[26]),"=f"(d[27]),"=f"(d[28]),"=f"(d[29]),"=f"(d[30]),"=f"(d[31]),"=f"(d[32]),"=f"(d[33]),"=f"(d[34]),"=f"(d[35]),"=f"(d[36]),
          "=f"(d[37]),"=f"(d[38]),"=f"(d[39]),"=f"(d[40]),"=f"(d[41]),"=f"(d[42]),"=f"(d[43]),"=f"(d[44]),"=f"(d[45]),"=f"(d[46]),"=f"(d[47]),"=f"(d[48]),
          "=f"(d[49]),"=f"(d[50]),"=f"(d[51]),"=f"(d[52]),"=f"(d[53]),"=f"(d[54]),"=f"(d[55]),"=f"(d[56]),"=f"(d[57]),"=f"(d[58]),"=f"(d[59]),"=f"(d[60]),
          "=f"(d[61]),"=f"(d[62]),"=f"(d[63])
        : "l"(da), "l"(db));
}
__device__ __forceinline__ void wgmma_ss_n128_acc(float* d, uint64_t da, uint64_t db) {
    asm volatile("wgmma.mma_async.sync.aligned.m64n128k16.f32.bf16.bf16 {"
        "%0,%1,%2,%3,%4,%5,%6,%7,%8,%9,%10,%11,%12,%13,%14,%15,%16,%17,%18,%19,%20,%21,%22,%23,%24,%25,%26,%27,%28,%29,%30,%31,%32,%33,%34,%35,%36,%37,%38,%39,"
        "%40,%41,%42,%43,%44,%45,%46,%47,%48,%49,%50,%51,%52,%53,%54,%55,%56,%57,%58,%59,%60,%61,%62,%63"
        "}, %64, %65, 1, 1, 1, 0, 1;\n"
        : "+f"(d[0]),"+f"(d[1]),"+f"(d[2]),"+f"(d[3]),"+f"(d[4]),"+f"(d[5]),"+f"(d[6]),"+f"(d[7]),"+f"(d[8]),"+f"(d[9]),"+f"(d[10]),"+f"(d[11]),"+f"(d[12]),
          "+f"(d[13]),"+f"(d[14]),"+f"(d[15]),"+f"(d[16]),"+f"(d[17]),"+f"(d[18]),"+f"(d[19]),"+f"(d[20]),"+f"(d[21]),"+f"(d[22]),"+f"(d[23]),"+f"(d[24]),
          "+f"(d[25]),"+f"(d[26]),"+f"(d[27]),"+f"(d[28]),"+f"(d[29]),"+f"(d[30]),"+f"(d[31]),"+f"(d[32]),"+f"(d[33]),"+f"(d[34]),"+f"(d[35]),"+f"(d[36]),
          "+f"(d[37]),"+f"(d[38]),"+f"(d[39]),"+f"(d[40]),"+f"(d[41]),"+f"(d[42]),"+f"(d[43]),"+f"(d[44]),"+f"(d[45]),"+f"(d[46]),"+f"(d[47]),"+f"(d[48]),
          "+f"(d[49]),"+f"(d[50]),"+f"(d[51]),"+f"(d[52]),"+f"(d[53]),"+f"(d[54]),"+f"(d[55]),"+f"(d[56]),"+f"(d[57]),"+f"(d[58]),"+f"(d[59]),"+f"(d[60]),
          "+f"(d[61]),"+f"(d[62]),"+f"(d[63])
        : "l"(da), "l"(db));
}
__device__ __forceinline__ void wgmma_ts_n128_acc(float* d, uint64_t da, uint64_t db) {
    asm volatile("wgmma.mma_async.sync.aligned.m64n128k16.f32.bf16.bf16 {"
        "%0,%1,%2,%3,%4,%5,%6,%7,%8,%9,%10,%11,%12,%13,%14,%15,%16,%17,%18,%19,%20,%21,%22,%23,%24,%25,%26,%27,%28,%29,%30,%31,%32,%33,%34,%35,%36,%37,%38,%39,"
        "%40,%41,%42,%43,%44,%45,%46,%47,%48,%49,%50,%51,%52,%53,%54,%55,%56,%57,%58,%59,%60,%61,%62,%63"
        "}, %64, %65, 1, 1, 1, 1, 0;\n"
        : "+f"(d[0]),"+f"(d[1]),"+f"(d[2]),"+f"(d[3]),"+f"(d[4]),"+f"(d[5]),"+f"(d[6]),"+f"(d[7]),"+f"(d[8]),"+f"(d[9]),"+f"(d[10]),"+f"(d[11]),"+f"(d[12]),
          "+f"(d[13]),"+f"(d[14]),"+f"(d[15]),"+f"(d[16]),"+f"(d[17]),"+f"(d[18]),"+f"(d[19]),"+f"(d[20]),"+f"(d[21]),"+f"(d[22]),"+f"(d[23]),"+f"(d[24]),
          "+f"(d[25]),"+f"(d[26]),"+f"(d[27]),"+f"(d[28]),"+f"(d[29]),"+f"(d[30]),"+f"(d[31]),"+f"(d[32]),"+f"(d[33]),"+f"(d[34]),"+f"(d[35]),"+f"(d[36]),
          "+f"(d[37]),"+f"(d[38]),"+f"(d[39]),"+f"(d[40]),"+f"(d[41]),"+f"(d[42]),"+f"(d[43]),"+f"(d[44]),"+f"(d[45]),"+f"(d[46]),"+f"(d[47]),"+f"(d[48]),
          "+f"(d[49]),"+f"(d[50]),"+f"(d[51]),"+f"(d[52]),"+f"(d[53]),"+f"(d[54]),"+f"(d[55]),"+f"(d[56]),"+f"(d[57]),"+f"(d[58]),"+f"(d[59]),"+f"(d[60]),
          "+f"(d[61]),"+f"(d[62]),"+f"(d[63])
        : "l"(da), "l"(db));
}
__device__ __forceinline__ void wgmma_ts_n64_acc(float* d, uint64_t da, uint64_t db) {
    asm volatile("wgmma.mma_async.sync.aligned.m64n64k16.f32.bf16.bf16 {"
        "%0,%1,%2,%3,%4,%5,%6,%7,%8,%9,%10,%11,%12,%13,%14,%15,%16,%17,%18,%19,%20,%21,%22,%23,%24,%25,%26,%27,%28,%29,%30,%31"
        "}, %32, %33, 1, 1, 1, 1, 0;\n"
        : "+f"(d[0]),"+f"(d[1]),"+f"(d[2]),"+f"(d[3]),"+f"(d[4]),"+f"(d[5]),"+f"(d[6]),"+f"(d[7]),"+f"(d[8]),"+f"(d[9]),"+f"(d[10]),"+f"(d[11]),"+f"(d[12]),
          "+f"(d[13]),"+f"(d[14]),"+f"(d[15]),"+f"(d[16]),"+f"(d[17]),"+f"(d[18]),"+f"(d[19]),"+f"(d[20]),"+f"(d[21]),"+f"(d[22]),"+f"(d[23]),"+f"(d[24]),
          "+f"(d[25]),"+f"(d[26]),"+f"(d[27]),"+f"(d[28]),"+f"(d[29]),"+f"(d[30]),"+f"(d[31])
        : "l"(da), "l"(db));
}
__device__ __forceinline__ void wgmma_rs_n64_zero(float* d, const uint32_t* a, uint64_t db) {
    asm volatile("wgmma.mma_async.sync.aligned.m64n64k16.f32.bf16.bf16 {"
        "%0,%1,%2,%3,%4,%5,%6,%7,%8,%9,%10,%11,%12,%13,%14,%15,%16,%17,%18,%19,%20,%21,%22,%23,%24,%25,%26,%27,%28,%29,%30,%31"
        "}, {%32,%33,%34,%35}, %36, 0, 1, 1, 0;\n"
        : "=f"(d[0]),"=f"(d[1]),"=f"(d[2]),"=f"(d[3]),"=f"(d[4]),"=f"(d[5]),"=f"(d[6]),"=f"(d[7]),"=f"(d[8]),"=f"(d[9]),"=f"(d[10]),"=f"(d[11]),"=f"(d[12]),
          "=f"(d[13]),"=f"(d[14]),"=f"(d[15]),"=f"(d[16]),"=f"(d[17]),"=f"(d[18]),"=f"(d[19]),"=f"(d[20]),"=f"(d[21]),"=f"(d[22]),"=f"(d[23]),"=f"(d[24]),
          "=f"(d[25]),"=f"(d[26]),"=f"(d[27]),"=f"(d[28]),"=f"(d[29]),"=f"(d[30]),"=f"(d[31])
        : "r"(a[0]), "r"(a[1]), "r"(a[2]), "r"(a[3]), "l"(db));
}
__device__ __forceinline__ void wgmma_rs_n64_acc(float* d, const uint32_t* a, uint64_t db) {
    asm volatile("wgmma.mma_async.sync.aligned.m64n64k16.f32.bf16.bf16 {"
        "%0,%1,%2,%3,%4,%5,%6,%7,%8,%9,%10,%11,%12,%13,%14,%15,%16,%17,%18,%19,%20,%21,%22,%23,%24,%25,%26,%27,%28,%29,%30,%31"
        "}, {%32,%33,%34,%35}, %36, 1, 1, 1, 0;\n"
        : "+f"(d[0]),"+f"(d[1]),"+f"(d[2]),"+f"(d[3]),"+f"(d[4]),"+f"(d[5]),"+f"(d[6]),"+f"(d[7]),"+f"(d[8]),"+f"(d[9]),"+f"(d[10]),"+f"(d[11]),"+f"(d[12]),
          "+f"(d[13]),"+f"(d[14]),"+f"(d[15]),"+f"(d[16]),"+f"(d[17]),"+f"(d[18]),"+f"(d[19]),"+f"(d[20]),"+f"(d[21]),"+f"(d[22]),"+f"(d[23]),"+f"(d[24]),
          "+f"(d[25]),"+f"(d[26]),"+f"(d[27]),"+f"(d[28]),"+f"(d[29]),"+f"(d[30]),"+f"(d[31])
        : "r"(a[0]), "r"(a[1]), "r"(a[2]), "r"(a[3]), "l"(db));
}
__device__ __forceinline__ void wgmma_rs_n24_acc(float* d, const uint32_t* a, uint64_t db) {
    asm volatile("wgmma.mma_async.sync.aligned.m64n24k16.f32.bf16.bf16 {"
        "%0,%1,%2,%3,%4,%5,%6,%7,%8,%9,%10,%11"
        "}, {%12,%13,%14,%15}, %16, 1, 1, 1, 1;\n"
        : "+f"(d[0]),"+f"(d[1]),"+f"(d[2]),"+f"(d[3]),"+f"(d[4]),"+f"(d[5]),"+f"(d[6]),"+f"(d[7]),"+f"(d[8]),"+f"(d[9]),"+f"(d[10]),"+f"(d[11])
        : "r"(a[0]), "r"(a[1]), "r"(a[2]), "r"(a[3]), "l"(db));
}

constexpr int OFF_ONES = 131072;
constexpr int OFF_RING = OFF_ONES + 4096;
constexpr int NRING = 5;
constexpr int OFF_B2 = OFF_RING + NRING * 16384;
constexpr int OFF_CS = OFF_B2 + 2048;
constexpr int OFF_RS = OFF_CS + 2560;
constexpr int OFF_BAR = OFF_RS + 512;
enum { B_FULL = 0,
       B_EMPTY = 40, B_TILE = 80, B_OW = 85, B_DONE = 87,
       B_O2 = 90, B_QKV = 98,
       B_KV = 100, B_T1 = 103, B_WO = 108, B_STATS = 110, B_O = 115,
       B_DN = 120,
       B_NUM = 148 };
constexpr int OFF_TS = OFF_BAR + 1280;
constexpr int SMEM_BYTES = OFF_BAR + B_NUM * 8;
constexpr unsigned FIXED_MASK = 0x1F;
constexpr float P71 = 2361183241434822606848.0f, M71 = 4.235164736271502e-22f;

__device__ __forceinline__ uint32_t exp2_fixed(float lo, float hi, uint32_t half2) {
    uint32_t y, g, d;
    asm("cvt.pack.sat.s16.s32 %0, %1, %2;" : "=r"(y) : "r"(__float_as_uint(hi)), "r"(__float_as_uint(lo)));
    asm("lop3.b32 %0, %1, 0x007F007F, %2, 0xEA;" : "=r"(g) : "r"(y), "r"(half2));
    asm("fma.rn.bf16x2 %0, %1, %2, %3;" : "=r"(d) : "r"(y), "r"(g), "r"(y & 0xFF80FF80u));
    return d;
}
constexpr uint64_t DK_STEP = 512 - (256ull << 16), DV_STEP = 512 - (256ull << 32);
constexpr uint32_t POS_LAST = 0x37521640u;
#define G0_LAG 7
#define CS_LAG -1
#define BG_SPLIT 1
#define BG_GRP 1
#define BG_WAIT 1
#define T1_GRP 2
#define ORD_LAG 2

struct WorkMap { int v[64]; };

__global__ void __cluster_dims__(2, 1, 1) __launch_bounds__(640, 1)
mega_kernel(const __nv_bfloat16* __restrict__ x, const __nv_bfloat16* __restrict__ wqkv, const __nv_bfloat16* __restrict__ w1,
            const __nv_bfloat16* __restrict__ w3, __nv_bfloat16* __restrict__ out, Scratch* sc,
            const __grid_constant__ WorkMap wmap,
            const __grid_constant__ CUtensorMap mx, const __grid_constant__ CUtensorMap mqkv, const __grid_constant__ CUtensorMap mw1,
            const __grid_constant__ CUtensorMap mw3, const __grid_constant__ CUtensorMap mw2, const __grid_constant__ CUtensorMap mwo) {
    extern __shared__ __align__(1024) uint8_t smem_raw[];
    const uint32_t sb = __shfl_sync(0xffffffffu, smem_u32(smem_raw), 0);
    const uint32_t bars = sb + OFF_BAR, ring = sb + OFF_RING;
    const int tid = threadIdx.x, lane = tid & 31, g = lane >> 2, t4 = lane & 3;
    const int warp = __shfl_sync(0xffffffffu, tid >> 5, 0), wg = warp >> 2, wq = warp & 3;
    const int rank = blockIdx.x & 1, wm = wmap.v[blockIdx.x >> 1];
    const int rot = wm & 255, mblk = rot * 2 + rank, gu0 = (wm >> 16) & 255;
    if (warp == 0) {
        if (elect_one()) {
            mbar_init(bars, 1); mbar_init(bars + 8, 1);
            fence_async_smem();
#pragma unroll
            for (int j = 0; j < 2; j++) {
                tma2d(sb + j * 16384, &mx, j * 64, mblk * 128, bars + 8 * (B_FULL + j));
                tma2d(ring + j * 16384, &mw1, gu0 * 64, j * 64, bars + 8 * (B_FULL + j));
                tma2d(ring + j * 16384 + 8192, &mw3, gu0 * 64, j * 64, bars + 8 * (B_FULL + j));
            }
            mbar_expect(bars, 32768); mbar_expect(bars + 8, 32768);
            TSTAMP(46);
        }
    }
    const int grp = (wm >> 8) & 255, qt0 = wm >> 24, nq = grp < 4 ? 2 : 1;
    auto is_qkv = [&](int t) { return (unsigned)(t - 1) < (unsigned)nq; };
    auto unit_of = [&](int t) { return t ? gu0 + t - nq : gu0; };
    if (warp == 16) {
        if (elect_one()) {
#pragma unroll
            for (int i = 2; i < 5; i++) mbar_init(bars + 8 * i, 1);
#pragma unroll
            for (int i = 2; i < 5; i++) mbar_expect(bars + 8 * i, 32768);
            asm volatile("fence.mbarrier_init.release.cluster;" ::: "memory");
        }
        __syncwarp();
        asm volatile("bar.arrive 0, 640;\nbarrier.cluster.arrive.relaxed.aligned;" ::: "memory");
        asm volatile("barrier.cluster.wait.aligned;" ::: "memory");
        if (tid == 512) TSTAMP(27);
        uint32_t slot = 2;
#pragma unroll 1
        for (int n = 2; n < 40; n++) {
            const int t = n >> 3, j = n & 7;
            const int kc = (n < 32 ? j : (POS_LAST >> (4 * j)) & 7) * 64;
            const CUtensorMap* m = is_qkv(t) ? &mqkv : rank ? &mw3 : &mw1;
            const int col = is_qkv(t) ? (qt0 + t) * 128 + rank * 64 : unit_of(t) * 64;
            const uint32_t dst = ring + slot * 16384 + rank * 8192, fb = bars + 8 * (B_FULL + n);
            if (n < 8 && elect_one()) tma2d(sb + n * 16384, &mx, kc, mblk * 128, fb);
            if (n >= NRING) mbar_wait(fb + 8 * (B_EMPTY - NRING), 0);
            if (elect_one()) {
                tma2d_mc(dst, m, col, kc, fb); }
            if (++slot == NRING) slot = 0;
        }
    } else {
        if (warp && elect_one()) {
            const uint32_t b0 = bars + (warp < 16 ? warp * 40 : warp * 80 - 640), cnt = warp < 8 || warp > 17 ? 1 : warp == 17 ? 2 : 8;
#pragma unroll
            for (int i = 0; i < 5; i++) mbar_init(b0 + 8 * i, cnt);
            if (warp < 8) {
#pragma unroll
                for (int i = 0; i < 5; i++) mbar_expect(b0 + 8 * i, i < 3 && warp == 1 ? 32768 : 16384);
            } else if (warp >= 14) {
                const uint32_t b1 = b0 + (warp < 16 ? 80 : 40);
#pragma unroll
                for (int i = 0; i < 5; i++) mbar_init(b1 + 8 * i, cnt);
            }
            asm volatile("fence.mbarrier_init.release.cluster;" ::: "memory");
        }
        __syncwarp();
        asm volatile("barrier.cluster.arrive.relaxed.aligned;" ::: "memory");
        bar_sync(0, 640);
        if (tid == 0) TSTAMP(26);
    }
    if ((sb & 0xFFFFFF) != SMEM_BASE) __trap();
    const int lid = blockIdx.x, head = lid >> 2, qb = lid & 3;
    const int cb = lid & 7, rb0 = (lid >> 5) * 8 + ((lid >> 3) & 3);

    if (wg < 4) {
        const int pair = (wg >> 1) ^ 1, half = wg & 1, w8 = warp & 7;
        if (pair == 1) {
            const int row = mblk * 128 + grp * 16 + w8 * 2 + (lane >> 4);
            uint4 v[6];
            const uint32_t* w = reinterpret_cast<const uint32_t*>(v);
#pragma unroll
            for (int j = 0; j < 2; j++) v[4 + j] = __ldg(reinterpret_cast<const uint4*>((rank ? w3 : w1) + (size_t)(rot * 64 + w8 * 8 + j * 4 + (lane >> 3)) * FF + gu0 * 64) + (lane & 7));
#pragma unroll
            for (int j = 0; j < 4; j++) v[j] = __ldg(reinterpret_cast<const uint4*>(x + (size_t)row * DM) + j * 16 + (lane & 15));
            const uint32_t tag = ld_epoch(sc) + 1;
            float c[8];
#pragma unroll
            for (int e = 0; e < 4; e++) { c[2 * e] = bf_lo(w[16 + e]) + bf_lo(w[20 + e]); c[2 * e + 1] = bf_hi(w[16 + e]) + bf_hi(w[20 + e]); }
#pragma unroll
            for (int n = 4; n > 1; n >>= 1) {
                const bool up = lane & (4 * n);
#pragma unroll
                for (int e = 0; e < n; e++) c[e] = (up ? c[e + n] : c[e]) + __shfl_xor_sync(0xffffffffu, up ? c[e] : c[e + n], 4 * n);
            }
            asm volatile("st.shared.v2.f32 [%0], {%1,%2};" :: "r"(sb + OFF_CS + 512 + w8 * 256 + (lane & 7) * 32 + (lane >> 3) * 8), "f"(c[0]), "f"(c[1]) : "memory");
            bar_sync(6, 256);
            if (w8 < 2) {
#pragma unroll
                for (int e = 0; e < 8; e++) asm volatile("ld.shared.f32 %0, [%1];" : "=f"(c[e]) : "r"(sb + OFF_CS + 512 + e * 256 + (tid & 63) * 4));
                st_tagged(reinterpret_cast<unsigned long long*>(sc->cs) + (grp * 40 + rot) * 128 + rank * 64 + (tid & 63),
                          __float_as_uint(((c[0] + c[1]) + (c[2] + c[3])) + ((c[4] + c[5]) + (c[6] + c[7]))), tag);
                if ((tid & 255) == 0) TSTAMP(40);
            }
            float sa[4] = {0.f, 0.f, 0.f, 0.f}, sq[4] = {0.f, 0.f, 0.f, 0.f};
#pragma unroll
            for (int j = 0; j < 16; j++) sa[j & 3] += bf_lo(w[j]) + bf_hi(w[j]);
            float mean = ((sa[0] + sa[1]) + (sa[2] + sa[3])) * (1.0f / 32);
#pragma unroll
            for (int j = 0; j < 16; j++) { const float a = bf_lo(w[j]) - mean, b = bf_hi(w[j]) - mean; sq[j & 1] = fmaf(a, a, sq[j & 1]); sq[2 + (j & 1)] = fmaf(b, b, sq[2 + (j & 1)]); }
            float m2 = (sq[0] + sq[1]) + (sq[2] + sq[3]);
#pragma unroll
            for (int d = 1; d < 16; d <<= 1) {
                const float om = __shfl_xor_sync(0xffffffffu, mean, d), o2 = __shfl_xor_sync(0xffffffffu, m2, d), dm = mean - om;
                m2 = fmaf(dm * dm, 16.0f * d, m2 + o2); mean = 0.5f * (mean + om);
            }
            float sd;
            asm("sqrt.approx.f32 %0, %1;" : "=f"(sd) : "f"(bf_round(bf_round(m2 * (1.0f / DM)) + 1e-5f)));
            if ((lane & 15) == 0) st_tagged(reinterpret_cast<unsigned long long*>(sc->rs) + row, pack_bf16(mean, sd), tag);
            if ((tid & 255) == 0) TSTAMP(45);
        }

        uint32_t q[4], qn[4];
        {
            const int rowblk = mblk * 2 + half, tile16 = rowblk * 4 + wq;
            uint32_t empty;
            asm("mapa.shared::cluster.u32 %0, %1, %2;" : "=r"(empty) : "r"(bars + 8 * B_EMPTY), "r"(wq & 1));
#pragma unroll 1
            for (int t = pair; t < 5; t += 2) {
                float acc[64];
                uint32_t full = bars + 8 * (B_FULL + 8 * t), rel = empty + 64 * t;
                uint32_t stepa = t == 4 ? 0x4AB93AC : 0x9999999, stepb = (uint32_t)(0x994999949999ull >> (4 * ((0x24130u >> (4 * t)) & 7)));
                uint64_t da = mkdesc(half * 8192, 16, 1024, 1), db = mkdesc(OFF_RING, 8192, 1024, 1) + ((0x24130u >> (4 * t)) & 7) * 1024;
                if ((tid & 255) == 0 && t == 0) TSTAMP(30);
                mbar_wait(full, 0);
                if ((tid & 255) == 0 && t == 0) TSTAMP(1);
                if (t > 0) mbar_wait(full + 8 * (B_EMPTY - ORD_LAG), 0);
                wg_fence();
                wgmma_ss_n128_zero(acc, da, db);
#pragma unroll
                for (int k = 1; k < 4; k++) wgmma_ss_n128_acc(acc, da + k * 2, db + k * 128);
                wg_commit();
                mbar_wait(full + 8, 0);
#pragma unroll 1
                do {
                    da += (int)((stepa & 15) << 10) - 8192; db += (int)((stepb & 15) << 10) - 8192;
                    stepa >>= 4; stepb >>= 4;
                    wg_fence();
#pragma unroll
                    for (int k = 0; k < 4; k++) wgmma_ss_n128_acc(acc, da + k * 2, db + k * 128);
                    wg_commit();
                    mbar_wait(full + 16, 0);
                    wg_wait<1>();
                    if (elect_one()) mbar_arrive_remote(rel);
                    full += 8; rel += 8;
                } while (stepa);
                auto fetch_q = [&]() {
                    mbar_wait(bars + 8 * B_QKV, 0);
                    const uint4* pq = sc->q + (head * 128 + (qb * 8 + wg) * 4 + wq) * 32 + lane;
                    const uint4 v = __ldcg(pq), u = __ldcg(pq + 512);
                    q[0] = v.x; q[1] = v.y; q[2] = v.z; q[3] = v.w; qn[0] = u.x; qn[1] = u.y; qn[2] = u.z; qn[3] = u.w;
                };
                if (t == 4) fetch_q();
                wg_wait<0>();
                if (elect_one()) mbar_arrive_remote(rel);
                pin<64>(acc);
                if (wq == 0 && half == 0 && lane == 0) TSTAMP(2 + 2 * t);
                if ((tid & 255) == 0 && t == 4) GSTAMP(10);
                mbar_wait(bars + 8 * (B_STATS + t), 0);
                uint32_t rs0, rs1;
                asm volatile("ld.shared.b32 %0, [%1];" : "=r"(rs0) : "r"(sb + OFF_RS + (half * 64 + wq * 16 + g) * 4));
                asm volatile("ld.shared.b32 %0, [%1];" : "=r"(rs1) : "r"(sb + OFF_RS + (half * 64 + wq * 16 + g + 8) * 4));
                const float m0 = bf_lo(rs0), m1 = bf_lo(rs1);
                float d0 = bf_hi(rs0), d1 = bf_hi(rs1);
                float r0 = rcpf(d0), r1 = rcpf(d1);
                const uint32_t pcs = sb + OFF_CS + t * 512 + t4 * 8;
                auto lds2 = [&](int j, float* c) { asm volatile("ld.shared.v2.f32 {%0,%1}, [%2];" : "=f"(c[0]), "=f"(c[1]) : "r"(pcs + j * 32) : "memory"); };
                auto fix = [&](float* a, const float* c) { a[0] = fmaf(-m0, c[0], a[0]); a[1] = fmaf(-m0, c[1], a[1]); a[2] = fmaf(-m1, c[0], a[2]); a[3] = fmaf(-m1, c[1], a[3]); };
                float c[2][4];
                if (is_qkv(t)) {
                    const int qt = qt0 + t;
                    if (qt < 4) {
                        r0 *= 0.25f * 1.4426950408889634f * M71; r1 *= 0.25f * 1.4426950408889634f * M71;
                    } else if (qt < 8) {
                        r0 *= ((FIXED_MASK >> (2 * wq)) & 1) ? M71 : P71; r1 *= ((FIXED_MASK >> (2 * wq + 1)) & 1) ? M71 : P71;
                    }
                    uint8_t* p = qt < 4 ? reinterpret_cast<uint8_t*>(sc->q + (qt * 1024 + tile16) * 32 + lane)
                                        : reinterpret_cast<uint8_t*>(sc->kv + (qt - 4) * 32768) + tile16 * 256 + lane * 4;
                    lds2(0, c[0]); lds2(1, c[0] + 2);
#pragma unroll
                    for (int hh = 0; hh < 8; hh++) {
                        if (hh < 7) { lds2(2 * hh + 2, c[~hh & 1]); lds2(2 * hh + 3, c[~hh & 1] + 2); }
                        float* a = acc + hh * 8;
                        fix(a, c[hh & 1]); fix(a + 4, c[hh & 1] + 2);
                        asm volatile("{\n.reg .pred p;\nsetp.lt.s32 p, %5, 4;\n@p st.global.v4.b32 [%0], {%1,%2,%3,%4};\n"
                                     "@!p st.global.b32 [%0], %1;\n@!p st.global.b32 [%0+128], %2;\n@!p st.global.b32 [%0+32768], %3;\n@!p st.global.b32 [%0+32896], %4;\n}"
                                     :: "l"(p + hh * 65536), "r"(pack_bf16(a[0] * r0, a[1] * r0)), "r"(pack_bf16(a[2] * r1, a[3] * r1)),
                                        "r"(pack_bf16(a[4] * r0, a[5] * r0)), "r"(pack_bf16(a[6] * r1, a[7] * r1)), "r"(qt) : "memory");
                    }
                } else {
                    uint32_t* p = reinterpret_cast<uint32_t*>(sc->h + ((((rowblk >> 3) * 4 + (rowblk & 3)) * 28 + unit_of(t)) * 2 + ((rowblk >> 2) & 1)) * 512) + wq * 512 + lane;
                    r0 *= -1.4426950408889634f; r1 *= -1.4426950408889634f; d0 *= d0; d1 *= d1;
                    lds2(0, c[0]); lds2(8, c[0] + 2);
#pragma unroll
                    for (int j = 0; j < 8; j++) {
                        if (j < 7) { lds2(j + 1, c[~j & 1]); lds2(j + 9, c[~j & 1] + 2); }
                        float* a = acc + j * 4; float* b = a + 32;
                        fix(a, c[j & 1]); fix(b, c[j & 1] + 2);
                        p[j * 32] = pack_bf16(a[0] * b[0] * rcpf(fmaf(ex2f(a[0] * r0), d0, d0)), a[1] * b[1] * rcpf(fmaf(ex2f(a[1] * r0), d0, d0)));
                        p[256 + j * 32] = pack_bf16(a[2] * b[2] * rcpf(fmaf(ex2f(a[2] * r1), d1, d1)), a[3] * b[3] * rcpf(fmaf(ex2f(a[3] * r1), d1, d1)));
                    }
                }
                __syncwarp();
                if (elect_one()) mbar_arrive(bars + 8 * (B_TILE + t));
                if (t == 3) fetch_q();
                if (wq == 0 && half == 0 && lane == 0) TSTAMP(3 + 2 * t);
            }
        }
        const uint64_t db2 = mkdesc(OFF_B2, 128, 256, 0) - (sb >> 28);
        const uint64_t DK0 = mkdesc(4096, 94208, 128, 0);
        const uint32_t half2 = 0x3F003F00u + __shfl_sync(0xffffffffu, lane, 0);
        uint32_t q2[4], chk_bar = bars + 8 * (B_KV + 1);
        uint4 v[8];
        const uint4* osrc = sc->o + (rb0 + 4) * 4096 + (warp >> 1) * 512 + (warp & 1) * 32 + lane;
        auto poll_o = [&](uint32_t pend) {
#pragma unroll
            for (int i = 0; i < 8; i++) {
                if (pend >> i & 1)
                    asm volatile("ld.relaxed.gpu.global.v4.u32 {%0,%1,%2,%3}, [%4];" : "=r"(v[i].x), "=r"(v[i].y), "=r"(v[i].z), "=r"(v[i].w) : "l"(osrc + i * 64) : "memory");
            }
        };
        uint32_t* po = reinterpret_cast<uint32_t*>(sc->o + ((qb * 8 + wg) * 8 + (head >> 2)) * 512) + wq * 512 + (head & 3) * 64 + lane;
        int redo = 0;
        mbar_wait(bars + 8 * B_KV, 0);
#pragma unroll 1
        for (int round = 0; round < 2;) {
            float s[32];
            float mq[2];
            if (!redo) {
                wg_fence();
                wgmma_rs_n64_zero(s, q, DK0);
                wg_commit();
                wg_wait<0>();
                pin<32>(s);
#pragma unroll
                for (int r = 0; r < 2; r++) {
                    int m = max(__float_as_int(s[2 * r]), __float_as_int(s[2 * r + 1]));
#pragma unroll
                    for (int i = 1; i < 5; i++) m = __vimax3_s32(m, __float_as_int(s[4 * i + 2 * r]), __float_as_int(s[4 * i + 2 * r + 1]));
                    mq[r] = __int_as_float(m & ~3) * (-0.25f * P71);
                }
            } else {
                float m0 = -INFINITY, m1 = -INFINITY, f0 = -INFINITY, f1 = -INFINITY;
#pragma unroll 1
                for (int t = redo - 1; t >= 0; t--) {
                    wg_fence();
                    wgmma_rs_n64_zero(s, q, DK0 + (t >> 2) * DK_STEP + (t & 3) * 64);
                    wg_commit();
                    wg_wait<0>();
                    pin<32>(s);
#pragma unroll
                    for (int i = 0; i < 8; i++) {
                        if ((FIXED_MASK >> i) & 1) { f0 = fmaxf(f0, fmaxf(s[4 * i], s[4 * i + 1])); f1 = fmaxf(f1, fmaxf(s[4 * i + 2], s[4 * i + 3])); }
                        else                       { m0 = fmaxf(m0, fmaxf(s[4 * i], s[4 * i + 1])); m1 = fmaxf(m1, fmaxf(s[4 * i + 2], s[4 * i + 3])); }
                    }
                }
                m0 = fmaxf(m0, f0 * P71 * P71); m1 = fmaxf(m1, f1 * P71 * P71);
                m0 = fmaxf(m0, __shfl_xor_sync(0xffffffffu, m0, 1)); m1 = fmaxf(m1, __shfl_xor_sync(0xffffffffu, m1, 1));
                m0 = fmaxf(m0, __shfl_xor_sync(0xffffffffu, m0, 2)); m1 = fmaxf(m1, __shfl_xor_sync(0xffffffffu, m1, 2));
                mq[0] = (floorf(m0) - 64.f) * (-0.25f * M71); mq[1] = (floorf(m1) - 64.f) * (-0.25f * M71);
            }
#pragma unroll
            for (int r = 0; r < 2; r++) {
                const float r1 = mq[r] - bf_hi(__float_as_uint(mq[r])), r2 = r1 - bf_hi(__float_as_uint(r1));
                q2[r] = __byte_perm(__float_as_uint(mq[r]), __float_as_uint(r1), 0x7632);
                q2[2 + r] = __byte_perm(__float_as_uint(r2), __float_as_uint(M71), 0x7632);
            }
            float o[12]; uint32_t p[16];
#pragma unroll
            for (int i = 0; i < 12; i++) o[i] = 0.f;
            pin<12>(o); pin<4>(q2);
            if (wq == 0 && half == 0 && lane == 0) TSTAMP(12 + 4 * round + pair);
            uint64_t dk = DK0, dv = mkdesc(0, 128, 65536, 0);
            wg_fence();
            wgmma_rs_n64_acc(s, q2, db2);
            wg_commit();
#pragma unroll 1
            for (uint32_t todo = redo ? 0x100 : round ? 0x180 : 0x103;; dk += DK_STEP, dv += DV_STEP) {
                if (todo & 1) { mbar_wait(chk_bar, 0); chk_bar += 8; }
                todo >>= 1;
#pragma unroll
                for (int t = 0; t < 4; t++) {
                    wg_wait<0>();
                    pin<32>(s); pin<16>(p);
#pragma unroll
                    for (int i = 0; i < 16; i++) {
                        if ((FIXED_MASK >> (i >> 1)) & 1) p[i] = exp2_fixed(s[2 * i], s[2 * i + 1], half2);
                        else                              p[i] = pack_bf16(ex2f(s[2 * i]), ex2f(s[2 * i + 1]));
                    }
                    wg_fence();
#pragma unroll
                    for (int k = 0; k < 4; k++) wgmma_rs_n24_acc(o, p + 4 * k, dv + (t * 4 + k) * 16);
                    wg_commit();
                    if (t == 3 && todo == 1) goto keys_done;
                    wg_fence();
                    wgmma_rs_n64_zero(s, q, t == 3 ? dk + DK_STEP : dk + (t + 1) * 64);
                    wgmma_rs_n64_acc(s, q2, db2);
                    wg_commit();
                }
            }
        keys_done:
            wg_wait<0>();
            pin<12>(o);
            const float r0 = rcpf(o[8]), r1 = rcpf(o[10]);
#pragma unroll
            for (int i = 0; i < 8; i++) o[i] *= (i & 2) ? r1 : r0;
            if (!redo) {
                const float chk = fmaf(o[0], o[1], fmaf(o[2], o[3], o[8] * 4.f)) + fmaf(o[4], o[5], fmaf(o[6], o[7], o[10] * 4.f));
                uint32_t bad;
                asm volatile("{\n.reg .pred p, q;\nsetp.geu.f32 q, %1, 0f7F800000;\nbar.red.or.pred p, %2, 128, q;\nselp.u32 %0, 1, 0, p;\n}" : "=r"(bad) : "f"(fabsf(chk)), "r"(1 + wg) : "memory");
                redo = __popc(__ballot_sync(0xffffffffu, bad));
                if (redo) continue;
            }
            st_relaxed(po, pack_bf16(o[0], o[1])); st_relaxed(po + 256, pack_bf16(o[2], o[3]));
            st_relaxed(po + 32, pack_bf16(o[4], o[5])); st_relaxed(po + 288, pack_bf16(o[6], o[7]));
            if (round == 0) {
                po += 4 * 8 * 2048;
                st_relaxed(po, ~0u); st_relaxed(po + 256, ~0u); st_relaxed(po + 32, ~0u); st_relaxed(po + 288, ~0u);
            }
            __syncwarp();
            if (elect_one()) mbar_arrive(bars + 8 * (B_OW + 2 * round + (wg >> 1)));
#pragma unroll
            for (int i = 0; i < 4; i++) q[i] = qn[i];
            redo = 0;
            if (wq == 0 && half == 0 && lane == 0) TSTAMP(14 + 4 * round + pair);
            if (wq == 0 && lane == 0) GSTAMP(round * 4 + wg);
            round++;
        }
        if (lane == 0) TS3(1, warp);
        poll_o(0xFF);
        bool dead = false;
#pragma unroll 1
        for (int n = 0; n < 2000000; n++) {
            dead = __all_sync(0xffffffffu, mbar_test(bars + 8 * B_DONE) & mbar_test(bars + 8 * (B_DONE + 1)));
            uint32_t bad = 0;
#pragma unroll
            for (int i = 0; i < 8; i++) bad |= (__vimax3_u32(max(v[i].x, v[i].y), v[i].z, v[i].w) == ~0u) << i;
            bad = __reduce_or_sync(0xffffffffu, bad);
            if (!bad) break;
            poll_o(bad);
        }
        if (lane == 0) TS3(2, warp);
        if (!dead) { mbar_wait(bars + 8 * B_DONE, 0); mbar_wait(bars + 8 * (B_DONE + 1), 0); }
#pragma unroll
        for (int i = 0; i < 8; i++)
            asm volatile("st.shared.v4.b32 [%0], {%1,%2,%3,%4};" :: "r"(sb + (warp >> 1) * 8192 + (warp & 1) * 512 + i * 1024 + lane * 16), "r"(v[i].x), "r"(v[i].y), "r"(v[i].z), "r"(v[i].w) : "memory");
        if (lane == 0) TS3(2, 16 + warp);
        fence_async_smem();
        __syncwarp();
        if (elect_one()) mbar_arrive(bars + 8 * (B_O2 + (warp >> 1)));
        if (lane == 0) TS3(2, 32 + warp);
        if (tid == 0) TSTAMP(24);
        if (lane == 0) GSTAMP(16 + warp);
    } else {
        uint32_t tag;
        if (wq == 0) {
            tag = ld_epoch(sc) + 1;
            wait_cnt(sc->cnt + (C_H + (rb0 >> 1)) * 8, 28 * tag, 100);
            wait_cnt(sc->cnt + (C_H + (rb0 >> 1) + 2) * 8, 28 * tag, 100);
            fence_async_all();
        } else if (!(warp & 2)) {
            if (elect_one()) asm volatile("prefetch.tensormap [%0];" :: "l"(&mqkv) : "memory");
            tag = ld_epoch(sc) + 1;
            mbar_wait(bars + 8 * (B_FULL + G0_LAG), 0);
#pragma unroll 1
            for (int t = 0; t < 5; t++) {
                float a[4];
#pragma unroll 1
                for (int n = 0; n < 2000000; n++) {
                    uint32_t stale = 0;
                    a[0] = a[1] = a[2] = a[3] = 0.f;
#pragma unroll
                    for (int i = 0; i < 16; i++) {
                        uint32_t u, v;
                        stale |= ld_tagged2(sc->cs + (grp * 5 + t) * 512 + i * 32 + lane, tag, u, v);
                        a[(i & 1) * 2] += __uint_as_float(u); a[(i & 1) * 2 + 1] += __uint_as_float(v);
                    }
                    if (__all_sync(0xffffffffu, stale == 0)) break;
                    if (t) __nanosleep(400);
                }
                asm volatile("st.shared.v2.f32 [%0], {%1,%2};" :: "r"(sb + OFF_CS + t * 512 + lane * 8), "f"(a[0]), "f"(a[1]) : "memory");
                asm volatile("st.shared.v2.f32 [%0], {%1,%2};" :: "r"(sb + OFF_CS + t * 512 + 256 + lane * 8), "f"(a[2]), "f"(a[3]) : "memory");
                if (t == 0) {
                    uint32_t r[4];
#pragma unroll 1
                    for (int n = 0; n < 2000000; n++) {
                        const uint32_t stale = ld_tagged2(sc->rs + mblk * 64 + lane * 2, tag, r[0], r[1]) | ld_tagged2(sc->rs + mblk * 64 + lane * 2 + 1, tag, r[2], r[3]);
                        if (__all_sync(0xffffffffu, stale == 0)) break;
                    }
                    asm volatile("st.shared.v4.b32 [%0], {%1,%2,%3,%4};" :: "r"(sb + OFF_RS + lane * 16), "r"(r[0]), "r"(r[1]), "r"(r[2]), "r"(r[3]) : "memory");
                }
                __syncwarp();
                if (elect_one()) { mbar_arrive(bars + 8 * (B_STATS + t)); TSTAMP(32 + t); }
            }
        } else {
            tag = ld_epoch(sc) + 1;
            mbar_wait(bars + 8 * (B_FULL + wq + CS_LAG), 0);
#pragma unroll 1
            for (int t = wq - 1; t < 5; t += 2) {
                const __nv_bfloat16* src; int ld;
                if (is_qkv(t)) { src = wqkv + (qt0 + t) * 128 + rank * 64; ld = 3 * DM; }
                else        { src = (rank ? w3 : w1) + unit_of(t) * 64; ld = FF; }
                src += (size_t)(rot * 64 + (lane >> 3)) * ld + (lane & 7) * 8;
                uint4 v[16];
                const uint32_t* w = reinterpret_cast<const uint32_t*>(v);
#pragma unroll
                for (int j = 0; j < 16; j++) v[j] = __ldg(reinterpret_cast<const uint4*>(src + (size_t)j * 4 * ld));
                float c[8];
#pragma unroll
                for (int e = 0; e < 4; e++) {
                    float a = 0.f, b = 0.f;
#pragma unroll
                    for (int j = 0; j < 16; j++) { a += bf_lo(w[4 * j + e]); b += bf_hi(w[4 * j + e]); }
                    c[2 * e] = a; c[2 * e + 1] = b;
                }
#pragma unroll
                for (int n = 4; n > 1; n >>= 1) {
                    const bool up = lane & (4 * n);
#pragma unroll
                    for (int e = 0; e < n; e++) c[e] = (up ? c[e + n] : c[e]) + __shfl_xor_sync(0xffffffffu, up ? c[e] : c[e + n], 4 * n);
                }
                unsigned long long* dst = reinterpret_cast<unsigned long long*>(sc->cs) + ((grp * 5 + t) * 8 + rot) * 128 + rank * 64 + (lane & 7) * 8 + (lane >> 3) * 2;
                st_tagged(dst, __float_as_uint(c[0]), tag); st_tagged(dst + 1, __float_as_uint(c[1]), tag);
                if (lane == 0) TSTAMP(40 + t);
            }
        }
        if (wq == 3) {
#pragma unroll 1
            for (int i = lane; i < 256; i += 32) asm volatile("st.shared.v4.b32 [%0], {%1,%1,%1,%1};" :: "r"(sb + OFF_ONES + i * 16), "r"(0x3F803F80u) : "memory");
#pragma unroll 1
            for (int i = lane; i < 128; i += 32) {
                const bool fx = (FIXED_MASK >> (i >> 4)) & 1;
                const float sc = fx ? M71 : P71;
                uint32_t a = pack_bf16(sc, sc), b = a, c = a;
                if (i & 8) { a = pack_bf16(sc, fx ? 27.0f * M71 : -99.5f * P71); b = pack_bf16(sc, fx ? 0.f : 0.08214f * P71); c = pack_bf16(sc, 0.f); }
                asm volatile("st.shared.v4.b32 [%0], {%1,%2,%3,%4};" :: "r"(sb + OFF_B2 + i * 16), "r"(a), "r"(b), "r"(c), "r"(c) : "memory");
            }
            if (elect_one()) {
#pragma unroll 1
                for (int i = 0; i < 28; i++) { mbar_init(bars + 8 * (B_DN + i), 1); mbar_expect(bars + 8 * (B_DN + i), 24576); }
                mbar_expect(bars + 8 * B_WO, 65536);
#pragma unroll 1
                for (int i = 0; i < 4; i++) mbar_expect(bars + 8 * (B_O + i), 16384);
            }
            fence_async_smem();
            __syncwarp();
            if (elect_one()) mbar_arrive(bars + 8 * B_QKV);
        } else if (wq == 1) {
#pragma unroll 1
            for (int i = 0; i < 3; i++) wait_cnt(sc->cnt + (C_QKV + i * 4 + (head >> 3)) * 8, 16 * tag, 100);
            fence_async_all();
            if (elect_one()) { mbar_arrive(bars + 8 * B_QKV); TSTAMP(29); }
            mbar_wait(bars + 8 * (B_EMPTY + 31), 0);
            const uint8_t* gk = reinterpret_cast<const uint8_t*>(sc->kv + head * 4096);
            const uint8_t* gv = reinterpret_cast<const uint8_t*>(sc->kv + (32 + head) * 4096);
#pragma unroll 1
            for (int c = 0; c < 8; c++) {
                mbar_wait(bars + 8 * (B_EMPTY + 34 + (c & 4) + ((c >> 1) & 1)), 0);
                if (elect_one()) {
                    const uint32_t b = bars + 8 * (B_KV + min(c, 2));
                    if (c <= 2) mbar_expect(b, c < 2 ? 16384 : 6 * 16384);
                    bulk_load(sb + (2 * c + 1) * 4096, gk + c * 4096, 4096, b);
                    bulk_load(sb + 2 * c * 4096, gv + c * 4096, 4096, b);
                    bulk_load(sb + 65536 + c * 4096, gv + 32768 + c * 4096, 4096, b);
                    bulk_load(sb + 98304 + c * 4096, gk + 32768 + c * 4096, 4096, b);
                }
            }
        } else if (wq == 2) {
#pragma unroll 1
            for (int t = 0; t < 5; t++) {
                mbar_wait(bars + 8 * (B_TILE + t), 0);
                if (elect_one()) signal_cnt(sc->cnt + (is_qkv(t) ? C_QKV + qt0 + t : C_H + mblk) * 8);
            }
        }
        pin<1>(&tag);
        bar_sync(5, 128);
        if (tid == 639) sc->epoch[blockIdx.x] = tag;
        uint32_t gate[2][16];
        {
            float dn[64];
#pragma unroll
            for (int i = 0; i < 64; i++) dn[i] = 0.f;
            pin<64>(dn);
            const uint4* hsrc = sc->h + (lid >> 3) * 28 * 1024;
            const int wcol = cb * 64;
            uint32_t nb = bars + 8 * B_DN, kc = 0;
            auto load_stage = [&](int slot) {
                const uint32_t dst = ring + slot * 24576;
                if (wq == 0) { if (elect_one()) bulk_load(dst, hsrc, 16384, nb); }
                if (wq == 1) { if (elect_one()) tma2d(dst + 16384, &mw2, wcol, kc, nb); }
                hsrc += 1024; kc += 64; nb += 8;
            };
            auto mma_stage = [&](int slot) {
                mbar_wait(nb - 16, 0);
#pragma unroll
                for (int k = 0; k < 4 * BG_SPLIT; k++) {
                    if (k % BG_GRP == 0) wg_fence();
                    const uint64_t dw = mkdesc(OFF_RING + 16384 + slot * 24576, 8192, 1024, 1) + k / BG_SPLIT * 128, dh = mkdesc(OFF_RING + slot * 24576, 128, 1024, 0) + k / BG_SPLIT * 16;
                    if (BG_SPLIT == 1) wgmma_ts_n128_acc(dn, dw, dh); else wgmma_ts_n64_acc(dn + (k & 1) * 32, dw, dh + (k & 1) * 512);
                    if (k % BG_GRP == BG_GRP - 1) { wg_commit(); wg_wait<BG_WAIT>(); }
                }
            };
            if (tid == 512) TSTAMP(20);
            load_stage(0); load_stage(1);
#pragma unroll 1
            for (int it = 0; it < 9; it++) {
                mma_stage(0); load_stage(2);
                mma_stage(1); load_stage(0);
                mma_stage(2); if (it < 8) load_stage(1); else nb += 8;
            }
            mma_stage(0);
            wg_wait<0>();
            pin<64>(dn);
            if (wq == 1 && elect_one()) {
#pragma unroll 1
                for (int i = 0; i < 8; i++) tma2d(ring + i * 8192, &mwo, cb * 64, i * 64, bars + 8 * B_WO);
            }
#pragma unroll
            for (int i = 0; i < 32; i++) gate[i >> 4][i & 15] = pack_bf16(siluf(dn[2 * i]), siluf(dn[2 * i + 1]));
        }
        if (tid == 512) TSTAMP(21);
        if (wq >= 2) {
            mbar_wait(bars + 8 * (B_OW + wq - 2), 0);
            if (elect_one()) {
                signal_cnt(sc->cnt + (C_O + qb * 8 + 2 * wq - 4) * 8);
                asm volatile("red.relaxed.gpu.global.add.u32 [%0], 1;" :: "l"(sc->cnt + (C_O + qb * 8 + 2 * wq - 3) * 8) : "memory");
            }
        }
#pragma unroll 1
        for (int tl = 0; tl < 2; tl++) {
            const int rb = rb0 + 4 * tl;
            const size_t goff = (size_t)(rb * 64 + wq * 16 + (lane >> 3)) * (DM / 8) + cb * 8 + (lane & 7);
            uint4 xr[4];
#pragma unroll
            for (int i = 0; i < 4; i++) xr[i] = __ldg(reinterpret_cast<const uint4*>(x) + goff + i * 4 * (DM / 8));
            float acc[32];
#pragma unroll
            for (int i = 0; i < 32; i++) acc[i] = 0.f;
            pin<32>(acc);
            uint64_t dw = mkdesc(OFF_RING, 8192, 1024, 1);
            if (tl == 0) {
                if (wq == 0) {
                    wait_cnt(sc->cnt + (C_O + rb) * 8, 32 * tag, 200);
                    fence_async_all();
                    if (elect_one()) { mbar_arrive(bars + 8 * B_T1); TSTAMP(22); }
                }
                mbar_wait(bars + 8 * B_WO, 0);
#pragma unroll 1
                for (int i = 0; i < 4; i++, dw += 1024) {
                    if (wq == 0 && elect_one()) bulk_load(ring + 65536, sc->o + (rb * 4 + i) * 1024, 16384, bars + 8 * (B_O + i));
                    mbar_wait(bars + 8 * (B_O + i), 0);
#pragma unroll
                    for (int k = 0; k < 8; k++) {
                        if (k % T1_GRP == 0) wg_fence();
                        wgmma_ts_n64_acc(acc, dw + k * 128, mkdesc(OFF_RING + 65536, 128, 1024, 0) + (k >> 2) * 512 + (k & 3) * 16);
                        if (k % T1_GRP == T1_GRP - 1) { wg_commit(); wg_wait<0>(); }
                    }
                }
            } else {
                uint64_t dx = mkdesc(0, 128, 1024, 0);
#pragma unroll 1
                for (int i = 0; i < 8; i++, dx += 512, dw += 512) {
                    mbar_wait(bars + 8 * (B_O2 + i), 0);
                    if (tid == 512) TS3(0, 48 + i);
                    wg_fence();
#pragma unroll
                    for (int k = 0; k < 4; k++) wgmma_ts_n64_acc(acc, dw + k * 128, dx + k * 16);
                    wg_commit();
                }
                wg_wait<0>();
            }
            pin<32>(acc);
            if (tid == 512) TS3(0, 56);
            const uint32_t stg = ring + 65536;
            uint32_t r[16];
#pragma unroll
            for (int i = 0; i < 16; i++) {
                asm("mul.rn.bf16x2 %0, %1, %2;" : "=r"(r[i]) : "r"(pack_bf16(acc[2 * i], acc[2 * i + 1])), "r"(gate[0][i]));
                gate[0][i] = gate[1][i];
            }
#pragma unroll
            for (int i = 0; i < 4; i++)
                asm volatile("stmatrix.sync.aligned.m8n8.x4.trans.shared.b16 [%0], {%1,%2,%3,%4};"
                             :: "r"(stg + (i * 16 + (lane >> 4) * 8 + (lane & 7)) * 128 + (((2 * wq + ((lane >> 3) & 1)) ^ (lane & 7)) << 4)),
                                "r"(r[4 * i]), "r"(r[4 * i + 1]), "r"(r[4 * i + 2]), "r"(r[4 * i + 3]) : "memory");
            bar_sync(5, 128);
#pragma unroll
            for (int i = 0; i < 4; i++) {
                const int row = wq * 16 + i * 4 + (lane >> 3);
                uint4 u;
                asm volatile("ld.shared.v4.b32 {%0,%1,%2,%3}, [%4];" : "=r"(u.x), "=r"(u.y), "=r"(u.z), "=r"(u.w) : "r"(stg + row * 128 + (((lane ^ row) & 7) << 4)) : "memory");
                asm("add.rn.bf16x2 %0, %0, %1;" : "+r"(u.x) : "r"(xr[i].x)); asm("add.rn.bf16x2 %0, %0, %1;" : "+r"(u.y) : "r"(xr[i].y));
                asm("add.rn.bf16x2 %0, %0, %1;" : "+r"(u.z) : "r"(xr[i].z)); asm("add.rn.bf16x2 %0, %0, %1;" : "+r"(u.w) : "r"(xr[i].w));
                reinterpret_cast<uint4*>(out)[goff + i * 4 * (DM / 8)] = u;
            }
            if (tid == 512) TSTAMP(23 + 2 * tl);
            if (tid == 512) GSTAMP(8 + tl);
        }
    }
}

typedef CUresult (*EncodeFn)(CUtensorMap*, CUtensorMapDataType, cuuint32_t, void*, const cuuint64_t*, const cuuint64_t*, const cuuint32_t*,
                             const cuuint32_t*, CUtensorMapInterleave, CUtensorMapSwizzle, CUtensorMapL2promotion, CUtensorMapFloatOOBfill);

void make_map(EncodeFn fn, CUtensorMap* m, const void* p, int rows, int cols, int box_rows) {
    cuuint64_t dims[2] = {(cuuint64_t)cols, (cuuint64_t)rows};
    cuuint64_t strides[1] = {(cuuint64_t)cols * 2};
    cuuint32_t box[2] = {64, (cuuint32_t)box_rows};
    cuuint32_t es[2] = {1, 1};
    fn(m, CU_TENSOR_MAP_DATA_TYPE_BFLOAT16, 2, const_cast<void*>(p), dims, strides, box, es, CU_TENSOR_MAP_INTERLEAVE_NONE,
       CU_TENSOR_MAP_SWIZZLE_128B, CU_TENSOR_MAP_L2_PROMOTION_L2_128B, CU_TENSOR_MAP_FLOAT_OOB_FILL_NONE);
}

}

extern "C" void kernel_launch(void* const* d_in, const int* in_sizes, int n_in, void* d_out, int out_size) {
    const __nv_bfloat16* x = (const __nv_bfloat16*)d_in[0];
    static EncodeFn fn = nullptr;
    static Scratch* scratch = nullptr;
    if (!fn) {
        cudaDriverEntryPointQueryResult qr;
        cudaGetDriverEntryPoint("cuTensorMapEncodeTiled", (void**)&fn, cudaEnableDefault, &qr);
        cudaGetSymbolAddress((void**)&scratch, g_scratch);
        cudaFuncSetAttribute(mega_kernel, cudaFuncAttributeMaxDynamicSharedMemorySize, SMEM_BYTES);
    }
    CUtensorMap mx, mqkv, mw1, mw3, mw2, mwo;
    make_map(fn, &mx, d_in[0], SEQ, DM, 128);
    make_map(fn, &mqkv, d_in[1], DM, 3 * DM, 64);
    make_map(fn, &mwo, d_in[2], DM, DM, 64);
    make_map(fn, &mw1, d_in[4], DM, FF, 64);
    make_map(fn, &mw3, d_in[5], DM, FF, 64);
    make_map(fn, &mw2, d_in[6], FF, DM, 64);
    WorkMap wmap;
    for (int cl = 0; cl < 64; cl++) {
        const int grp = cl < 4 ? 4 + cl : cl < 36 ? (cl - 4) >> 3 : 4 + (cl - 36) / 7;
        const int rot = cl < 4 ? 7 : cl < 36 ? (cl - 4) & 7 : (cl - 36) % 7;
        wmap.v[cl] = rot | grp << 8 | (grp < 4 ? 3 * grp : 4 * grp - 4) << 16 | (int)((unsigned)(grp < 4 ? 2 * grp - 1 : 3 + grp) << 24);
    }
    mega_kernel<<<128, 640, SMEM_BYTES, cudaStreamPerThread>>>(x, (const __nv_bfloat16*)d_in[1], (const __nv_bfloat16*)d_in[4], (const __nv_bfloat16*)d_in[5],
                                                               (__nv_bfloat16*)d_out, scratch, wmap, mx, mqkv, mw1, mw3, mw2, mwo);
}
```

```cpp
#include <cuda_runtime.h>
#include <cuda_bf16.h>
#include <cuda.h>
#include <stdint.h>
#include <stddef.h>
#include <limits.h>

namespace {

constexpr int SEQ = 2048, DM = 512, FF = 1792;

constexpr int C_QKV = 0, C_H = 12, C_O = 28, C_NUM = 60;
struct Scratch {
    uint4 q[32 * 128 * 32];
    uint4 kv[64 * 4096];
    uint4 o[32 * 8 * 512];
    uint4 h[32 * 28 * 512];
    ulonglong2 cs[40 * 8 * 64];
    ulonglong2 rs[SEQ / 2];
    unsigned cnt[C_NUM * 8];
    unsigned epoch[128];
};
__device__ __align__(1024) Scratch g_scratch;
#define TSTAMP(i)
#define GSTAMP(i)
#define TS3(k, i)
#define TS2(k, i)

__device__ __forceinline__ uint32_t smem_u32(const void* p) { return (uint32_t)__cvta_generic_to_shared(p); }
__device__ __forceinline__ void mbar_init(uint32_t a, int c) { asm volatile("mbarrier.init.shared::cta.b64 [%0], %1;" :: "r"(a), "r"(c)); }
__device__ __forceinline__ void mbar_expect(uint32_t a, int b) { asm volatile("mbarrier.arrive.expect_tx.shared::cta.b64 _, [%0], %1;" :: "r"(a), "r"(b) : "memory"); }
__device__ __forceinline__ void mbar_arrive(uint32_t a) { asm volatile("mbarrier.arrive.shared::cta.b64 _, [%0];" :: "r"(a) : "memory"); }
__device__ __forceinline__ void mbar_arrive_remote(uint32_t a) { asm volatile("mbarrier.arrive.shared::cluster.b64 _, [%0];" :: "r"(a) : "memory"); }
constexpr int SPIN_LIMIT = 1 << 19;
__device__ __forceinline__ bool mbar_try(uint32_t a, uint32_t ph) {
    uint32_t ok;
    asm volatile("{\n.reg .pred p;\nmbarrier.try_wait.parity.shared::cta.b64 p, [%1], %2;\nselp.u32 %0, 1, 0, p;\n}" : "=r"(ok) : "r"(a), "r"(ph) : "memory");
    return ok;
}
__device__ __forceinline__ bool mbar_test(uint32_t a) {
    uint32_t ok;
    asm volatile("{\n.reg .pred p;\nmbarrier.test_wait.parity.shared::cta.b64 p, [%1], 0;\nselp.u32 %0, 1, 0, p;\n}" : "=r"(ok) : "r"(a) : "memory");
    return ok;
}
__device__ __forceinline__ void mbar_wait(uint32_t a, uint32_t ph) {
    int n = SPIN_LIMIT;
#pragma unroll 1
    do { n = __all_sync(0xffffffffu, mbar_try(a, ph)) ? 0 : n - 1; } while (n > 0);
}
__device__ __forceinline__ bool elect_one() {
    uint32_t p;
    asm volatile("{\n.reg .pred P;\nelect.sync _|P, 0xffffffff;\nselp.u32 %0, 1, 0, P;\n}" : "=r"(p));
    return p;
}
__device__ __forceinline__ void signal_cnt(unsigned* cnt) {
    asm volatile("fence.release.gpu;\nred.relaxed.gpu.global.add.u32 [%0], 1;" :: "l"(cnt) : "memory");
}
__device__ __forceinline__ void wait_cnt(const unsigned* cnt, unsigned target, int ns) {
#pragma unroll 1
    for (int n = 0; n < SPIN_LIMIT; n++) {
        unsigned v;
        asm volatile("ld.relaxed.gpu.global.u32 %0, [%1];" : "=r"(v) : "l"(cnt) : "memory");
        if (__all_sync(0xffffffffu, (int)(v - target) >= 0)) break;
        __nanosleep(ns);
    }
}
__device__ __forceinline__ uint32_t ld_epoch(const Scratch* sc) {
    uint32_t e;
    asm volatile("ld.relaxed.gpu.global.u32 %0, [%1];" : "=r"(e) : "l"(sc->epoch + blockIdx.x) : "memory");
    return e;
}
__device__ __forceinline__ void st_relaxed(uint32_t* p, uint32_t v) { asm volatile("st.relaxed.gpu.global.u32 [%0], %1;" :: "l"(p), "r"(v) : "memory"); }
__device__ __forceinline__ void st_tagged(void* p, uint32_t v, uint32_t tag) {
    asm volatile("st.relaxed.gpu.global.b64 [%0], %1;" :: "l"(p), "l"((unsigned long long)tag << 32 | v) : "memory");
}
__device__ __forceinline__ uint32_t ld_tagged2(const ulonglong2* p, uint32_t tag, uint32_t& a, uint32_t& b) {
    unsigned long long u, v;
    asm volatile("ld.relaxed.gpu.global.v2.b64 {%0,%1}, [%2];" : "=l"(u), "=l"(v) : "l"(p) : "memory");
    a = (uint32_t)u; b = (uint32_t)v;
    return ((uint32_t)(u >> 32) ^ tag) | ((uint32_t)(v >> 32) ^ tag);
}
__device__ __forceinline__ void tma2d(uint32_t dst, const CUtensorMap* m, int c0, int c1, uint32_t bar) {
    asm volatile("cp.async.bulk.tensor.2d.shared::cluster.global.mbarrier::complete_tx::bytes [%0], [%1, {%3, %4}], [%2];"
                 :: "r"(dst), "l"(m), "r"(bar), "r"(c0), "r"(c1) : "memory");
}
__device__ __forceinline__ void tma2d_mc(uint32_t dst, const CUtensorMap* m, int c0, int c1, uint32_t bar) {
    asm volatile("cp.async.bulk.tensor.2d.shared::cluster.global.mbarrier::complete_tx::bytes.multicast::cluster [%0], [%1, {%3, %4}], [%2], %5;"
                 :: "r"(dst), "l"(m), "r"(bar), "r"(c0), "r"(c1), "h"((uint16_t)3) : "memory");
}
__device__ __forceinline__ void bulk_load(uint32_t dst, const void* src, int bytes, uint32_t bar) {
    asm volatile("cp.async.bulk.shared::cluster.global.mbarrier::complete_tx::bytes [%0], [%1], %2, [%3];"
                 :: "r"(dst), "l"(src), "r"(bytes), "r"(bar) : "memory");
}
__device__ __forceinline__ void bar_sync(int id, int n) { asm volatile("bar.sync %0, %1;" :: "r"(id), "r"(n) : "memory"); }
__device__ __forceinline__ void fence_async_smem() { asm volatile("fence.proxy.async.shared::cta;" ::: "memory"); }
__device__ __forceinline__ void fence_async_all() { asm volatile("fence.acquire.gpu;\nfence.proxy.async.global;" ::: "memory"); }
__device__ __forceinline__ void wg_fence() { asm volatile("wgmma.fence.sync.aligned;" ::: "memory"); }
__device__ __forceinline__ void wg_commit() { asm volatile("wgmma.commit_group.sync.aligned;" ::: "memory"); }
template <int N> __device__ __forceinline__ void wg_wait() { asm volatile("wgmma.wait_group.sync.aligned %0;" :: "n"(N) : "memory"); }
template <int N> __device__ __forceinline__ void pin(float* d) {
#pragma unroll
    for (int i = 0; i < N; i++) asm volatile("" : "+f"(d[i]) :: "memory");
}
template <int N> __device__ __forceinline__ void pin(uint32_t* d) {
#pragma unroll
    for (int i = 0; i < N; i++) asm volatile("" : "+r"(d[i]) :: "memory");
}
constexpr uint32_t SMEM_BASE = 1024;
__device__ __forceinline__ uint64_t mkdesc(uint32_t off, uint32_t lbo, uint32_t sbo, uint32_t swz) {
    return (uint64_t)((SMEM_BASE + off) >> 4) | ((uint64_t)(lbo >> 4) << 16) | ((uint64_t)(sbo >> 4) << 32) | ((uint64_t)swz << 62);
}
__device__ __forceinline__ float ex2f(float x) { float y; asm("ex2.approx.ftz.f32 %0, %1;" : "=f"(y) : "f"(x)); return y; }
__device__ __forceinline__ float rcpf(float x) { float y; asm("rcp.approx.ftz.f32 %0, %1;" : "=f"(y) : "f"(x)); return y; }
__device__ __forceinline__ uint32_t pack_bf16(float lo, float hi) { uint32_t r; asm("cvt.rn.bf16x2.f32 %0, %1, %2;" : "=r"(r) : "f"(hi), "f"(lo)); return r; }
__device__ __forceinline__ float bf_lo(uint32_t v) { return __uint_as_float(v << 16); }
__device__ __forceinline__ float bf_hi(uint32_t v) { return __uint_as_float(v & 0xFFFF0000u); }
__device__ __forceinline__ float bf_round(float x) { return __bfloat162float(__float2bfloat16_rn(x)); }
__device__ __forceinline__ float siluf(float g) { return g * rcpf(1.0f + ex2f(g * -1.4426950408889634f)); }

__device__ __forceinline__ void wgmma_ss_n128_zero(float* d, uint64_t da, uint64_t db) {
    asm volatile("wgmma.mma_async.sync.aligned.m64n128k16.f32.bf16.bf16 {"
        "%0,%1,%2,%3,%4,%5,%6,%7,%8,%9,%10,%11,%12,%13,%14,%15,%16,%17,%18,%19,%20,%21,%22,%23,%24,%25,%26,%27,%28,%29,%30,%31,%32,%33,%34,%35,%36,%37,%38,%39,"
        "%40,%41,%42,%43,%44,%45,%46,%47,%48,%49,%50,%51,%52,%53,%54,%55,%56,%57,%58,%59,%60,%61,%62,%63"
        "}, %64, %65, 0, 1, 1, 0, 1;\n"
        : "=f"(d[0]),"=f"(d[1]),"=f"(d[2]),"=f"(d[3]),"=f"(d[4]),"=f"(d[5]),"=f"(d[6]),"=f"(d[7]),"=f"(d[8]),"=f"(d[9]),"=f"(d[10]),"=f"(d[11]),"=f"(d[12]),
          "=f"(d[13]),"=f"(d[14]),"=f"(d[15]),"=f"(d[16]),"=f"(d[17]),"=f"(d[18]),"=f"(d[19]),"=f"(d[20]),"=f"(d[21]),"=f"(d[22]),"=f"(d[23]),"=f"(d[24]),
          "=f"(d[25]),"=f"(d[26]),"=f"(d[27]),"=f"(d[28]),"=f"(d[29]),"=f"(d[30]),"=f"(d[31]),"=f"(d[32]),"=f"(d[33]),"=f"(d[34]),"=f"(d[35]),"=f"(d[36]),
          "=f"(d[37]),"=f"(d[38]),"=f"(d[39]),"=f"(d[40]),"=f"(d[41]),"=f"(d[42]),"=f"(d[43]),"=f"(d[44]),"=f"(d[45]),"=f"(d[46]),"=f"(d[47]),"=f"(d[48]),
          "=f"(d[49]),"=f"(d[50]),"=f"(d[51]),"=f"(d[52]),"=f"(d[53]),"=f"(d[54]),"=f"(d[55]),"=f"(d[56]),"=f"(d[57]),"=f"(d[58]),"=f"(d[59]),"=f"(d[60]),
          "=f"(d[61]),"=f"(d[62]),"=f"(d[63])
        : "l"(da), "l"(db));
}
__device__ __forceinline__ void wgmma_ss_n128_acc(float* d, uint64_t da, uint64_t db) {
    asm volatile("wgmma.mma_async.sync.aligned.m64n128k16.f32.bf16.bf16 {"
        "%0,%1,%2,%3,%4,%5,%6,%7,%8,%9,%10,%11,%12,%13,%14,%15,%16,%17,%18,%19,%20,%21,%22,%23,%24,%25,%26,%27,%28,%29,%30,%31,%32,%33,%34,%35,%36,%37,%38,%39,"
        "%40,%41,%42,%43,%44,%45,%46,%47,%48,%49,%50,%51,%52,%53,%54,%55,%56,%57,%58,%59,%60,%61,%62,%63"
        "}, %64, %65, 1, 1, 1, 0, 1;\n"
        : "+f"(d[0]),"+f"(d[1]),"+f"(d[2]),"+f"(d[3]),"+f"(d[4]),"+f"(d[5]),"+f"(d[6]),"+f"(d[7]),"+f"(d[8]),"+f"(d[9]),"+f"(d[10]),"+f"(d[11]),"+f"(d[12]),
          "+f"(d[13]),"+f"(d[14]),"+f"(d[15]),"+f"(d[16]),"+f"(d[17]),"+f"(d[18]),"+f"(d[19]),"+f"(d[20]),"+f"(d[21]),"+f"(d[22]),"+f"(d[23]),"+f"(d[24]),
          "+f"(d[25]),"+f"(d[26]),"+f"(d[27]),"+f"(d[28]),"+f"(d[29]),"+f"(d[30]),"+f"(d[31]),"+f"(d[32]),"+f"(d[33]),"+f"(d[34]),"+f"(d[35]),"+f"(d[36]),
          "+f"(d[37]),"+f"(d[38]),"+f"(d[39]),"+f"(d[40]),"+f"(d[41]),"+f"(d[42]),"+f"(d[43]),"+f"(d[44]),"+f"(d[45]),"+f"(d[46]),"+f"(d[47]),"+f"(d[48]),
          "+f"(d[49]),"+f"(d[50]),"+f"(d[51]),"+f"(d[52]),"+f"(d[53]),"+f"(d[54]),"+f"(d[55]),"+f"(d[56]),"+f"(d[57]),"+f"(d[58]),"+f"(d[59]),"+f"(d[60]),
          "+f"(d[61]),"+f"(d[62]),"+f"(d[63])
        : "l"(da), "l"(db));
}
__device__ __forceinline__ void wgmma_ts_n128_acc(float* d, uint64_t da, uint64_t db) {
    asm volatile("wgmma.mma_async.sync.aligned.m64n128k16.f32.bf16.bf16 {"
        "%0,%1,%2,%3,%4,%5,%6,%7,%8,%9,%10,%11,%12,%13,%14,%15,%16,%17,%18,%19,%20,%21,%22,%23,%24,%25,%26,%27,%28,%29,%30,%31,%32,%33,%34,%35,%36,%37,%38,%39,"
        "%40,%41,%42,%43,%44,%45,%46,%47,%48,%49,%50,%51,%52,%53,%54,%55,%56,%57,%58,%59,%60,%61,%62,%63"
        "}, %64, %65, 1, 1, 1, 1, 0;\n"
        : "+f"(d[0]),"+f"(d[1]),"+f"(d[2]),"+f"(d[3]),"+f"(d[4]),"+f"(d[5]),"+f"(d[6]),"+f"(d[7]),"+f"(d[8]),"+f"(d[9]),"+f"(d[10]),"+f"(d[11]),"+f"(d[12]),
          "+f"(d[13]),"+f"(d[14]),"+f"(d[15]),"+f"(d[16]),"+f"(d[17]),"+f"(d[18]),"+f"(d[19]),"+f"(d[20]),"+f"(d[21]),"+f"(d[22]),"+f"(d[23]),"+f"(d[24]),
          "+f"(d[25]),"+f"(d[26]),"+f"(d[27]),"+f"(d[28]),"+f"(d[29]),"+f"(d[30]),"+f"(d[31]),"+f"(d[32]),"+f"(d[33]),"+f"(d[34]),"+f"(d[35]),"+f"(d[36]),
          "+f"(d[37]),"+f"(d[38]),"+f"(d[39]),"+f"(d[40]),"+f"(d[41]),"+f"(d[42]),"+f"(d[43]),"+f"(d[44]),"+f"(d[45]),"+f"(d[46]),"+f"(d[47]),"+f"(d[48]),
          "+f"(d[49]),"+f"(d[50]),"+f"(d[51]),"+f"(d[52]),"+f"(d[53]),"+f"(d[54]),"+f"(d[55]),"+f"(d[56]),"+f"(d[57]),"+f"(d[58]),"+f"(d[59]),"+f"(d[60]),
          "+f"(d[61]),"+f"(d[62]),"+f"(d[63])
        : "l"(da), "l"(db));
}
__device__ __forceinline__ void wgmma_ts_n64_acc(float* d, uint64_t da, uint64_t db) {
    asm volatile("wgmma.mma_async.sync.aligned.m64n64k16.f32.bf16.bf16 {"
        "%0,%1,%2,%3,%4,%5,%6,%7,%8,%9,%10,%11,%12,%13,%14,%15,%16,%17,%18,%19,%20,%21,%22,%23,%24,%25,%26,%27,%28,%29,%30,%31"
        "}, %32, %33, 1, 1, 1, 1, 0;\n"
        : "+f"(d[0]),"+f"(d[1]),"+f"(d[2]),"+f"(d[3]),"+f"(d[4]),"+f"(d[5]),"+f"(d[6]),"+f"(d[7]),"+f"(d[8]),"+f"(d[9]),"+f"(d[10]),"+f"(d[11]),"+f"(d[12]),
          "+f"(d[13]),"+f"(d[14]),"+f"(d[15]),"+f"(d[16]),"+f"(d[17]),"+f"(d[18]),"+f"(d[19]),"+f"(d[20]),"+f"(d[21]),"+f"(d[22]),"+f"(d[23]),"+f"(d[24]),
          "+f"(d[25]),"+f"(d[26]),"+f"(d[27]),"+f"(d[28]),"+f"(d[29]),"+f"(d[30]),"+f"(d[31])
        : "l"(da), "l"(db));
}
__device__ __forceinline__ void wgmma_rs_n64_zero(float* d, const uint32_t* a, uint64_t db) {
    asm volatile("wgmma.mma_async.sync.aligned.m64n64k16.f32.bf16.bf16 {"
        "%0,%1,%2,%3,%4,%5,%6,%7,%8,%9,%10,%11,%12,%13,%14,%15,%16,%17,%18,%19,%20,%21,%22,%23,%24,%25,%26,%27,%28,%29,%30,%31"
        "}, {%32,%33,%34,%35}, %36, 0, 1, 1, 0;\n"
        : "=f"(d[0]),"=f"(d[1]),"=f"(d[2]),"=f"(d[3]),"=f"(d[4]),"=f"(d[5]),"=f"(d[6]),"=f"(d[7]),"=f"(d[8]),"=f"(d[9]),"=f"(d[10]),"=f"(d[11]),"=f"(d[12]),
          "=f"(d[13]),"=f"(d[14]),"=f"(d[15]),"=f"(d[16]),"=f"(d[17]),"=f"(d[18]),"=f"(d[19]),"=f"(d[20]),"=f"(d[21]),"=f"(d[22]),"=f"(d[23]),"=f"(d[24]),
          "=f"(d[25]),"=f"(d[26]),"=f"(d[27]),"=f"(d[28]),"=f"(d[29]),"=f"(d[30]),"=f"(d[31])
        : "r"(a[0]), "r"(a[1]), "r"(a[2]), "r"(a[3]), "l"(db));
}
__device__ __forceinline__ void wgmma_rs_n64_acc(float* d, const uint32_t* a, uint64_t db) {
    asm volatile("wgmma.mma_async.sync.aligned.m64n64k16.f32.bf16.bf16 {"
        "%0,%1,%2,%3,%4,%5,%6,%7,%8,%9,%10,%11,%12,%13,%14,%15,%16,%17,%18,%19,%20,%21,%22,%23,%24,%25,%26,%27,%28,%29,%30,%31"
        "}, {%32,%33,%34,%35}, %36, 1, 1, 1, 0;\n"
        : "+f"(d[0]),"+f"(d[1]),"+f"(d[2]),"+f"(d[3]),"+f"(d[4]),"+f"(d[5]),"+f"(d[6]),"+f"(d[7]),"+f"(d[8]),"+f"(d[9]),"+f"(d[10]),"+f"(d[11]),"+f"(d[12]),
          "+f"(d[13]),"+f"(d[14]),"+f"(d[15]),"+f"(d[16]),"+f"(d[17]),"+f"(d[18]),"+f"(d[19]),"+f"(d[20]),"+f"(d[21]),"+f"(d[22]),"+f"(d[23]),"+f"(d[24]),
          "+f"(d[25]),"+f"(d[26]),"+f"(d[27]),"+f"(d[28]),"+f"(d[29]),"+f"(d[30]),"+f"(d[31])
        : "r"(a[0]), "r"(a[1]), "r"(a[2]), "r"(a[3]), "l"(db));
}
__device__ __forceinline__ void wgmma_rs_n24_acc(float* d, const uint32_t* a, uint64_t db) {
    asm volatile("wgmma.mma_async.sync.aligned.m64n24k16.f32.bf16.bf16 {"
        "%0,%1,%2,%3,%4,%5,%6,%7,%8,%9,%10,%11"
        "}, {%12,%13,%14,%15}, %16, 1, 1, 1, 1;\n"
        : "+f"(d[0]),"+f"(d[1]),"+f"(d[2]),"+f"(d[3]),"+f"(d[4]),"+f"(d[5]),"+f"(d[6]),"+f"(d[7]),"+f"(d[8]),"+f"(d[9]),"+f"(d[10]),"+f"(d[11])
        : "r"(a[0]), "r"(a[1]), "r"(a[2]), "r"(a[3]), "l"(db));
}

constexpr int OFF_ONES = 131072;
constexpr int OFF_RING = OFF_ONES + 4096;
constexpr int NRING = 5;
constexpr int OFF_B2 = OFF_RING + NRING * 16384;
constexpr int OFF_CS = OFF_B2 + 2048;
constexpr int OFF_RS = OFF_CS + 2560;
constexpr int OFF_BAR = OFF_RS + 512;
enum { B_FULL = 0,
       B_EMPTY = 40, B_TILE = 80, B_OW = 85, B_DONE = 87,
       B_O2 = 90, B_QKV = 98,
       B_KV = 100, B_T1 = 103, B_WO = 108, B_STATS = 110, B_O = 115,
       B_DN = 120,
       B_NUM = 148 };
constexpr int OFF_TS = OFF_BAR + 1280;
constexpr int SMEM_BYTES = OFF_BAR + B_NUM * 8;
constexpr unsigned FIXED_MASK = 0x1F;
constexpr float P71 = 2361183241434822606848.0f, M71 = 4.235164736271502e-22f;

__device__ __forceinline__ uint32_t exp2_fixed(float lo, float hi, uint32_t half2) {
    uint32_t y, g, d;
    asm("cvt.pack.sat.s16.s32 %0, %1, %2;" : "=r"(y) : "r"(__float_as_uint(hi)), "r"(__float_as_uint(lo)));
    asm("lop3.b32 %0, %1, 0x007F007F, %2, 0xEA;" : "=r"(g) : "r"(y), "r"(half2));
    asm("fma.rn.bf16x2 %0, %1, %2, %3;" : "=r"(d) : "r"(y), "r"(g), "r"(y & 0xFF80FF80u));
    return d;
}
constexpr uint64_t DK_STEP = 512 - (256ull << 16), DV_STEP = 512 - (256ull << 32);
constexpr uint32_t POS_LAST = 0x37521640u;
#define OPQ 1

struct WorkMap { int v[64]; };

__global__ void __cluster_dims__(2, 1, 1) __launch_bounds__(640, 1)
mega_kernel(const __nv_bfloat16* __restrict__ x, const __nv_bfloat16* __restrict__ wqkv, const __nv_bfloat16* __restrict__ w1,
            const __nv_bfloat16* __restrict__ w3, __nv_bfloat16* __restrict__ out, Scratch* sc,
            const __grid_constant__ WorkMap wmap,
            const __grid_constant__ CUtensorMap mx, const __grid_constant__ CUtensorMap mqkv, const __grid_constant__ CUtensorMap mw1,
            const __grid_constant__ CUtensorMap mw3, const __grid_constant__ CUtensorMap mw2, const __grid_constant__ CUtensorMap mwo) {
    extern __shared__ __align__(1024) uint8_t smem_raw[];
    const uint32_t sb = __shfl_sync(0xffffffffu, smem_u32(smem_raw), 0);
    const uint32_t bars = sb + OFF_BAR, ring = sb + OFF_RING;
    const int tid = threadIdx.x, lane = tid & 31, g = lane >> 2, t4 = lane & 3;
    const int warp = __shfl_sync(0xffffffffu, tid >> 5, 0), wg = warp >> 2, wq = warp & 3;
    const int rank = blockIdx.x & 1, wm = wmap.v[blockIdx.x >> 1];
    const int rot = wm & 255, mblk = rot * 2 + rank, gu0 = (wm >> 16) & 255;
    if (warp == 0) {
        if (elect_one()) {
            mbar_init(bars, 1); mbar_init(bars + 8, 1);
            fence_async_smem();
#pragma unroll
            for (int j = 0; j < 2; j++) {
                tma2d(sb + j * 16384, &mx, j * 64, mblk * 128, bars + 8 * (B_FULL + j));
                tma2d(ring + j * 16384, &mw1, gu0 * 64, j * 64, bars + 8 * (B_FULL + j));
                tma2d(ring + j * 16384 + 8192, &mw3, gu0 * 64, j * 64, bars + 8 * (B_FULL + j));
            }
            mbar_expect(bars, 32768); mbar_expect(bars + 8, 32768);
            TSTAMP(46);
        }
    }
    const int grp = (wm >> 8) & 255, qt0 = wm >> 24, nq = grp < 4 ? 2 : 1;
    auto is_qkv = [&](int t) { return (unsigned)(t - 1) < (unsigned)nq; };
    auto unit_of = [&](int t) { return t ? gu0 + t - nq : gu0; };
    if (warp == 16) {
        if (elect_one()) {
#pragma unroll
            for (int i = 2; i < 5; i++) mbar_init(bars + 8 * i, 1);
#pragma unroll
            for (int i = 2; i < 5; i++) mbar_expect(bars + 8 * i, 32768);
            asm volatile("fence.mbarrier_init.release.cluster;" ::: "memory");
        }
        __syncwarp();
        asm volatile("bar.arrive 0, 640;\nbarrier.cluster.arrive.relaxed.aligned;" ::: "memory");
        asm volatile("barrier.cluster.wait.aligned;" ::: "memory");
        if (tid == 512) TSTAMP(27);
        uint32_t slot = 2;
#pragma unroll 1
        for (int n = 2; n < 40; n++) {
            const int t = n >> 3, j = n & 7;
            const int kc = (n < 32 ? j : (POS_LAST >> (4 * j)) & 7) * 64;
            const CUtensorMap* m = is_qkv(t) ? &mqkv : rank ? &mw3 : &mw1;
            const int col = is_qkv(t) ? (qt0 + t) * 128 + rank * 64 : unit_of(t) * 64;
            const uint32_t dst = ring + slot * 16384 + rank * 8192, fb = bars + 8 * (B_FULL + n);
            if (n < 8 && elect_one()) tma2d(sb + n * 16384, &mx, kc, mblk * 128, fb);
            if (n >= NRING) mbar_wait(fb + 8 * (B_EMPTY - NRING), 0);
            if (elect_one()) {
                tma2d_mc(dst, m, col, kc, fb); }
            if (++slot == NRING) slot = 0;
        }
    } else {
        if (warp && elect_one()) {
            const uint32_t b0 = bars + (warp < 16 ? warp * 40 : warp * 80 - 640), cnt = warp < 8 || warp > 17 ? 1 : warp == 17 ? 2 : 8;
#pragma unroll
            for (int i = 0; i < 5; i++) mbar_init(b0 + 8 * i, cnt);
            if (warp < 8) {
#pragma unroll
                for (int i = 0; i < 5; i++) mbar_expect(b0 + 8 * i, i < 3 && warp == 1 ? 32768 : 16384);
            } else if (warp >= 14) {
                const uint32_t b1 = b0 + (warp < 16 ? 80 : 40);
#pragma unroll
                for (int i = 0; i < 5; i++) mbar_init(b1 + 8 * i, cnt);
            }
            asm volatile("fence.mbarrier_init.release.cluster;" ::: "memory");
        }
        __syncwarp();
        asm volatile("barrier.cluster.arrive.relaxed.aligned;" ::: "memory");
        bar_sync(0, 640);
        if (tid == 0) TSTAMP(26);
    }
    if ((sb & 0xFFFFFF) != SMEM_BASE) __trap();
    const int lid = blockIdx.x, head = lid >> 2, qb = lid & 3;
    const int cb = lid & 7, rb0 = (lid >> 5) * 8 + ((lid >> 3) & 3);

    if (wg < 4) {
        const int pair = (wg >> 1) ^ 1, half = wg & 1, w8 = warp & 7;
        if (pair == 1) {
            const int row = mblk * 128 + grp * 16 + w8 * 2 + (lane >> 4);
            uint4 v[6];
            const uint32_t* w = reinterpret_cast<const uint32_t*>(v);
#pragma unroll
            for (int j = 0; j < 2; j++) v[4 + j] = __ldg(reinterpret_cast<const uint4*>((rank ? w3 : w1) + (size_t)(rot * 64 + w8 * 8 + j * 4 + (lane >> 3)) * FF + gu0 * 64) + (lane & 7));
#pragma unroll
            for (int j = 0; j < 4; j++) v[j] = __ldg(reinterpret_cast<const uint4*>(x + (size_t)row * DM) + j * 16 + (lane & 15));
            const uint32_t tag = ld_epoch(sc) + 1;
            float c[8];
#pragma unroll
            for (int e = 0; e < 4; e++) { c[2 * e] = bf_lo(w[16 + e]) + bf_lo(w[20 + e]); c[2 * e + 1] = bf_hi(w[16 + e]) + bf_hi(w[20 + e]); }
#pragma unroll
            for (int n = 4; n > 1; n >>= 1) {
                const bool up = lane & (4 * n);
#pragma unroll
                for (int e = 0; e < n; e++) c[e] = (up ? c[e + n] : c[e]) + __shfl_xor_sync(0xffffffffu, up ? c[e] : c[e + n], 4 * n);
            }
            asm volatile("st.shared.v2.f32 [%0], {%1,%2};" :: "r"(sb + OFF_CS + 512 + w8 * 256 + (lane & 7) * 32 + (lane >> 3) * 8), "f"(c[0]), "f"(c[1]) : "memory");
            bar_sync(6, 256);
            if (w8 < 2) {
#pragma unroll
                for (int e = 0; e < 8; e++) asm volatile("ld.shared.f32 %0, [%1];" : "=f"(c[e]) : "r"(sb + OFF_CS + 512 + e * 256 + (tid & 63) * 4));
                st_tagged(reinterpret_cast<unsigned long long*>(sc->cs) + (grp * 40 + rot) * 128 + rank * 64 + (tid & 63),
                          __float_as_uint(((c[0] + c[1]) + (c[2] + c[3])) + ((c[4] + c[5]) + (c[6] + c[7]))), tag);
                if ((tid & 255) == 0) TSTAMP(40);
            }
            float sa[4] = {0.f, 0.f, 0.f, 0.f}, sq[4] = {0.f, 0.f, 0.f, 0.f};
#pragma unroll
            for (int j = 0; j < 16; j++) sa[j & 3] += bf_lo(w[j]) + bf_hi(w[j]);
            float mean = ((sa[0] + sa[1]) + (sa[2] + sa[3])) * (1.0f / 32);
#pragma unroll
            for (int j = 0; j < 16; j++) { const float a = bf_lo(w[j]) - mean, b = bf_hi(w[j]) - mean; sq[j & 1] = fmaf(a, a, sq[j & 1]); sq[2 + (j & 1)] = fmaf(b, b, sq[2 + (j & 1)]); }
            float m2 = (sq[0] + sq[1]) + (sq[2] + sq[3]);
#pragma unroll
            for (int d = 1; d < 16; d <<= 1) {
                const float om = __shfl_xor_sync(0xffffffffu, mean, d), o2 = __shfl_xor_sync(0xffffffffu, m2, d), dm = mean - om;
                m2 = fmaf(dm * dm, 16.0f * d, m2 + o2); mean = 0.5f * (mean + om);
            }
            float sd;
            asm("sqrt.approx.f32 %0, %1;" : "=f"(sd) : "f"(bf_round(bf_round(m2 * (1.0f / DM)) + 1e-5f)));
            if ((lane & 15) == 0) st_tagged(reinterpret_cast<unsigned long long*>(sc->rs) + row, pack_bf16(mean, sd), tag);
            if ((tid & 255) == 0) TSTAMP(45);
        }

        uint32_t q[4], qn[4];
        {
            const int rowblk = mblk * 2 + half, tile16 = rowblk * 4 + wq;
            uint32_t empty;
            asm("mapa.shared::cluster.u32 %0, %1, %2;" : "=r"(empty) : "r"(bars + 8 * B_EMPTY), "r"(wq & 1));
#pragma unroll 1
            for (int t = pair; t < 5; t += 2) {
                float acc[64];
                uint32_t full = bars + 8 * (B_FULL + 8 * t), rel = empty + 64 * t;
                uint32_t stepa = t == 4 ? 0x4AB93AC : 0x9999999, stepb = (uint32_t)(0x994999949999ull >> (4 * ((0x24130u >> (4 * t)) & 7)));
                uint64_t da = mkdesc(half * 8192, 16, 1024, 1), db = mkdesc(OFF_RING, 8192, 1024, 1) + ((0x24130u >> (4 * t)) & 7) * 1024;
                if ((tid & 255) == 0 && t == 0) TSTAMP(30);
                mbar_wait(full, 0);
                if ((tid & 255) == 0 && t == 0) TSTAMP(1);
                if (t > 0) mbar_wait(full + 8 * (B_EMPTY - 2), 0);
                wg_fence();
                wgmma_ss_n128_zero(acc, da, db);
#pragma unroll
                for (int k = 1; k < 4; k++) wgmma_ss_n128_acc(acc, da + k * 2, db + k * 128);
                wg_commit();
                mbar_wait(full + 8, 0);
#pragma unroll 1
                do {
                    da += (int)((stepa & 15) << 10) - 8192; db += (int)((stepb & 15) << 10) - 8192;
                    stepa >>= 4; stepb >>= 4;
                    wg_fence();
#pragma unroll
                    for (int k = 0; k < 4; k++) wgmma_ss_n128_acc(acc, da + k * 2, db + k * 128);
                    wg_commit();
                    mbar_wait(full + 16, 0);
                    wg_wait<1>();
                    if (elect_one()) mbar_arrive_remote(rel);
                    full += 8; rel += 8;
                } while (stepa);
                auto fetch_q = [&]() {
                    mbar_wait(bars + 8 * B_QKV, 0);
                    const uint4* pq = sc->q + (head * 128 + (qb * 8 + wg) * 4 + wq) * 32 + lane;
                    const uint4 v = __ldcg(pq), u = __ldcg(pq + 512);
                    q[0] = v.x; q[1] = v.y; q[2] = v.z; q[3] = v.w; qn[0] = u.x; qn[1] = u.y; qn[2] = u.z; qn[3] = u.w;
                };
                if (t == 4) fetch_q();
                wg_wait<0>();
                if (elect_one()) mbar_arrive_remote(rel);
                pin<64>(acc);
                if (wq == 0 && half == 0 && lane == 0) TSTAMP(2 + 2 * t);
                if ((tid & 255) == 0 && t == 4) GSTAMP(10);
                mbar_wait(bars + 8 * (B_STATS + t), 0);
                uint32_t rs0, rs1;
                asm volatile("ld.shared.b32 %0, [%1];" : "=r"(rs0) : "r"(sb + OFF_RS + (half * 64 + wq * 16 + g) * 4));
                asm volatile("ld.shared.b32 %0, [%1];" : "=r"(rs1) : "r"(sb + OFF_RS + (half * 64 + wq * 16 + g + 8) * 4));
                const float m0 = bf_lo(rs0), m1 = bf_lo(rs1);
                float d0 = bf_hi(rs0), d1 = bf_hi(rs1);
                float r0 = rcpf(d0), r1 = rcpf(d1);
                const uint32_t pcs = sb + OFF_CS + t * 512 + t4 * 8;
                auto lds2 = [&](int j, float* c) { asm volatile("ld.shared.v2.f32 {%0,%1}, [%2];" : "=f"(c[0]), "=f"(c[1]) : "r"(pcs + j * 32) : "memory"); };
                auto fix = [&](float* a, const float* c) { a[0] = fmaf(-m0, c[0], a[0]); a[1] = fmaf(-m0, c[1], a[1]); a[2] = fmaf(-m1, c[0], a[2]); a[3] = fmaf(-m1, c[1], a[3]); };
                float c[2][4];
                if (is_qkv(t)) {
                    const int qt = qt0 + t;
                    if (qt < 4) {
                        r0 *= 0.25f * 1.4426950408889634f * M71; r1 *= 0.25f * 1.4426950408889634f * M71;
                    } else if (qt < 8) {
                        r0 *= ((FIXED_MASK >> (2 * wq)) & 1) ? M71 : P71; r1 *= ((FIXED_MASK >> (2 * wq + 1)) & 1) ? M71 : P71;
                    }
                    uint8_t* p = qt < 4 ? reinterpret_cast<uint8_t*>(sc->q + (qt * 1024 + tile16) * 32 + lane)
                                        : reinterpret_cast<uint8_t*>(sc->kv + (qt - 4) * 32768) + tile16 * 256 + lane * 4;
                    lds2(0, c[0]); lds2(1, c[0] + 2);
#pragma unroll
                    for (int hh = 0; hh < 8; hh++) {
                        if (hh < 7) { lds2(2 * hh + 2, c[~hh & 1]); lds2(2 * hh + 3, c[~hh & 1] + 2); }
                        float* a = acc + hh * 8;
                        fix(a, c[hh & 1]); fix(a + 4, c[hh & 1] + 2);
                        asm volatile("{\n.reg .pred p;\nsetp.lt.s32 p, %5, 4;\n@p st.global.v4.b32 [%0], {%1,%2,%3,%4};\n"
                                     "@!p st.global.b32 [%0], %1;\n@!p st.global.b32 [%0+128], %2;\n@!p st.global.b32 [%0+32768], %3;\n@!p st.global.b32 [%0+32896], %4;\n}"
                                     :: "l"(p + hh * 65536), "r"(pack_bf16(a[0] * r0, a[1] * r0)), "r"(pack_bf16(a[2] * r1, a[3] * r1)),
                                        "r"(pack_bf16(a[4] * r0, a[5] * r0)), "r"(pack_bf16(a[6] * r1, a[7] * r1)), "r"(qt) : "memory");
                    }
                } else {
                    uint32_t* p = reinterpret_cast<uint32_t*>(sc->h + ((((rowblk >> 3) * 4 + (rowblk & 3)) * 28 + unit_of(t)) * 2 + ((rowblk >> 2) & 1)) * 512) + wq * 512 + lane;
                    r0 *= -1.4426950408889634f; r1 *= -1.4426950408889634f; d0 *= d0; d1 *= d1;
                    lds2(0, c[0]); lds2(8, c[0] + 2);
#pragma unroll
                    for (int j = 0; j < 8; j++) {
                        if (j < 7) { lds2(j + 1, c[~j & 1]); lds2(j + 9, c[~j & 1] + 2); }
                        float* a = acc + j * 4; float* b = a + 32;
                        fix(a, c[j & 1]); fix(b, c[j & 1] + 2);
                        p[j * 32] = pack_bf16(a[0] * b[0] * rcpf(fmaf(ex2f(a[0] * r0), d0, d0)), a[1] * b[1] * rcpf(fmaf(ex2f(a[1] * r0), d0, d0)));
                        p[256 + j * 32] = pack_bf16(a[2] * b[2] * rcpf(fmaf(ex2f(a[2] * r1), d1, d1)), a[3] * b[3] * rcpf(fmaf(ex2f(a[3] * r1), d1, d1)));
                    }
                }
                __syncwarp();
                if (elect_one()) mbar_arrive(bars + 8 * (B_TILE + t));
                if (t == 3) fetch_q();
                if (wq == 0 && half == 0 && lane == 0) TSTAMP(3 + 2 * t);
            }
        }
        const uint64_t db2 = mkdesc(OFF_B2, 128, 256, 0) - (sb >> 28);
        const uint64_t DK0 = mkdesc(4096, 94208, 128, 0);
        const uint32_t half2 = 0x3F003F00u + __shfl_sync(0xffffffffu, lane, 0);
        uint32_t q2[4], chk_bar = bars + 8 * (B_KV + 1);
        uint32_t* po = reinterpret_cast<uint32_t*>(sc->o + ((qb * 8 + wg) * 8 + (head >> 2)) * 512) + wq * 512 + (head & 3) * 64 + lane;
        int redo = 0;
        mbar_wait(bars + 8 * B_KV, 0);
#pragma unroll 1
        for (int round = 0; round < 2;) {
            float s[32];
            float mq[2];
            if (!redo) {
                wg_fence();
                wgmma_rs_n64_zero(s, q, DK0);
                wg_commit();
                wg_wait<0>();
                pin<32>(s);
#pragma unroll
                for (int r = 0; r < 2; r++) {
                    int m = INT_MIN;
#pragma unroll
                    for (int i = 0; i < 8; i++) if ((FIXED_MASK >> i) & 1) m = __vimax3_s32(m, __float_as_int(s[4 * i + 2 * r]), __float_as_int(s[4 * i + 2 * r + 1]));
                    mq[r] = __int_as_float(m & ~3) * (-0.25f * P71);
                }
            } else {
                float m0 = -INFINITY, m1 = -INFINITY, f0 = -INFINITY, f1 = -INFINITY;
#pragma unroll 1
                for (int t = redo - 1; t >= 0; t--) {
                    wg_fence();
                    wgmma_rs_n64_zero(s, q, DK0 + (t >> 2) * DK_STEP + (t & 3) * 64);
                    wg_commit();
                    wg_wait<0>();
                    pin<32>(s);
#pragma unroll
                    for (int i = 0; i < 8; i++) {
                        if ((FIXED_MASK >> i) & 1) { f0 = fmaxf(f0, fmaxf(s[4 * i], s[4 * i + 1])); f1 = fmaxf(f1, fmaxf(s[4 * i + 2], s[4 * i + 3])); }
                        else                       { m0 = fmaxf(m0, fmaxf(s[4 * i], s[4 * i + 1])); m1 = fmaxf(m1, fmaxf(s[4 * i + 2], s[4 * i + 3])); }
                    }
                }
                m0 = fmaxf(m0, f0 * P71 * P71); m1 = fmaxf(m1, f1 * P71 * P71);
                m0 = fmaxf(m0, __shfl_xor_sync(0xffffffffu, m0, 1)); m1 = fmaxf(m1, __shfl_xor_sync(0xffffffffu, m1, 1));
                m0 = fmaxf(m0, __shfl_xor_sync(0xffffffffu, m0, 2)); m1 = fmaxf(m1, __shfl_xor_sync(0xffffffffu, m1, 2));
                mq[0] = (floorf(m0) - 64.f) * (-0.25f * M71); mq[1] = (floorf(m1) - 64.f) * (-0.25f * M71);
            }
#pragma unroll
            for (int r = 0; r < 2; r++) {
                const float r1 = mq[r] - bf_hi(__float_as_uint(mq[r])), r2 = r1 - bf_hi(__float_as_uint(r1));
                q2[r] = __byte_perm(__float_as_uint(mq[r]), __float_as_uint(r1), 0x7632);
                q2[2 + r] = __byte_perm(__float_as_uint(r2), __float_as_uint(M71), 0x7632);
            }
            float o[12]; uint32_t p[16];
#pragma unroll
            for (int i = 0; i < 12; i++) o[i] = 0.f;
            pin<12>(o); pin<4>(q2);
            if (wq == 0 && half == 0 && lane == 0) TSTAMP(12 + 4 * round + pair);
            uint64_t dk = DK0, dv = mkdesc(0, 128, 65536, 0);
            wg_fence();
            wgmma_rs_n64_acc(s, q2, db2);
            wg_commit();
#pragma unroll 1
            for (uint32_t todo = redo ? 0x100 : round ? 0x180 : 0x103;; dk += DK_STEP, dv += DV_STEP) {
                if (todo & 1) { mbar_wait(chk_bar, 0); chk_bar += 8; }
                todo >>= 1;
#pragma unroll
                for (int t = 0; t < 4; t++) {
                    wg_wait<0>();
                    pin<32>(s); pin<16>(p);
#pragma unroll
                    for (int i = 0; i < 16; i++) {
                        if ((FIXED_MASK >> (i >> 1)) & 1) p[i] = exp2_fixed(s[2 * i], s[2 * i + 1], half2);
                        else                              p[i] = pack_bf16(ex2f(s[2 * i]), ex2f(s[2 * i + 1]));
                    }
                    if (t == 3 && todo == 1) goto last_tile;
                    wg_fence();
#pragma unroll
                    for (int k = 0; k < 4; k++) wgmma_rs_n24_acc(o, p + 4 * k, dv + (t * 4 + k) * 16);
                    wgmma_rs_n64_zero(s, q, t == 3 ? dk + DK_STEP : dk + (t + 1) * 64);
                    wgmma_rs_n64_acc(s, q2, db2);
                    wg_commit();
                }
            }
        last_tile:
            wg_fence();
#pragma unroll
            for (int k = 0; k < 4; k++) wgmma_rs_n24_acc(o, p + 4 * k, dv + (12 + k) * 16);
            wg_commit();
            wg_wait<0>();
            pin<12>(o);
            const float r0 = rcpf(o[8]), r1 = rcpf(o[10]);
#pragma unroll
            for (int i = 0; i < 8; i++) o[i] *= (i & 2) ? r1 : r0;
            if (!redo) {
                const float chk = fmaf(o[0], o[1], fmaf(o[2], o[3], o[8] * 4.f)) + fmaf(o[4], o[5], fmaf(o[6], o[7], o[10] * 4.f));
                uint32_t bad;
                asm volatile("{\n.reg .pred p, q;\nsetp.geu.f32 q, %1, 0f7F800000;\nbar.red.or.pred p, %2, 128, q;\nselp.u32 %0, 1, 0, p;\n}" : "=r"(bad) : "f"(fabsf(chk)), "r"(1 + wg) : "memory");
                redo = __popc(__ballot_sync(0xffffffffu, bad));
                if (redo) continue;
            }
            st_relaxed(po, pack_bf16(o[0], o[1])); st_relaxed(po + 256, pack_bf16(o[2], o[3]));
            st_relaxed(po + 32, pack_bf16(o[4], o[5])); st_relaxed(po + 288, pack_bf16(o[6], o[7]));
            if (round == 0) {
                po += 4 * 8 * 2048;
                st_relaxed(po, ~0u); st_relaxed(po + 256, ~0u); st_relaxed(po + 32, ~0u); st_relaxed(po + 288, ~0u);
            }
            __syncwarp();
            if (elect_one()) mbar_arrive(bars + 8 * (B_OW + 2 * round + (wg >> 1)));
#pragma unroll
            for (int i = 0; i < 4; i++) q[i] = qn[i];
            redo = 0;
            if (wq == 0 && half == 0 && lane == 0) TSTAMP(14 + 4 * round + pair);
            if (wq == 0 && lane == 0) GSTAMP(round * 4 + wg);
            round++;
        }
        if (lane == 0) TS3(1, warp);
        uint4 v[8];
        const uint4* osrc = sc->o + (rb0 + 4) * 4096 + (warp >> 1) * 512 + (warp & 1) * 32;
        bool dead = false;
#pragma unroll 1
        for (int n = 0; n < SPIN_LIMIT; n++) {
#pragma unroll 1
            for (; n < SPIN_LIMIT; n++) {
                uint32_t w;
                asm volatile("ld.relaxed.gpu.global.u32 %0, [%1+124];" : "=r"(w) : "l"(osrc + 7 * 64 + (lane & 16) + 8) : "memory");
                if (__all_sync(0xffffffffu, w != ~0u)) break;
            }
#pragma unroll
            for (int i = 0; i < 8; i++)
                asm volatile("ld.relaxed.gpu.global.v4.u32 {%0,%1,%2,%3}, [%4];" : "=r"(v[i].x), "=r"(v[i].y), "=r"(v[i].z), "=r"(v[i].w) : "l"(osrc + i * 64 + lane) : "memory");
            dead = __all_sync(0xffffffffu, mbar_test(bars + 8 * B_DONE) & mbar_test(bars + 8 * (B_DONE + 1)));
            uint32_t m0 = 0, m1 = 0;
#pragma unroll
            for (int i = 0; i < 8; i++) { m0 = __vimax3_u32(m0, v[i].x, v[i].y); m1 = __vimax3_u32(m1, v[i].z, v[i].w); }
            if (__all_sync(0xffffffffu, max(m0, m1) != ~0u)) break;
        }
        if (lane == 0) TS3(2, warp);
        if (!dead) { mbar_wait(bars + 8 * B_DONE, 0); mbar_wait(bars + 8 * (B_DONE + 1), 0); }
#pragma unroll
        for (int i = 0; i < 8; i++)
            asm volatile("st.shared.v4.b32 [%0], {%1,%2,%3,%4};" :: "r"(sb + (warp >> 1) * 8192 + (warp & 1) * 512 + i * 1024 + lane * 16), "r"(v[i].x), "r"(v[i].y), "r"(v[i].z), "r"(v[i].w) : "memory");
        if (lane == 0) TS3(2, 16 + warp);
        fence_async_smem();
        __syncwarp();
        if (elect_one()) mbar_arrive(bars + 8 * (B_O2 + (warp >> 1)));
        if (lane == 0) TS3(2, 32 + warp);
        if (tid == 0) TSTAMP(24);
        if (lane == 0) GSTAMP(16 + warp);
    } else {
        uint32_t tag;
        if (wq == 0) {
            tag = ld_epoch(sc) + 1;
            wait_cnt(sc->cnt + (C_H + (rb0 >> 1)) * 8, 28 * tag, 100);
            wait_cnt(sc->cnt + (C_H + (rb0 >> 1) + 2) * 8, 28 * tag, 100);
            fence_async_all();
        } else if (!(warp & 2)) {
            if (elect_one()) asm volatile("prefetch.tensormap [%0];" :: "l"(&mqkv) : "memory");
            tag = ld_epoch(sc) + 1;
            mbar_wait(bars + 8 * (B_FULL + 7), 0);
#pragma unroll 1
            for (int t = 0; t < 5; t++) {
                float a[4];
#pragma unroll 1
                for (int n = 0; n < SPIN_LIMIT; n++) {
                    uint32_t stale = 0;
                    a[0] = a[1] = a[2] = a[3] = 0.f;
#pragma unroll
                    for (int i = 0; i < 16; i++) {
                        uint32_t u, v;
                        stale |= ld_tagged2(sc->cs + (grp * 5 + t) * 512 + i * 32 + lane, tag, u, v);
                        a[(i & 1) * 2] += __uint_as_float(u); a[(i & 1) * 2 + 1] += __uint_as_float(v);
                    }
                    if (__all_sync(0xffffffffu, stale == 0)) break;
                    if (t) __nanosleep(400);
                }
                asm volatile("st.shared.v2.f32 [%0], {%1,%2};" :: "r"(sb + OFF_CS + t * 512 + lane * 8), "f"(a[0]), "f"(a[1]) : "memory");
                asm volatile("st.shared.v2.f32 [%0], {%1,%2};" :: "r"(sb + OFF_CS + t * 512 + 256 + lane * 8), "f"(a[2]), "f"(a[3]) : "memory");
                if (t == 0) {
                    uint32_t r[4];
#pragma unroll 1
                    for (int n = 0; n < SPIN_LIMIT; n++) {
                        const uint32_t stale = ld_tagged2(sc->rs + mblk * 64 + lane * 2, tag, r[0], r[1]) | ld_tagged2(sc->rs + mblk * 64 + lane * 2 + 1, tag, r[2], r[3]);
                        if (__all_sync(0xffffffffu, stale == 0)) break;
                    }
                    asm volatile("st.shared.v4.b32 [%0], {%1,%2,%3,%4};" :: "r"(sb + OFF_RS + lane * 16), "r"(r[0]), "r"(r[1]), "r"(r[2]), "r"(r[3]) : "memory");
                }
                __syncwarp();
                if (elect_one()) { mbar_arrive(bars + 8 * (B_STATS + t)); TSTAMP(32 + t); }
            }
        } else {
            tag = ld_epoch(sc) + 1;
            mbar_wait(bars + 8 * (B_FULL + wq - 1), 0);
#pragma unroll 1
            for (int t = wq - 1; t < 5; t += 2) {
                const __nv_bfloat16* src; int ld;
                if (is_qkv(t)) { src = wqkv + (qt0 + t) * 128 + rank * 64; ld = 3 * DM; }
                else        { src = (rank ? w3 : w1) + unit_of(t) * 64; ld = FF; }
                src += (size_t)(rot * 64 + (lane >> 3)) * ld + (lane & 7) * 8;
                uint4 v[16];
                const uint32_t* w = reinterpret_cast<const uint32_t*>(v);
#pragma unroll
                for (int j = 0; j < 16; j++) v[j] = __ldg(reinterpret_cast<const uint4*>(src + (size_t)j * 4 * ld));
                float c[8];
#pragma unroll
                for (int e = 0; e < 4; e++) {
                    float a = 0.f, b = 0.f;
#pragma unroll
                    for (int j = 0; j < 16; j++) { a += bf_lo(w[4 * j + e]); b += bf_hi(w[4 * j + e]); }
                    c[2 * e] = a; c[2 * e + 1] = b;
                }
#pragma unroll
                for (int n = 4; n > 1; n >>= 1) {
                    const bool up = lane & (4 * n);
#pragma unroll
                    for (int e = 0; e < n; e++) c[e] = (up ? c[e + n] : c[e]) + __shfl_xor_sync(0xffffffffu, up ? c[e] : c[e + n], 4 * n);
                }
                unsigned long long* dst = reinterpret_cast<unsigned long long*>(sc->cs) + ((grp * 5 + t) * 8 + rot) * 128 + rank * 64 + (lane & 7) * 8 + (lane >> 3) * 2;
                st_tagged(dst, __float_as_uint(c[0]), tag); st_tagged(dst + 1, __float_as_uint(c[1]), tag);
                if (lane == 0) TSTAMP(40 + t);
            }
        }
        if (wq == 3) {
#pragma unroll 1
            for (int i = lane; i < 256; i += 32) asm volatile("st.shared.v4.b32 [%0], {%1,%1,%1,%1};" :: "r"(sb + OFF_ONES + i * 16), "r"(0x3F803F80u) : "memory");
#pragma unroll 1
            for (int i = lane; i < 128; i += 32) {
                const bool fx = (FIXED_MASK >> (i >> 4)) & 1;
                const float sc = fx ? M71 : P71;
                uint32_t a = pack_bf16(sc, sc), b = a, c = a;
                if (i & 8) { a = pack_bf16(sc, fx ? 27.0f * M71 : -99.5f * P71); b = pack_bf16(sc, fx ? 0.f : 0.08214f * P71); c = pack_bf16(sc, 0.f); }
                asm volatile("st.shared.v4.b32 [%0], {%1,%2,%3,%4};" :: "r"(sb + OFF_B2 + i * 16), "r"(a), "r"(b), "r"(c), "r"(c) : "memory");
            }
            if (elect_one()) {
#pragma unroll 1
                for (int i = 0; i < 28; i++) { mbar_init(bars + 8 * (B_DN + i), 1); mbar_expect(bars + 8 * (B_DN + i), 24576); }
                mbar_expect(bars + 8 * B_WO, 65536);
#pragma unroll 1
                for (int i = 0; i < 4; i++) mbar_expect(bars + 8 * (B_O + i), 16384);
            }
            fence_async_smem();
            __syncwarp();
            if (elect_one()) mbar_arrive(bars + 8 * B_QKV);
        } else if (wq == 1) {
#pragma unroll 1
            for (int i = 0; i < 3; i++) wait_cnt(sc->cnt + (C_QKV + i * 4 + (head >> 3)) * 8, 16 * tag, 100);
            fence_async_all();
            if (elect_one()) { mbar_arrive(bars + 8 * B_QKV); TSTAMP(29); }
            mbar_wait(bars + 8 * (B_EMPTY + 31), 0);
            const uint8_t* gk = reinterpret_cast<const uint8_t*>(sc->kv + head * 4096);
            const uint8_t* gv = reinterpret_cast<const uint8_t*>(sc->kv + (32 + head) * 4096);
#pragma unroll 1
            for (int c = 0; c < 8; c++) {
                mbar_wait(bars + 8 * (B_EMPTY + 34 + (c & 4) + ((c >> 1) & 1)), 0);
                if (elect_one()) {
                    const uint32_t b = bars + 8 * (B_KV + min(c, 2));
                    if (c <= 2) mbar_expect(b, c < 2 ? 16384 : 6 * 16384);
                    bulk_load(sb + (2 * c + 1) * 4096, gk + c * 4096, 4096, b);
                    bulk_load(sb + 2 * c * 4096, gv + c * 4096, 4096, b);
                    bulk_load(sb + 65536 + c * 4096, gv + 32768 + c * 4096, 4096, b);
                    bulk_load(sb + 98304 + c * 4096, gk + 32768 + c * 4096, 4096, b);
                }
            }
        } else if (wq == 2) {
#pragma unroll 1
            for (int t = 0; t < 5; t++) {
                mbar_wait(bars + 8 * (B_TILE + t), 0);
                if (elect_one()) signal_cnt(sc->cnt + (is_qkv(t) ? C_QKV + qt0 + t : C_H + mblk) * 8);
            }
        }
        pin<1>(&tag);
        bar_sync(5, 128);
        if (tid == 639) sc->epoch[blockIdx.x] = tag;
        uint32_t gate[2][16];
        {
            float dn[64];
#pragma unroll
            for (int i = 0; i < 64; i++) dn[i] = 0.f;
            pin<64>(dn);
            const uint4* hsrc = sc->h + (lid >> 3) * 28 * 1024;
            const int wcol = cb * 64;
            uint32_t nb = bars + 8 * B_DN, kc = 0;
            auto load_stage = [&](int slot) {
                const uint32_t dst = ring + slot * 24576;
                if (wq == 0) { if (elect_one()) bulk_load(dst, hsrc, 16384, nb); }
                if (wq == 1) { if (elect_one()) tma2d(dst + 16384, &mw2, wcol, kc, nb); }
                hsrc += 1024; kc += 64; nb += 8;
            };
            const uint64_t z = OPQ * (uint64_t)(int64_t)(int)(sb & 0xF0000000u) >> 20;
            const uint64_t dw0 = mkdesc(OFF_RING + 16384, 8192, 1024, 1) ^ z, dh0 = mkdesc(OFF_RING, 128, 1024, 0) ^ z;
            auto mma_stage = [&](int slot) {
                mbar_wait(nb - 16, 0);
#pragma unroll
                for (int k = 0; k < 4; k++) {
                    wg_fence();
                    wgmma_ts_n128_acc(dn, dw0 + slot * 1536 + k * 128, dh0 + slot * 1536 + k * 16);
                    wg_commit();
                    wg_wait<1>();
                }
            };
            if (tid == 512) TSTAMP(20);
            load_stage(0); load_stage(1);
#pragma unroll 1
            for (int it = 0; it < 9; it++) {
                mma_stage(0); load_stage(2);
                mma_stage(1); load_stage(0);
                mma_stage(2); if (it < 8) load_stage(1); else nb += 8;
            }
            mma_stage(0);
            wg_wait<0>();
            pin<64>(dn);
            if (wq == 1 && elect_one()) {
#pragma unroll 1
                for (int i = 0; i < 8; i++) tma2d(ring + i * 8192, &mwo, cb * 64, i * 64, bars + 8 * B_WO);
            }
#pragma unroll
            for (int i = 0; i < 32; i++) gate[i >> 4][i & 15] = pack_bf16(siluf(dn[2 * i]), siluf(dn[2 * i + 1]));
        }
        if (tid == 512) TSTAMP(21);
        if (wq >= 2) {
            mbar_wait(bars + 8 * (B_OW + wq - 2), 0);
            if (elect_one()) {
                signal_cnt(sc->cnt + (C_O + qb * 8 + 2 * wq - 4) * 8);
                asm volatile("red.relaxed.gpu.global.add.u32 [%0], 1;" :: "l"(sc->cnt + (C_O + qb * 8 + 2 * wq - 3) * 8) : "memory");
            }
        }
#pragma unroll 1
        for (int tl = 0; tl < 2; tl++) {
            const int rb = rb0 + 4 * tl;
            const size_t goff = (size_t)(rb * 64 + wq * 16 + (lane >> 3)) * (DM / 8) + cb * 8 + (lane & 7);
            uint4 xr[4];
#pragma unroll
            for (int i = 0; i < 4; i++) xr[i] = __ldg(reinterpret_cast<const uint4*>(x) + goff + i * 4 * (DM / 8));
            float acc[32];
#pragma unroll
            for (int i = 0; i < 32; i++) acc[i] = 0.f;
            pin<32>(acc);
            uint64_t dw = mkdesc(OFF_RING, 8192, 1024, 1);
            if (tl == 0) {
                if (wq == 0) {
                    wait_cnt(sc->cnt + (C_O + rb) * 8, 32 * tag, 200);
                    fence_async_all();
                    if (elect_one()) { mbar_arrive(bars + 8 * B_T1); TSTAMP(22); }
                }
                mbar_wait(bars + 8 * B_WO, 0);
#pragma unroll 1
                for (int i = 0; i < 4; i++, dw += 1024) {
                    if (wq == 0 && elect_one()) bulk_load(ring + 65536, sc->o + (rb * 4 + i) * 1024, 16384, bars + 8 * (B_O + i));
                    mbar_wait(bars + 8 * (B_O + i), 0);
#pragma unroll
                    for (int k = 0; k < 8; k++) {
                        if (!(k & 1)) wg_fence();
                        wgmma_ts_n64_acc(acc, dw + k * 128, mkdesc(OFF_RING + 65536, 128, 1024, 0) + (k >> 2) * 512 + (k & 3) * 16);
                        if (k & 1) { wg_commit(); wg_wait<0>(); }
                    }
                }
            } else {
                uint64_t dx = mkdesc(0, 128, 1024, 0);
#pragma unroll 1
                for (int i = 0; i < 8; i++, dx += 512, dw += 512) {
                    mbar_wait(bars + 8 * (B_O2 + i), 0);
                    if (tid == 512) TS3(0, 48 + i);
                    wg_fence();
#pragma unroll
                    for (int k = 0; k < 4; k++) wgmma_ts_n64_acc(acc, dw + k * 128, dx + k * 16);
                    wg_commit();
                }
                wg_wait<0>();
            }
            pin<32>(acc);
            if (tid == 512) TS3(0, 56);
            const uint32_t stg = ring + 65536;
            uint32_t r[16];
#pragma unroll
            for (int i = 0; i < 16; i++) {
                asm("mul.rn.bf16x2 %0, %1, %2;" : "=r"(r[i]) : "r"(pack_bf16(acc[2 * i], acc[2 * i + 1])), "r"(gate[0][i]));
                gate[0][i] = gate[1][i];
            }
#pragma unroll
            for (int i = 0; i < 4; i++)
                asm volatile("stmatrix.sync.aligned.m8n8.x4.trans.shared.b16 [%0], {%1,%2,%3,%4};"
                             :: "r"(stg + (i * 16 + (lane >> 4) * 8 + (lane & 7)) * 128 + (((2 * wq + ((lane >> 3) & 1)) ^ (lane & 7)) << 4)),
                                "r"(r[4 * i]), "r"(r[4 * i + 1]), "r"(r[4 * i + 2]), "r"(r[4 * i + 3]) : "memory");
            bar_sync(5, 128);
#pragma unroll
            for (int i = 0; i < 4; i++) {
                const int row = wq * 16 + i * 4 + (lane >> 3);
                uint4 u;
                asm volatile("ld.shared.v4.b32 {%0,%1,%2,%3}, [%4];" : "=r"(u.x), "=r"(u.y), "=r"(u.z), "=r"(u.w) : "r"(stg + row * 128 + (((lane ^ row) & 7) << 4)) : "memory");
                asm("add.rn.bf16x2 %0, %0, %1;" : "+r"(u.x) : "r"(xr[i].x)); asm("add.rn.bf16x2 %0, %0, %1;" : "+r"(u.y) : "r"(xr[i].y));
                asm("add.rn.bf16x2 %0, %0, %1;" : "+r"(u.z) : "r"(xr[i].z)); asm("add.rn.bf16x2 %0, %0, %1;" : "+r"(u.w) : "r"(xr[i].w));
                reinterpret_cast<uint4*>(out)[goff + i * 4 * (DM / 8)] = u;
            }
            if (tid == 512) TSTAMP(23 + 2 * tl);
            if (tid == 512) GSTAMP(8 + tl);
        }
    }
}

typedef CUresult (*EncodeFn)(CUtensorMap*, CUtensorMapDataType, cuuint32_t, void*, const cuuint64_t*, const cuuint64_t*, const cuuint32_t*,
                             const cuuint32_t*, CUtensorMapInterleave, CUtensorMapSwizzle, CUtensorMapL2promotion, CUtensorMapFloatOOBfill);

void make_map(EncodeFn fn, CUtensorMap* m, const void* p, int rows, int cols, int box_rows) {
    cuuint64_t dims[2] = {(cuuint64_t)cols, (cuuint64_t)rows};
    cuuint64_t strides[1] = {(cuuint64_t)cols * 2};
    cuuint32_t box[2] = {64, (cuuint32_t)box_rows};
    cuuint32_t es[2] = {1, 1};
    fn(m, CU_TENSOR_MAP_DATA_TYPE_BFLOAT16, 2, const_cast<void*>(p), dims, strides, box, es, CU_TENSOR_MAP_INTERLEAVE_NONE,
       CU_TENSOR_MAP_SWIZZLE_128B, CU_TENSOR_MAP_L2_PROMOTION_L2_128B, CU_TENSOR_MAP_FLOAT_OOB_FILL_NONE);
}

}

extern "C" void kernel_launch(void* const* d_in, const int* in_sizes, int n_in, void* d_out, int out_size) {
    const __nv_bfloat16* x = (const __nv_bfloat16*)d_in[0];
    static EncodeFn fn = nullptr;
    static Scratch* scratch = nullptr;
    if (!fn) {
        cudaDriverEntryPointQueryResult qr;
        cudaGetDriverEntryPoint("cuTensorMapEncodeTiled", (void**)&fn, cudaEnableDefault, &qr);
        cudaGetSymbolAddress((void**)&scratch, g_scratch);
        cudaFuncSetAttribute(mega_kernel, cudaFuncAttributeMaxDynamicSharedMemorySize, SMEM_BYTES);
    }
    CUtensorMap mx, mqkv, mw1, mw3, mw2, mwo;
    make_map(fn, &mx, d_in[0], SEQ, DM, 128);
    make_map(fn, &mqkv, d_in[1], DM, 3 * DM, 64);
    make_map(fn, &mwo, d_in[2], DM, DM, 64);
    make_map(fn, &mw1, d_in[4], DM, FF, 64);
    make_map(fn, &mw3, d_in[5], DM, FF, 64);
    make_map(fn, &mw2, d_in[6], FF, DM, 64);
    WorkMap wmap;
    for (int cl = 0; cl < 64; cl++) {
        const int grp = cl < 4 ? 4 + cl : cl < 36 ? (cl - 4) >> 3 : 4 + (cl - 36) / 7;
        const int rot = cl < 4 ? 7 : cl < 36 ? (cl - 4) & 7 : (cl - 36) % 7;
        wmap.v[cl] = rot | grp << 8 | (grp < 4 ? 3 * grp : 4 * grp - 4) << 16 | (int)((unsigned)(grp < 4 ? 2 * grp - 1 : 3 + grp) << 24);
    }
    mega_kernel<<<128, 640, SMEM_BYTES, cudaStreamPerThread>>>(x, (const __nv_bfloat16*)d_in[1], (const __nv_bfloat16*)d_in[4], (const __nv_bfloat16*)d_in[5],
                                                               (__nv_bfloat16*)d_out, scratch, wmap, mx, mqkv, mw1, mw3, mw2, mwo);
}
```
